```python
import torch

def _softmax(x, axis=-1):
    return torch.softmax(x, dim=axis)
def _gelu(x):
    return torch.nn.functional.gelu(x, approximate="tanh")
def _silu(x):
    return torch.nn.functional.silu(x)
def _sigmoid(x):
    return torch.sigmoid(x)
def _layernorm(x, axis=-1, eps=1e-5):
    m = x.mean(dim=axis, keepdim=True)
    v = x.var(dim=axis, keepdim=True, unbiased=False)
    return (x - m) / torch.sqrt(v + eps)
def _scatter_add(tgt, idx, src, axis=0):
    return tgt.clone().index_add_(axis, idx, src)
def _segment_sum(src, seg, n):
    out = torch.zeros((n,) + src.shape[1:], dtype=src.dtype)
    return out.index_add_(0, seg, src)
def _pad(x, pw):
    flat = tuple(v for pair in reversed(pw) for v in pair)
    return torch.nn.functional.pad(x, flat)

kernel_name = 'sequential_preLN__sliding_block__dense_activation_silu__prompt'

def setup_inputs():

    _w = (lambda a: (lambda t: t.to(torch.bfloat16) if t.is_floating_point() else t)(torch.as_tensor(a)))
    def _A_setup():
        B, S, D = 1, 2048, 640
        return {
            "x": _w((lambda *s: torch.randn(*s, dtype=torch.bfloat16) * 0.05)(B, S, D)),
            "wqkv": _w((lambda *s: torch.randn(*s, dtype=torch.bfloat16) * 0.05)(D, 3 * D)),
            "wo": _w((lambda *s: torch.randn(*s, dtype=torch.bfloat16) * 0.05)(D, D)),
        }
    _A_in = _A_setup()

    def _B_setup():
        B, S, D, F = 1, 2048, 640, 1728
        return {
            "x": _w((lambda *s: torch.randn(*s, dtype=torch.bfloat16) * 0.05)(B, S, D)),
            "w1": _w((lambda *s: torch.randn(*s, dtype=torch.bfloat16) * 3.2)(D, F) * (D ** -0.5)),
            "w2": _w((lambda *s: torch.randn(*s, dtype=torch.bfloat16) * 0.4)(F, D) * (F ** -0.5)),
        }
    _B_in = _B_setup()

    return {
        "A_x": _A_in["x"],
        "A_wqkv": _A_in["wqkv"],
        "A_wo": _A_in["wo"],
        "B_x": _B_in["x"],
        "B_w1": _B_in["w1"],
        "B_w2": _B_in["w2"],
    }

def reference(A_x, A_wqkv, A_wo, B_x, B_w1, B_w2):
    def _A_ref(x, wqkv, wo):
        B, S, D = x.shape
        H = 32; Dh = D // H; W = 256
        qkv = (lambda x, *d: x.permute(*d))((x @ wqkv).reshape(B, S, 3, H, Dh), 2, 0, 3, 1, 4)
        q, k, v = qkv[0], qkv[1], qkv[2]
        scores = torch.einsum("bhqd,bhkd->bhqk", q, k) * (Dh ** -0.5)
        idx = torch.arange(S)
        mask = (idx[:, None] - idx[None, :] >= 0) & (idx[:, None] - idx[None, :] < W)
        scores = torch.where(mask[None, None], scores, -1e9)
        p = _softmax(scores, axis=-1)
        o = torch.einsum("bhqk,bhkd->bhqd", p, v)
        return (lambda x, *d: x.permute(*d))(o, 0, 2, 1, 3).reshape(B, S, D) @ wo

    def _B_ref(x, w1, w2):
        h = torch.einsum("bsd,df->bsf", x, w1)
        h = _silu(h)
        out = torch.einsum("bsf,fd->bsd", h, w2)
        return out

    x = A_x
    h = x + _A_ref(_layernorm(x, axis=-1), A_wqkv, A_wo)
    h2 = h + _B_ref(_layernorm(h, axis=-1), B_w1, B_w2)
    return h2
```

```cpp
#include <cuda_runtime.h>
#include <cuda.h>
#include <cuda_bf16.h>
#include <stdint.h>

#define PROF 0

__device__ __align__(1024) uint8_t g_kv[32 * 8 * 22528];
__device__ __align__(1024) uint8_t g_o[32 * 8 * 10240];
__device__ __align__(1024) uint8_t g_h[32 * 8 * 10240];
__device__ __align__(1024) float2 g_hstat[32 * 8 * 64];
__device__ __align__(1024) uint8_t g_part[32 * 8 * 8 * 8192];
__device__ __align__(1024) uint8_t g_p89[32 * 4 * 8 * 4096];
__device__ __align__(128) float2 g_xstat[2048];
__device__ __align__(128) float g_csq[16 * 8 * 240];
__device__ __align__(128) float g_cs1[16 * 8 * 224];
enum { F_KV = 0, F_O = 256, F_H = 512, F_P89 = 768, F_XS = 1024, F_CSQ = 1280, F_CS1 = 1408, F_PART = 1536, F_TOTAL = 1536 + 2048 };
__device__ __align__(128) uint32_t g_flags[F_TOTAL];
__device__ __align__(128) uint32_t g_epoch[128];
#define STAMP(slot)
#define STAMPW(slot)

struct Params {
  CUtensorMap mX, mWqM, mWqL, mWo, mW1a, mW1b, mW2;
  const __nv_bfloat16 *x, *wqkv, *wo, *w1, *w2;
  __nv_bfloat16* out;
};

constexpr uint32_t QST = 47104;
constexpr uint32_t KVB = 22528;
constexpr uint32_t OFF_WOB = 0;
constexpr uint32_t OFF_SPARE = 107520;
constexpr uint32_t OFF_B0 = 111616;
constexpr uint32_t OFF_A = 147456;
constexpr uint32_t W2SLOT = 57344;
constexpr uint32_t OFF_MISC = 229376;
constexpr uint32_t OFF_CS = OFF_MISC + 512;
constexpr uint32_t OFF_XS = OFF_CS + 960;
constexpr uint32_t SMEM_BYTES = 232448;

enum {
  B_QFULL = 0, B_QEMPTY = 4, B_KVOWN = 8, B_KVFULL = 10, B_WOB = 14, B_ATTL = 15, B_ATTP = 16, B_OSTG = 17, B_OSD = 19,
  B_HSTG = 21, B_AFULL = 23, B_AEMPTY = 29, B_WODP = 35, B_BFULL = 36, B_BEMPTY = 40, B_W2FULL = 44, B_W2E = 49,
  B_PSTG = 50, B_STAT = 60, B_CS1 = 61, B_WOB7 = 62, B_Q23 = 63, NBAR = 64
};

__device__ __forceinline__ uint32_t s2u(const void* p) { return (uint32_t)__cvta_generic_to_shared(p); }
__device__ __forceinline__ void mbar_init(uint32_t b, int c) { asm volatile("mbarrier.init.shared::cta.b64 [%0], %1;" ::"r"(b), "r"(c)); }
__device__ __forceinline__ void mbar_expect(uint32_t b, int bytes) { asm volatile("mbarrier.arrive.expect_tx.shared::cta.b64 _, [%0], %1;" ::"r"(b), "r"(bytes) : "memory"); }
__device__ __forceinline__ void mbar_arrive(uint32_t b) { asm volatile("mbarrier.arrive.shared::cta.b64 _, [%0];" ::"r"(b) : "memory"); }
__device__ __forceinline__ void mbar_arrive_pair(uint32_t b) {
  asm volatile("{\n.reg .b32 r;\nmapa.shared::cluster.u32 r, %0, 0;\nmbarrier.arrive.shared::cluster.b64 _, [r];\n"
               "mapa.shared::cluster.u32 r, %0, 1;\nmbarrier.arrive.shared::cluster.b64 _, [r];\n}" ::"r"(b) : "memory");
}
__device__ __forceinline__ bool mbar_try(uint32_t b, uint32_t ph) {
  uint32_t ok;
  asm volatile("{\n.reg .pred p;\nmbarrier.try_wait.parity.shared::cta.b64 p, [%1], %2;\nselp.u32 %0, 1, 0, p;\n}" : "=r"(ok) : "r"(b), "r"(ph) : "memory");
  return ok != 0;
}
__device__ __forceinline__ void mbar_wait(uint32_t b, uint32_t ph) {
  if (mbar_try(b, ph)) return;
  const long long t0 = clock64();
  while (!mbar_try(b, ph)) { if (clock64() - t0 > 100000000LL) break; }
}
__device__ __forceinline__ void tma2d(uint32_t dst, const CUtensorMap* m, int c0, int c1, uint32_t bar) {
  asm volatile("cp.async.bulk.tensor.2d.shared::cluster.global.mbarrier::complete_tx::bytes [%0], [%1, {%3, %4}], [%2];" ::"r"(dst), "l"(m), "r"(bar), "r"(c0), "r"(c1) : "memory");
}
__device__ __forceinline__ void tma2d_mc(uint32_t dst, const CUtensorMap* m, int c0, int c1, uint32_t bar) {
  asm volatile("cp.async.bulk.tensor.2d.shared::cluster.global.mbarrier::complete_tx::bytes.multicast::cluster [%0], [%1, {%3, %4}], [%2], %5;" ::"r"(dst), "l"(m), "r"(bar), "r"(c0), "r"(c1), "h"((uint16_t)3) : "memory");
}
__device__ __forceinline__ void tma3d_mc(uint32_t dst, const CUtensorMap* m, int c0, int c1, int c2, uint32_t bar) {
  asm volatile("cp.async.bulk.tensor.3d.shared::cluster.global.mbarrier::complete_tx::bytes.multicast::cluster [%0], [%1, {%3, %4, %5}], [%2], %6;" ::"r"(dst), "l"(m), "r"(bar), "r"(c0), "r"(c1), "r"(c2), "h"((uint16_t)3) : "memory");
}
__device__ __forceinline__ void tma4d_mc(uint32_t dst, const CUtensorMap* m, int c0, int c1, int c2, int c3, uint32_t bar) {
  asm volatile("cp.async.bulk.tensor.4d.shared::cluster.global.mbarrier::complete_tx::bytes.multicast::cluster [%0], [%1, {%3, %4, %5, %6}], [%2], %7;" ::"r"(dst), "l"(m), "r"(bar), "r"(c0), "r"(c1), "r"(c2), "r"(c3), "h"((uint16_t)3) : "memory");
}
__device__ __forceinline__ void bulk_load(uint32_t dst, const void* src, int bytes, uint32_t bar) {
  asm volatile("cp.async.bulk.shared::cluster.global.mbarrier::complete_tx::bytes [%0], [%1], %2, [%3];" ::"r"(dst), "l"(src), "r"(bytes), "r"(bar) : "memory");
}
__device__ __forceinline__ void bulk_store(void* dst, uint32_t src, int bytes) {
  asm volatile("cp.async.bulk.global.shared::cta.bulk_group [%0], [%1], %2;" ::"l"(dst), "r"(src), "r"(bytes) : "memory");
}
__device__ __forceinline__ void bulk_commit_wait() {
  asm volatile("cp.async.bulk.commit_group;\ncp.async.bulk.wait_group 0;" ::: "memory");
}
__device__ __forceinline__ void l2_prefetch_bulk(const void* p, int bytes) { asm volatile("cp.async.bulk.prefetch.L2.global [%0], %1;" ::"l"(p), "r"(bytes) : "memory"); }
__device__ __forceinline__ void l2_prefetch(const void* p) { asm volatile("prefetch.global.L2 [%0];" ::"l"(p)); }
__device__ __forceinline__ uint32_t ld_flag(const uint32_t* p) { uint32_t v; asm volatile("ld.acquire.gpu.global.u32 %0, [%1];" : "=r"(v) : "l"(p) : "memory"); return v; }
__device__ __forceinline__ void st_flag(uint32_t* p, uint32_t v) { asm volatile("st.relaxed.gpu.global.u32 [%0], %1;" ::"l"(p), "r"(v) : "memory"); }
__device__ __forceinline__ void fence_gpu() { asm volatile("fence.acq_rel.gpu;" ::: "memory"); }
__device__ __forceinline__ void fence_async_smem() { asm volatile("fence.proxy.async.shared::cta;" ::: "memory"); }
__device__ __forceinline__ void fence_async_glob() { asm volatile("fence.proxy.async.global;" ::: "memory"); }
__device__ __forceinline__ uint4 ldcg128(const void* p) { uint4 v; asm volatile("ld.relaxed.gpu.global.v4.u32 {%0,%1,%2,%3}, [%4];" : "=r"(v.x), "=r"(v.y), "=r"(v.z), "=r"(v.w) : "l"(p) : "memory"); return v; }
__device__ __forceinline__ uint2 ldcg64(const void* p) { uint2 v; asm volatile("ld.relaxed.gpu.global.v2.u32 {%0,%1}, [%2];" : "=r"(v.x), "=r"(v.y) : "l"(p) : "memory"); return v; }
__device__ __forceinline__ uint32_t ldcg32(const void* p) { uint32_t v; asm volatile("ld.relaxed.gpu.global.u32 %0, [%1];" : "=r"(v) : "l"(p) : "memory"); return v; }
__device__ __forceinline__ uint32_t pack2(float lo, float hi) { uint32_t r; asm("cvt.rn.bf16x2.f32 %0, %1, %2;" : "=r"(r) : "f"(hi), "f"(lo)); return r; }
__device__ __forceinline__ float bf_lo(uint32_t v) { return __uint_as_float(v << 16); }
__device__ __forceinline__ float bf_hi(uint32_t v) { return __uint_as_float(v & 0xffff0000u); }
__device__ __forceinline__ float ex2(float x) { float y; asm("ex2.approx.ftz.f32 %0, %1;" : "=f"(y) : "f"(x)); return y; }
__device__ __forceinline__ float tanh_fast(float x) { float y; asm("tanh.approx.f32 %0, %1;" : "=f"(y) : "f"(x)); return y; }
__device__ __forceinline__ void stsm4(uint32_t a, uint32_t r0, uint32_t r1, uint32_t r2, uint32_t r3) {
  asm volatile("stmatrix.sync.aligned.m8n8.x4.shared.b16 [%0], {%1,%2,%3,%4};" ::"r"(a), "r"(r0), "r"(r1), "r"(r2), "r"(r3) : "memory");
}
__device__ __forceinline__ float2 lds64f(uint32_t a) { float2 v; asm volatile("ld.shared.v2.f32 {%0,%1}, [%2];" : "=f"(v.x), "=f"(v.y) : "r"(a)); return v; }
__device__ __forceinline__ constexpr uint64_t desc_hi(uint32_t lbo, uint32_t sbo, uint32_t sw) {
  return ((uint64_t)(lbo >> 4) << 16) | ((uint64_t)(sbo >> 4) << 32) | ((uint64_t)sw << 62);
}
__device__ __forceinline__ uint64_t mkdesc(uint32_t addr, uint64_t hi) { return hi | (uint64_t)((addr & 0x3FFFF) >> 4); }
#define WG_FENCE() asm volatile("wgmma.fence.sync.aligned;" ::: "memory")
#define WG_COMMIT() asm volatile("wgmma.commit_group.sync.aligned;" ::: "memory")
#define WG_WAIT(n) asm volatile("wgmma.wait_group.sync.aligned " #n ";" ::: "memory")
template <int N> __device__ __forceinline__ void reg_fence(float (&a)[N]) {
#pragma unroll
  for (int i = 0; i < N; i++) asm volatile("" : "+f"(a[i])::"memory");
}

__device__ __forceinline__ void wg_ss192(float (&d)[96], uint64_t da, uint64_t db, int sd) {
  asm volatile("{\n.reg .pred p;\nsetp.ne.b32 p, %98, 0;\n"
  "wgmma.mma_async.sync.aligned.m64n192k16.f32.bf16.bf16 {%0, %1, %2, %3, %4, %5, %6, %7, %8, %9, %10, %11, %12, %13, %14, %15, %16, %17, %18, %19, %20, %21, %22, %23, %24, %25, %26, %27, %28, %29, %30, %31, %32, %33, %34, %35, %36, %37, %38, %39, %40, %41, %42, %43, %44, %45, %46, %47, %48, %49, %50, %51, %52, %53, %54, %55, %56, %57, %58, %59, %60, %61, %62, %63, %64, %65, %66, %67, %68, %69, %70, %71, %72, %73, %74, %75, %76, %77, %78, %79, %80, %81, %82, %83, %84, %85, %86, %87, %88, %89, %90, %91, %92, %93, %94, %95}, %96, %97, p, 1, 1, 0, 1;\n}\n"
  : "+f"(d[0]), "+f"(d[1]), "+f"(d[2]), "+f"(d[3]), "+f"(d[4]), "+f"(d[5]), "+f"(d[6]), "+f"(d[7]), "+f"(d[8]), "+f"(d[9]), "+f"(d[10]), "+f"(d[11]), "+f"(d[12]), "+f"(d[13]), "+f"(d[14]), "+f"(d[15]), "+f"(d[16]), "+f"(d[17]), "+f"(d[18]), "+f"(d[19]), "+f"(d[20]), "+f"(d[21]), "+f"(d[22]), "+f"(d[23]), "+f"(d[24]), "+f"(d[25]), "+f"(d[26]), "+f"(d[27]), "+f"(d[28]), "+f"(d[29]), "+f"(d[30]), "+f"(d[31]), "+f"(d[32]), "+f"(d[33]), "+f"(d[34]), "+f"(d[35]), "+f"(d[36]), "+f"(d[37]), "+f"(d[38]), "+f"(d[39]), "+f"(d[40]), "+f"(d[41]), "+f"(d[42]), "+f"(d[43]), "+f"(d[44]), "+f"(d[45]), "+f"(d[46]), "+f"(d[47]), "+f"(d[48]), "+f"(d[49]), "+f"(d[50]), "+f"(d[51]), "+f"(d[52]), "+f"(d[53]), "+f"(d[54]), "+f"(d[55]), "+f"(d[56]), "+f"(d[57]), "+f"(d[58]), "+f"(d[59]), "+f"(d[60]), "+f"(d[61]), "+f"(d[62]), "+f"(d[63]), "+f"(d[64]), "+f"(d[65]), "+f"(d[66]), "+f"(d[67]), "+f"(d[68]), "+f"(d[69]), "+f"(d[70]), "+f"(d[71]), "+f"(d[72]), "+f"(d[73]), "+f"(d[74]), "+f"(d[75]), "+f"(d[76]), "+f"(d[77]), "+f"(d[78]), "+f"(d[79]), "+f"(d[80]), "+f"(d[81]), "+f"(d[82]), "+f"(d[83]), "+f"(d[84]), "+f"(d[85]), "+f"(d[86]), "+f"(d[87]), "+f"(d[88]), "+f"(d[89]), "+f"(d[90]), "+f"(d[91]), "+f"(d[92]), "+f"(d[93]), "+f"(d[94]), "+f"(d[95]) : "l"(da), "l"(db), "r"(sd));
}
__device__ __forceinline__ void wg_ss48(float (&d)[24], uint64_t da, uint64_t db, int sd) {
  asm volatile("{\n.reg .pred p;\nsetp.ne.b32 p, %26, 0;\n"
  "wgmma.mma_async.sync.aligned.m64n48k16.f32.bf16.bf16 {%0, %1, %2, %3, %4, %5, %6, %7, %8, %9, %10, %11, %12, %13, %14, %15, %16, %17, %18, %19, %20, %21, %22, %23}, %24, %25, p, 1, 1, 0, 1;\n}\n"
  : "+f"(d[0]), "+f"(d[1]), "+f"(d[2]), "+f"(d[3]), "+f"(d[4]), "+f"(d[5]), "+f"(d[6]), "+f"(d[7]), "+f"(d[8]), "+f"(d[9]), "+f"(d[10]), "+f"(d[11]), "+f"(d[12]), "+f"(d[13]), "+f"(d[14]), "+f"(d[15]), "+f"(d[16]), "+f"(d[17]), "+f"(d[18]), "+f"(d[19]), "+f"(d[20]), "+f"(d[21]), "+f"(d[22]), "+f"(d[23]) : "l"(da), "l"(db), "r"(sd));
}
__device__ __forceinline__ void wg_ss80(float (&d)[40], uint64_t da, uint64_t db, int sd) {
  asm volatile("{\n.reg .pred p;\nsetp.ne.b32 p, %42, 0;\n"
  "wgmma.mma_async.sync.aligned.m64n80k16.f32.bf16.bf16 {%0, %1, %2, %3, %4, %5, %6, %7, %8, %9, %10, %11, %12, %13, %14, %15, %16, %17, %18, %19, %20, %21, %22, %23, %24, %25, %26, %27, %28, %29, %30, %31, %32, %33, %34, %35, %36, %37, %38, %39}, %40, %41, p, 1, 1, 0, 1;\n}\n"
  : "+f"(d[0]), "+f"(d[1]), "+f"(d[2]), "+f"(d[3]), "+f"(d[4]), "+f"(d[5]), "+f"(d[6]), "+f"(d[7]), "+f"(d[8]), "+f"(d[9]), "+f"(d[10]), "+f"(d[11]), "+f"(d[12]), "+f"(d[13]), "+f"(d[14]), "+f"(d[15]), "+f"(d[16]), "+f"(d[17]), "+f"(d[18]), "+f"(d[19]), "+f"(d[20]), "+f"(d[21]), "+f"(d[22]), "+f"(d[23]), "+f"(d[24]), "+f"(d[25]), "+f"(d[26]), "+f"(d[27]), "+f"(d[28]), "+f"(d[29]), "+f"(d[30]), "+f"(d[31]), "+f"(d[32]), "+f"(d[33]), "+f"(d[34]), "+f"(d[35]), "+f"(d[36]), "+f"(d[37]), "+f"(d[38]), "+f"(d[39]) : "l"(da), "l"(db), "r"(sd));
}
__device__ __forceinline__ void wg_ss224(float (&d)[112], uint64_t da, uint64_t db, int sd) {
  asm volatile("{\n.reg .pred p;\nsetp.ne.b32 p, %114, 0;\n"
  "wgmma.mma_async.sync.aligned.m64n224k16.f32.bf16.bf16 {%0, %1, %2, %3, %4, %5, %6, %7, %8, %9, %10, %11, %12, %13, %14, %15, %16, %17, %18, %19, %20, %21, %22, %23, %24, %25, %26, %27, %28, %29, %30, %31, %32, %33, %34, %35, %36, %37, %38, %39, %40, %41, %42, %43, %44, %45, %46, %47, %48, %49, %50, %51, %52, %53, %54, %55, %56, %57, %58, %59, %60, %61, %62, %63, %64, %65, %66, %67, %68, %69, %70, %71, %72, %73, %74, %75, %76, %77, %78, %79, %80, %81, %82, %83, %84, %85, %86, %87, %88, %89, %90, %91, %92, %93, %94, %95, %96, %97, %98, %99, %100, %101, %102, %103, %104, %105, %106, %107, %108, %109, %110, %111}, %112, %113, p, 1, 1, 0, 1;\n}\n"
  : "+f"(d[0]), "+f"(d[1]), "+f"(d[2]), "+f"(d[3]), "+f"(d[4]), "+f"(d[5]), "+f"(d[6]), "+f"(d[7]), "+f"(d[8]), "+f"(d[9]), "+f"(d[10]), "+f"(d[11]), "+f"(d[12]), "+f"(d[13]), "+f"(d[14]), "+f"(d[15]), "+f"(d[16]), "+f"(d[17]), "+f"(d[18]), "+f"(d[19]), "+f"(d[20]), "+f"(d[21]), "+f"(d[22]), "+f"(d[23]), "+f"(d[24]), "+f"(d[25]), "+f"(d[26]), "+f"(d[27]), "+f"(d[28]), "+f"(d[29]), "+f"(d[30]), "+f"(d[31]), "+f"(d[32]), "+f"(d[33]), "+f"(d[34]), "+f"(d[35]), "+f"(d[36]), "+f"(d[37]), "+f"(d[38]), "+f"(d[39]), "+f"(d[40]), "+f"(d[41]), "+f"(d[42]), "+f"(d[43]), "+f"(d[44]), "+f"(d[45]), "+f"(d[46]), "+f"(d[47]), "+f"(d[48]), "+f"(d[49]), "+f"(d[50]), "+f"(d[51]), "+f"(d[52]), "+f"(d[53]), "+f"(d[54]), "+f"(d[55]), "+f"(d[56]), "+f"(d[57]), "+f"(d[58]), "+f"(d[59]), "+f"(d[60]), "+f"(d[61]), "+f"(d[62]), "+f"(d[63]), "+f"(d[64]), "+f"(d[65]), "+f"(d[66]), "+f"(d[67]), "+f"(d[68]), "+f"(d[69]), "+f"(d[70]), "+f"(d[71]), "+f"(d[72]), "+f"(d[73]), "+f"(d[74]), "+f"(d[75]), "+f"(d[76]), "+f"(d[77]), "+f"(d[78]), "+f"(d[79]), "+f"(d[80]), "+f"(d[81]), "+f"(d[82]), "+f"(d[83]), "+f"(d[84]), "+f"(d[85]), "+f"(d[86]), "+f"(d[87]), "+f"(d[88]), "+f"(d[89]), "+f"(d[90]), "+f"(d[91]), "+f"(d[92]), "+f"(d[93]), "+f"(d[94]), "+f"(d[95]), "+f"(d[96]), "+f"(d[97]), "+f"(d[98]), "+f"(d[99]), "+f"(d[100]), "+f"(d[101]), "+f"(d[102]), "+f"(d[103]), "+f"(d[104]), "+f"(d[105]), "+f"(d[106]), "+f"(d[107]), "+f"(d[108]), "+f"(d[109]), "+f"(d[110]), "+f"(d[111]) : "l"(da), "l"(db), "r"(sd));
}
__device__ __forceinline__ void wg_rs64k(float (&d)[32], uint32_t a0, uint32_t a1, uint32_t a2, uint32_t a3, uint64_t db, int sd) {
  asm volatile("{\n.reg .pred p;\nsetp.ne.b32 p, %37, 0;\n"
  "wgmma.mma_async.sync.aligned.m64n64k16.f32.bf16.bf16 {%0, %1, %2, %3, %4, %5, %6, %7, %8, %9, %10, %11, %12, %13, %14, %15, %16, %17, %18, %19, %20, %21, %22, %23, %24, %25, %26, %27, %28, %29, %30, %31}, {%32, %33, %34, %35}, %36, p, 1, 1, 0;\n}\n"
  : "+f"(d[0]), "+f"(d[1]), "+f"(d[2]), "+f"(d[3]), "+f"(d[4]), "+f"(d[5]), "+f"(d[6]), "+f"(d[7]), "+f"(d[8]), "+f"(d[9]), "+f"(d[10]), "+f"(d[11]), "+f"(d[12]), "+f"(d[13]), "+f"(d[14]), "+f"(d[15]), "+f"(d[16]), "+f"(d[17]), "+f"(d[18]), "+f"(d[19]), "+f"(d[20]), "+f"(d[21]), "+f"(d[22]), "+f"(d[23]), "+f"(d[24]), "+f"(d[25]), "+f"(d[26]), "+f"(d[27]), "+f"(d[28]), "+f"(d[29]), "+f"(d[30]), "+f"(d[31]) : "r"(a0), "r"(a1), "r"(a2), "r"(a3), "l"(db), "r"(sd));
}
__device__ __forceinline__ void wg_rs24(float (&d)[12], uint32_t a0, uint32_t a1, uint32_t a2, uint32_t a3, uint64_t db, int sd) {
  asm volatile("{\n.reg .pred p;\nsetp.ne.b32 p, %17, 0;\n"
  "wgmma.mma_async.sync.aligned.m64n24k16.f32.bf16.bf16 {%0, %1, %2, %3, %4, %5, %6, %7, %8, %9, %10, %11}, {%12, %13, %14, %15}, %16, p, 1, 1, 1;\n}\n"
  : "+f"(d[0]), "+f"(d[1]), "+f"(d[2]), "+f"(d[3]), "+f"(d[4]), "+f"(d[5]), "+f"(d[6]), "+f"(d[7]), "+f"(d[8]), "+f"(d[9]), "+f"(d[10]), "+f"(d[11]) : "r"(a0), "r"(a1), "r"(a2), "r"(a3), "l"(db), "r"(sd));
}
__device__ __forceinline__ void wg_rs128(float (&d)[64], uint32_t a0, uint32_t a1, uint32_t a2, uint32_t a3, uint64_t db, int sd) {
  asm volatile("{\n.reg .pred p;\nsetp.ne.b32 p, %69, 0;\n"
  "wgmma.mma_async.sync.aligned.m64n128k16.f32.bf16.bf16 {%0, %1, %2, %3, %4, %5, %6, %7, %8, %9, %10, %11, %12, %13, %14, %15, %16, %17, %18, %19, %20, %21, %22, %23, %24, %25, %26, %27, %28, %29, %30, %31, %32, %33, %34, %35, %36, %37, %38, %39, %40, %41, %42, %43, %44, %45, %46, %47, %48, %49, %50, %51, %52, %53, %54, %55, %56, %57, %58, %59, %60, %61, %62, %63}, {%64, %65, %66, %67}, %68, p, 1, 1, 1;\n}\n"
  : "+f"(d[0]), "+f"(d[1]), "+f"(d[2]), "+f"(d[3]), "+f"(d[4]), "+f"(d[5]), "+f"(d[6]), "+f"(d[7]), "+f"(d[8]), "+f"(d[9]), "+f"(d[10]), "+f"(d[11]), "+f"(d[12]), "+f"(d[13]), "+f"(d[14]), "+f"(d[15]), "+f"(d[16]), "+f"(d[17]), "+f"(d[18]), "+f"(d[19]), "+f"(d[20]), "+f"(d[21]), "+f"(d[22]), "+f"(d[23]), "+f"(d[24]), "+f"(d[25]), "+f"(d[26]), "+f"(d[27]), "+f"(d[28]), "+f"(d[29]), "+f"(d[30]), "+f"(d[31]), "+f"(d[32]), "+f"(d[33]), "+f"(d[34]), "+f"(d[35]), "+f"(d[36]), "+f"(d[37]), "+f"(d[38]), "+f"(d[39]), "+f"(d[40]), "+f"(d[41]), "+f"(d[42]), "+f"(d[43]), "+f"(d[44]), "+f"(d[45]), "+f"(d[46]), "+f"(d[47]), "+f"(d[48]), "+f"(d[49]), "+f"(d[50]), "+f"(d[51]), "+f"(d[52]), "+f"(d[53]), "+f"(d[54]), "+f"(d[55]), "+f"(d[56]), "+f"(d[57]), "+f"(d[58]), "+f"(d[59]), "+f"(d[60]), "+f"(d[61]), "+f"(d[62]), "+f"(d[63]) : "r"(a0), "r"(a1), "r"(a2), "r"(a3), "l"(db), "r"(sd));
}
__device__ __forceinline__ void wg_rs64(float (&d)[32], uint32_t a0, uint32_t a1, uint32_t a2, uint32_t a3, uint64_t db, int sd) {
  asm volatile("{\n.reg .pred p;\nsetp.ne.b32 p, %37, 0;\n"
  "wgmma.mma_async.sync.aligned.m64n64k16.f32.bf16.bf16 {%0, %1, %2, %3, %4, %5, %6, %7, %8, %9, %10, %11, %12, %13, %14, %15, %16, %17, %18, %19, %20, %21, %22, %23, %24, %25, %26, %27, %28, %29, %30, %31}, {%32, %33, %34, %35}, %36, p, 1, 1, 1;\n}\n"
  : "+f"(d[0]), "+f"(d[1]), "+f"(d[2]), "+f"(d[3]), "+f"(d[4]), "+f"(d[5]), "+f"(d[6]), "+f"(d[7]), "+f"(d[8]), "+f"(d[9]), "+f"(d[10]), "+f"(d[11]), "+f"(d[12]), "+f"(d[13]), "+f"(d[14]), "+f"(d[15]), "+f"(d[16]), "+f"(d[17]), "+f"(d[18]), "+f"(d[19]), "+f"(d[20]), "+f"(d[21]), "+f"(d[22]), "+f"(d[23]), "+f"(d[24]), "+f"(d[25]), "+f"(d[26]), "+f"(d[27]), "+f"(d[28]), "+f"(d[29]), "+f"(d[30]), "+f"(d[31]) : "r"(a0), "r"(a1), "r"(a2), "r"(a3), "l"(db), "r"(sd));
}

__device__ __forceinline__ void poll_all(const uint32_t* p, bool need, uint32_t epoch) {
  uint32_t n = 0;
  while (true) {
    bool ok = !need || ld_flag(p) == epoch;
    if (__all_sync(0xffffffffu, ok)) break;
    if (++n > (1u << 20)) break;
  }
}
__device__ __forceinline__ int korder(int i, int c) { return i == 0 ? c : (i - 1 < c ? i - 1 : i); }
__device__ __forceinline__ uint32_t ring_addr(int idx) {
  return OFF_A + 10240u * (uint32_t)((0x275143u >> (4 * idx)) & 15u);
}
__device__ __forceinline__ uint32_t kv_addr(int i) {
  return 94208u + KVB * (uint32_t)((0x541032u >> (4 * i)) & 15u);
}
__device__ __forceinline__ uint32_t w1b_addr(int slot) { return slot == 0 ? OFF_B0 : (uint32_t)(slot - 1) * 35840u; }

template <int H>
__device__ __forceinline__ void qk_issue(float (&s)[32], const uint32_t (&q)[24], uint32_t kb) {
  constexpr uint64_t HI = desc_hi(1024, 128, 0);
  constexpr int J0 = (H == 0) ? 0 : (H == 1) ? 2 : (H == 2) ? 5 : 7;
  wg_rs64k(s, q[H * 6 + 0], q[H * 6 + 1], q[H * 6 + 2], q[H * 6 + 3], mkdesc(kb + J0 * 1024, HI), 0);
  wg_rs64k(s, q[H * 6 + 4], q[H * 6 + 5], 0u, 0u, mkdesc(kb + (J0 + 2) * 1024, HI), 1);
}
template <int H>
__device__ __forceinline__ void pv_issue(float (&o)[12], const uint32_t (&p)[16], uint32_t kb) {
  constexpr uint64_t HI = desc_hi(128, 1024, 0);
  constexpr int J0 = 3 * H;
#pragma unroll
  for (int i = 0; i < 4; i++)
    wg_rs24(o, p[4 * i], p[4 * i + 1], p[4 * i + 2], p[4 * i + 3], mkdesc(kb + 10240 + J0 * 1024 + i * 256, HI), 1);
}
__device__ __forceinline__ void softmax_chunk(float (&s)[32], uint32_t (&p)[16], float (&o)[12], float (&m)[2]) {
  float a0 = fmaxf(s[0], s[1]), a1 = fmaxf(s[2], s[3]), b0 = fmaxf(s[4], s[5]), b1 = fmaxf(s[6], s[7]);
#pragma unroll
  for (int t = 2; t < 8; t += 2) {
    a0 = fmaxf(a0, fmaxf(s[4 * t], s[4 * t + 1]));
    a1 = fmaxf(a1, fmaxf(s[4 * t + 2], s[4 * t + 3]));
    b0 = fmaxf(b0, fmaxf(s[4 * t + 4], s[4 * t + 5]));
    b1 = fmaxf(b1, fmaxf(s[4 * t + 6], s[4 * t + 7]));
  }
  a0 = fmaxf(a0, b0);
  a1 = fmaxf(a1, b1);
  a0 = fmaxf(a0, __shfl_xor_sync(0xffffffffu, a0, 1));
  a1 = fmaxf(a1, __shfl_xor_sync(0xffffffffu, a1, 1));
  a0 = fmaxf(a0, __shfl_xor_sync(0xffffffffu, a0, 2));
  a1 = fmaxf(a1, __shfl_xor_sync(0xffffffffu, a1, 2));
  float n0 = fmaxf(m[0], a0), n1 = fmaxf(m[1], a1);
  float al0 = ex2(m[0] - n0), al1 = ex2(m[1] - n1);
  m[0] = n0;
  m[1] = n1;
#pragma unroll
  for (int t = 0; t < 8; t++) {
    float e0 = ex2(s[4 * t] - n0), e1 = ex2(s[4 * t + 1] - n0), e2 = ex2(s[4 * t + 2] - n1), e3 = ex2(s[4 * t + 3] - n1);
    p[2 * t] = pack2(e0, e1);
    p[2 * t + 1] = pack2(e2, e3);
  }
#pragma unroll
  for (int t = 0; t < 3; t++) {
    o[4 * t] *= al0; o[4 * t + 1] *= al0; o[4 * t + 2] *= al1; o[4 * t + 3] *= al1;
  }
}
template <int H>
__device__ __forceinline__ void comb_task(float (&s0)[32], float (&s1)[32], uint32_t (&p0)[16], uint32_t (&p1)[16], const uint32_t (&q)[24],
                                          float (&o)[12], float (&m)[2], uint32_t kd, uint32_t ka, bool anti, int dthr) {
  asm volatile("" : "+r"(dthr));
  WG_FENCE();
  qk_issue<H>(s0, q, kd);
  qk_issue<H>(s1, q, ka);
  WG_COMMIT();
  WG_WAIT(0);
  reg_fence(s0); reg_fence(s1); reg_fence(o);
  if (!anti) {
#pragma unroll
    for (int i = 0; i < 32; i++) asm volatile("mov.b32 %0, 0xff800000;" : "=f"(s1[i]));
  }
#pragma unroll
  for (int t = 0; t < 8; t++) {
    s0[4 * t + 0] = (8 * t + 0 <= dthr) ? s0[4 * t + 0] : s1[4 * t + 0];
    s0[4 * t + 1] = (8 * t + 1 <= dthr) ? s0[4 * t + 1] : s1[4 * t + 1];
    s0[4 * t + 2] = (8 * t - 8 <= dthr) ? s0[4 * t + 2] : s1[4 * t + 2];
    s0[4 * t + 3] = (8 * t - 7 <= dthr) ? s0[4 * t + 3] : s1[4 * t + 3];
  }
  softmax_chunk(s0, p0, o, m);
#pragma unroll
  for (int t = 0; t < 8; t++) {
    uint32_t k0 = (8 * t + 1 <= dthr) ? 0xffffffffu : ((8 * t <= dthr) ? 0x0000ffffu : 0u);
    uint32_t k1 = (8 * t - 7 <= dthr) ? 0xffffffffu : ((8 * t - 8 <= dthr) ? 0x0000ffffu : 0u);
    p1[2 * t] = p0[2 * t] & ~k0;
    p0[2 * t] &= k0;
    p1[2 * t + 1] = p0[2 * t + 1] & ~k1;
    p0[2 * t + 1] &= k1;
  }
  WG_FENCE();
  pv_issue<H>(o, p0, kd);
  pv_issue<H>(o, p1, ka);
  WG_COMMIT();
}

__device__ __forceinline__ void store_partial64(const float* a, uint8_t* dst) {
#pragma unroll
  for (int i = 0; i < 4; i++) {
    uint4 v;
    v.x = pack2(a[8 * i + 0], a[8 * i + 1]);
    v.y = pack2(a[8 * i + 2], a[8 * i + 3]);
    v.z = pack2(a[8 * i + 4], a[8 * i + 5]);
    v.w = pack2(a[8 * i + 6], a[8 * i + 7]);
    *reinterpret_cast<uint4*>(dst + i * 512) = v;
  }
}

__global__ void __cluster_dims__(2, 1, 1) __launch_bounds__(384, 1) fused_block_kernel(const __grid_constant__ Params P) {
  extern __shared__ __align__(1024) uint8_t smem[];
  const uint32_t sb = s2u(smem);
  const int tid = threadIdx.x, lane = tid & 31, warp = __shfl_sync(0xffffffffu, tid >> 5, 0);
  uint32_t rank, smid;
  asm("mov.u32 %0, %%cluster_ctarank;" : "=r"(rank));
  asm("mov.u32 %0, %%smid;" : "=r"(smid));
  int g, c;
  {
    int pr = smid >> 1;
    if (pr < 32) { g = pr & 7; c = pr >> 3; }
    else if (pr < 60) { g = 1 + (pr - 32) % 7; c = 4 + (pr - 32) / 7; }
    else if (pr < 62) { return; }
    else { g = 0; c = 4 + (pr - 62); }
  }
  const int rb = 2 * g + (int)rank;
  const int tile = rb * 8 + c;
  const uint32_t bars = sb + OFF_MISC;
#define BAR(i) (bars + 8u * (uint32_t)(i))

  if (tid == 256) {
#pragma unroll 1
    for (int i = 0; i < NBAR; i++) {
      int cnt = 1;
      if ((i >= B_QEMPTY && i < B_KVOWN) || i == B_ATTP || i == B_WODP || (i >= B_BEMPTY && i < B_W2FULL) || i == B_W2E) cnt = 16;
      else if ((i >= B_KVOWN && i < B_KVFULL) || (i >= B_OSTG && i < B_OSD) || (i >= B_HSTG && i < B_AFULL) || (i >= B_AEMPTY && i < B_WODP) || (i >= B_PSTG && i < B_STAT)) cnt = 4;
      else if (i == B_ATTL || i == B_Q23) cnt = 8;
      mbar_init(BAR(i), cnt);
    }
    asm volatile("fence.mbarrier_init.release.cluster;" ::: "memory");
    asm volatile("prefetch.tensormap [%0];" ::"l"(&P.mX) : "memory");
    asm volatile("prefetch.tensormap [%0];" ::"l"(&P.mWqM) : "memory");
    asm volatile("prefetch.tensormap [%0];" ::"l"(&P.mWqL) : "memory");
  }
  __syncthreads();
  asm volatile("barrier.cluster.arrive.aligned;\nbarrier.cluster.wait.aligned;" ::: "memory");
  const uint32_t epoch = ldcg32(&g_epoch[tile]) + 1u;
  const int odd = c & 1;
  const int sc = (27 * c + 3) >> 2;

  if (warp >= 8) {
    asm volatile("setmaxnreg.dec.sync.aligned.u32 56;");
    if (warp == 8) {
      if (lane == 0) {
        const int mainch = (c >> 1) * 5 + (odd ? 3 : 0), leftch = (c >> 1) * 10 + (odd ? 5 : 4);
#pragma unroll 1
        for (int kt = 0; kt < 10; kt++) {
          const int st = kt & 3;
          if (kt >= 4) mbar_wait(BAR(B_QEMPTY + st), ((kt >> 2) - 1) & 1);
          const uint32_t a = sb + st * QST, fb = BAR(B_QFULL + st);
          mbar_expect(fb, QST);
          tma2d(a, &P.mX, kt * 64, rb * 128, fb);
          tma4d_mc(a + 16384 + rank * 12288, &P.mWqM, 0, kt * 64 + rank * 32, mainch, 0, fb);
          tma4d_mc(a + 40960 + rank * 3072, &P.mWqL, 0, kt * 64 + rank * 32, leftch, 0, fb);
        }
        asm volatile("prefetch.tensormap [%0];" ::"l"(&P.mWo) : "memory");
        asm volatile("prefetch.tensormap [%0];" ::"l"(rank ? &P.mW1b : &P.mW1a) : "memory");
        asm volatile("prefetch.tensormap [%0];" ::"l"(&P.mW2) : "memory");
        mbar_wait(BAR(B_QEMPTY + 2), 1);
        mbar_wait(BAR(B_QEMPTY + 0), 0);
        mbar_wait(BAR(B_QEMPTY + 1), 0);
        mbar_expect(BAR(B_WOB), 89600);
#pragma unroll 1
        for (int i = 0; i < 4 - (int)rank; i++) {
          const int pos = rank * 4 + i;
          tma3d_mc(sb + OFF_WOB + pos * 12800, &P.mWo, 0, korder(pos, c) * 80, c * 5, BAR(B_WOB));
        }
        const CUtensorMap* mW1 = rank ? &P.mW1b : &P.mW1a;
#pragma unroll 1
        for (int s = 0; s < 8; s++) {
          if (s == 0) {
            mbar_wait(BAR(B_ATTP), 0);
            mbar_expect(BAR(B_WOB7), 12800);
            if (rank) tma3d_mc(sb + OFF_WOB + 7 * 12800, &P.mWo, 0, korder(7, c) * 80, c * 5, BAR(B_WOB7));
          }
          else if (s == 1) mbar_wait(BAR(B_WODP), 0);
          else if (s >= 4) mbar_wait(BAR(B_BEMPTY + (s & 3)), 0);
          const uint32_t fb = BAR(B_BFULL + (s & 3));
          mbar_expect(fb, 35840);
          tma3d_mc(sb + w1b_addr(s & 3) + rank * 20480, mW1, 0, korder(s, c) * 80, sc + rank * 4, fb);
        }
#pragma unroll 1
        for (int s = 0; s < 5; s++) {
          if (s < 3) mbar_wait(BAR(B_BEMPTY + 1 + s), 1);
          else if (s == 4) mbar_wait(BAR(B_W2E), 0);
          const uint32_t dst = sb + ((0x23102u >> (4 * s)) & 15u) * W2SLOT + rank * 14336, fb = BAR(B_W2FULL + s);
          const int bx0 = s == 0 ? 8 : ((c + 2 * s - 1) & 7), bx1 = s == 0 ? 9 : ((c + 2 * s) & 7);
          mbar_expect(fb, W2SLOT);
          tma2d_mc(dst, &P.mW2, bx0 * 64, sc * 32 + rank * 112, fb);
          tma2d_mc(dst + 28672, &P.mW2, bx1 * 64, sc * 32 + rank * 112, fb);
        }
      }
    } else {
      if (warp != 11) {
        const int row0 = rb * 128 + c * 16 + (warp - 9) * 8;
        const uint8_t* xb = reinterpret_cast<const uint8_t*>(P.x) + (size_t)row0 * 1280;
        for (int i = lane; i < 80; i += 32) l2_prefetch(xb + i * 128);
#pragma unroll 1
        for (int i = 0; i < 8; i += 2) {
          uint2 v[2][5];
#pragma unroll
          for (int u = 0; u < 2; u++)
#pragma unroll
            for (int q = 0; q < 5; q++) v[u][q] = __ldg(reinterpret_cast<const uint2*>(xb + (i + u) * 1280 + q * 256 + lane * 8));
#pragma unroll
          for (int u = 0; u < 2; u++) {
            float s = 0.f;
#pragma unroll
            for (int q = 0; q < 5; q++) s += (bf_lo(v[u][q].x) + bf_hi(v[u][q].x)) + (bf_lo(v[u][q].y) + bf_hi(v[u][q].y));
#pragma unroll
            for (int o = 16; o; o >>= 1) s += __shfl_xor_sync(0xffffffffu, s, o);
            const float mean = s * (1.f / 640.f);
            float m2 = 0.f;
#pragma unroll
            for (int q = 0; q < 5; q++) {
              float d0 = bf_lo(v[u][q].x) - mean, d1 = bf_hi(v[u][q].x) - mean, d2 = bf_lo(v[u][q].y) - mean, d3 = bf_hi(v[u][q].y) - mean;
              m2 += (d0 * d0 + d1 * d1) + (d2 * d2 + d3 * d3);
            }
#pragma unroll
            for (int o = 16; o; o >>= 1) m2 += __shfl_xor_sync(0xffffffffu, m2, o);
            if (lane == 0) g_xstat[row0 + i + u] = make_float2(mean, 1.f / sqrtf(m2 * (1.f / 640.f) + 1e-5f));
          }
        }
        if (lane == 0) { fence_gpu(); st_flag(&g_flags[F_XS + rb * 16 + c * 2 + (warp - 9)], epoch); }
      }
      if (warp != 9) {
        const bool isq = (warp == 11);
        const int col = isq ? (lane / 10) * 640 + c * 80 + (lane % 10) * 8 : sc * 32 + lane * 8;
        const bool act = isq ? (lane < 30) : (lane < 28 && col < 1728);
        const size_t pitch = isq ? 3840 : 3456;
        const uint8_t* wb = reinterpret_cast<const uint8_t*>(isq ? P.wqkv : P.w1) + (size_t)rb * 40 * pitch + (size_t)col * 2;
        float acc[8];
#pragma unroll
        for (int i = 0; i < 8; i++) acc[i] = 0.f;
        if (act) {
#pragma unroll 1
          for (int i = 0; i < 40; i += 8) {
            uint4 v[8];
#pragma unroll
            for (int u = 0; u < 8; u++) v[u] = __ldg(reinterpret_cast<const uint4*>(wb + (size_t)(i + u) * pitch));
#pragma unroll
            for (int u = 0; u < 8; u++) {
              acc[0] += bf_lo(v[u].x); acc[1] += bf_hi(v[u].x); acc[2] += bf_lo(v[u].y); acc[3] += bf_hi(v[u].y);
              acc[4] += bf_lo(v[u].z); acc[5] += bf_hi(v[u].z); acc[6] += bf_lo(v[u].w); acc[7] += bf_hi(v[u].w);
            }
          }
        }
        if (lane < (isq ? 30 : 28)) {
          float4* dst = reinterpret_cast<float4*>(isq ? &g_csq[tile * 240 + lane * 8] : &g_cs1[tile * 224 + lane * 8]);
          dst[0] = make_float4(acc[0], acc[1], acc[2], acc[3]);
          dst[1] = make_float4(acc[4], acc[5], acc[6], acc[7]);
        }
        __syncwarp();
        if (lane == 0) {
          fence_gpu();
          st_flag(&g_flags[(isq ? F_CSQ : F_CS1) + c * 16 + rb], epoch);
          if (isq) l2_prefetch_bulk(reinterpret_cast<const uint8_t*>(P.wo) + tile * 6400, 6400);
          else l2_prefetch_bulk(reinterpret_cast<const uint8_t*>(P.w2) + tile * 17280, 17280);
        }
      }
      if (warp == 9) {
        STAMPW(0);
        poll_all(lane < 16 ? &g_flags[F_XS + rb * 16 + lane] : &g_flags[F_CSQ + c * 16 + lane - 16], true, epoch);
        STAMPW(1);
#pragma unroll 1
        for (int q = lane; q < 60; q += 32) {
          float4 a = make_float4(0.f, 0.f, 0.f, 0.f);
#pragma unroll 1
          for (int i = 0; i < 16; i += 8) {
            uint4 v[8];
#pragma unroll
            for (int u = 0; u < 8; u++) v[u] = ldcg128(&g_csq[((i + u) * 8 + c) * 240 + q * 4]);
#pragma unroll
            for (int u = 0; u < 8; u++) {
              a.x += __uint_as_float(v[u].x); a.y += __uint_as_float(v[u].y); a.z += __uint_as_float(v[u].z); a.w += __uint_as_float(v[u].w);
            }
          }
          *reinterpret_cast<float4*>(smem + OFF_CS + q * 16) = a;
        }
        {
          uint4 v0 = ldcg128(&g_xstat[rb * 128 + lane * 2]), v1 = ldcg128(&g_xstat[rb * 128 + 64 + lane * 2]);
          *reinterpret_cast<uint4*>(smem + OFF_XS + lane * 16) = v0;
          *reinterpret_cast<uint4*>(smem + OFF_XS + 512 + lane * 16) = v1;
        }
        __syncwarp();
        if (lane == 0) mbar_arrive(BAR(B_STAT));
        STAMPW(2);
        mbar_wait(BAR(B_Q23), 0);
        {
          const int blk = 2 * rb - 4 + lane;
          bool pend = lane < 4 && blk >= 0;
          uint32_t n = 0;
          while (__any_sync(0xffffffffu, pend)) {
            if (pend && ld_flag(&g_flags[F_KV + blk * 8 + c]) == epoch) {
              fence_async_glob();
              mbar_expect(BAR(B_KVFULL + lane), KVB);
              bulk_load(sb + kv_addr(lane), g_kv + (size_t)(blk * 8 + c) * KVB, KVB, BAR(B_KVFULL + lane));
              pend = false;
            }
            if (++n > (1u << 20)) break;
          }
        }
        STAMPW(3);
        mbar_wait(BAR(B_ATTL), 0);
        uint32_t ready = 0;
#pragma unroll 1
        for (int n = 0; n < 28; n++) {
          const int r = n & 1, j = n >> 1, i = (j < 7 ? j : j - 7) + 1;
          if (n == 14) ready = 0;
          const int src = korder(i, c), idx = r * 3 + j % 3;
          if (j >= 3) mbar_wait(BAR(B_AEMPTY + idx), (j / 3 - 1) & 1);
          uint32_t it = 0;
          while (!((ready >> (r * 8 + src)) & 1u)) {
            bool ok = lane < 16 && ld_flag(&g_flags[(n < 14 ? F_O : F_H) + rb * 16 + lane]) == epoch;
            ready = __ballot_sync(0xffffffffu, ok);
            if (++it > (1u << 20)) break;
          }
          if (lane == 0) {
            fence_async_glob();
            mbar_expect(BAR(B_AFULL + idx), 10240);
            bulk_load(sb + ring_addr(idx), (n < 14 ? g_o : g_h) + (size_t)((rb * 2 + r) * 8 + src) * 10240, 10240, BAR(B_AFULL + idx));
          }
          if (n == 0) STAMPW(4);
          if (n == 13) STAMPW(5);
          if (n == 14) STAMPW(6);
          if (n == 27) STAMPW(7);
        }
      } else {
        const int r = warp - 10, b = rb * 2 + r;
        mbar_wait(BAR(B_KVOWN + r), 0);
        if (lane == 0) {
          bulk_store(g_kv + (size_t)(b * 8 + c) * KVB, sb + kv_addr(4 + r), KVB);
          bulk_commit_wait();
          st_flag(&g_flags[F_KV + b * 8 + c], epoch);
          mbar_arrive(BAR(B_OSD + r));
        }
        __syncwarp();
        if (r == 1) {
          mbar_wait(BAR(B_KVOWN), 0);
          poll_all(&g_flags[F_CS1 + c * 16 + (lane & 15)], true, epoch);
#pragma unroll 1
          for (int q = lane; q < 56; q += 32) {
            float4 a = make_float4(0.f, 0.f, 0.f, 0.f);
#pragma unroll 1
            for (int i = 0; i < 16; i += 8) {
              uint4 v[8];
#pragma unroll
              for (int u = 0; u < 8; u++) v[u] = ldcg128(&g_cs1[((i + u) * 8 + c) * 224 + q * 4]);
#pragma unroll
              for (int u = 0; u < 8; u++) {
                a.x += __uint_as_float(v[u].x); a.y += __uint_as_float(v[u].y); a.z += __uint_as_float(v[u].z); a.w += __uint_as_float(v[u].w);
              }
            }
            *reinterpret_cast<float4*>(smem + OFF_XS + q * 16) = a;
          }
          __syncwarp();
          if (lane == 0) mbar_arrive(BAR(B_CS1));
        }
        if (lane == 0) {
          const uint32_t stg = sb + OFF_A + r * 61440;
          mbar_wait(BAR(B_OSTG + r), 0);
          bulk_store(g_o + (size_t)(b * 8 + c) * 10240, stg, 10240);
          bulk_commit_wait();
          st_flag(&g_flags[F_O + b * 8 + c], epoch);
          mbar_arrive(BAR(B_OSD + r));
          mbar_wait(BAR(B_HSTG + r), 0);
          bulk_store(g_h + (size_t)(b * 8 + c) * 10240, stg, 10240);
          bulk_store(&g_hstat[(b * 8 + c) * 64], sb + OFF_SPARE + r * 512, 512);
          bulk_commit_wait();
          st_flag(&g_flags[F_H + b * 8 + c], epoch);
          mbar_arrive(BAR(B_OSD + r));
#pragma unroll 1
          for (int s = 0; s < 5; s++) {
            mbar_wait(BAR(B_PSTG + r * 5 + s), 0);
            fence_gpu();
            if (s == 0) st_flag(&g_flags[F_P89 + b * 8 + c], epoch);
            else {
              st_flag(&g_flags[F_PART + (b * 8 + ((c + 2 * s - 1) & 7)) * 8 + c], epoch);
              if (s < 4) st_flag(&g_flags[F_PART + (b * 8 + ((c + 2 * s) & 7)) * 8 + c], epoch);
            }
          }
          if (r == 1) st_flag(&g_epoch[tile], epoch);
        }
      }
    }
    __syncwarp();
    asm volatile("barrier.cluster.arrive.aligned;\nbarrier.cluster.wait.aligned;" ::: "memory");
  } else {
    asm volatile("setmaxnreg.inc.sync.aligned.u32 224;");
    const int r = warp >> 2, w = warp & 3, gq = lane >> 2, tq = lane & 3;
    const int b = rb * 2 + r;
    const uint32_t stsm_off = (uint32_t)(w * 16 + ((lane >> 3) & 1) * 8 + (lane & 7)) * 16u + (uint32_t)(lane >> 4) * 1024u;
    uint32_t q[24];
    STAMP(0);
    {
      float accM[96], accL[24];
#pragma unroll 1
      for (int kt = 0; kt < 10; kt++) {
        const int st = kt & 3;
        mbar_wait(BAR(B_QFULL + st), (kt >> 2) & 1);
        if (kt == 0) STAMP(1);
        const uint32_t a = sb + st * QST;
        const uint64_t da = mkdesc(a + r * 8192, desc_hi(16, 1024, 1));
        const uint64_t dm = mkdesc(a + 16384, desc_hi(2048, 512, 2));
        const uint64_t dl = mkdesc(a + 40960, desc_hi(1024, 256, 3));
        reg_fence(accM); reg_fence(accL);
        WG_FENCE();
#pragma unroll
        for (int k = 0; k < 4; k++) {
          wg_ss192(accM, da + k * 2, dm + (k >> 1) * 768 + (k & 1) * 64, kt | k);
          wg_ss48(accL, da + k * 2, dl + (k >> 1) * 192 + (k & 1) * 32, kt | k);
        }
        WG_COMMIT();
        WG_WAIT(0);
        reg_fence(accM); reg_fence(accL);
        if (lane == 0) {
          mbar_arrive_pair(BAR(B_QEMPTY + st));
          if (kt == 7) mbar_arrive(BAR(B_Q23));
        }
      }
      STAMP(2);
      mbar_wait(BAR(B_STAT), 0);
      mbar_wait(BAR(B_Q23), 0);
      const float2 s0 = lds64f(sb + OFF_XS + (r * 64 + w * 16 + gq) * 8), s1 = lds64f(sb + OFF_XS + (r * 64 + w * 16 + gq + 8) * 8);
      const uint32_t csM = sb + OFF_CS + (odd ? 64 : 0) + tq * 8, csL = sb + OFF_CS + (odd ? 0 : 256) + tq * 8;
      const uint32_t kvo = sb + kv_addr(4 + r) + stsm_off;
      const float qs = 0.22360679774997896f * 1.4426950408889634f;
      const bool lo = tq < 2;
      uint32_t qj[20];
#pragma unroll
      for (int mm = 0; mm < 3; mm++) {
        const int mat = (mm + 1) % 3;
        const float r0 = mat == 0 ? s0.y * qs : s0.y, r1 = mat == 0 ? s1.y * qs : s1.y;
        const float n0 = -s0.x * r0, n1 = -s1.x * r1;
        uint32_t pk[20];
#pragma unroll
        for (int t = 0; t < 10; t++) {
          const float* a = t < 8 ? &accM[(mat * 8 + t) * 4] : &accL[(mat * 2 + t - 8) * 4];
          const float2 cs = lds64f(t < 8 ? csM + mat * 320 + t * 32 : csL + mat * 320 + (t - 8) * 32);
          pk[2 * t] = pack2(fmaf(a[0], r0, cs.x * n0), fmaf(a[1], r0, cs.y * n0));
          pk[2 * t + 1] = pack2(fmaf(a[2], r1, cs.x * n1), fmaf(a[3], r1, cs.y * n1));
        }
        if (mat == 1) {
#pragma unroll
          for (int t = 0; t < 8; t += 2) stsm4(kvo + (odd ? 2048 : 0) + t * 1024, pk[2 * t], pk[2 * t + 1], pk[2 * t + 2], pk[2 * t + 3]);
          stsm4(kvo + (odd ? 0 : 8192), pk[16], pk[17], pk[18], pk[19]);
        } else {
#pragma unroll
          for (int i = 0; i < 20; i++) qj[i] = odd ? pk[(i + 16) % 20] : pk[i];
        }
        if (mat == 2) {
          const uint32_t one = (tq & 1) ? 0u : 0x3f80u;
#pragma unroll
          for (int hp = 0; hp < 2; hp++) {
            const int j = hp * 10;
            const uint32_t base = kvo + 10240 + hp * 6144;
            stsm4(base, qj[j], qj[j + 1], qj[j + 2], qj[j + 3]);
            stsm4(base + 2048, lo ? qj[j + 4] : one, lo ? qj[j + 5] : one, lo ? one : qj[j + 4], lo ? one : qj[j + 5]);
            stsm4(base + 4096, qj[j + 6], qj[j + 7], qj[j + 8], qj[j + 9]);
          }
          fence_async_smem();
          __syncwarp();
          if (lane == 0) mbar_arrive(BAR(B_KVOWN + r));
        }
      }
#pragma unroll
      for (int hp = 0; hp < 2; hp++) {
        const int j = hp * 10;
        q[hp * 12 + 0] = qj[j + 0]; q[hp * 12 + 1] = qj[j + 1]; q[hp * 12 + 2] = qj[j + 2]; q[hp * 12 + 3] = qj[j + 3];
        q[hp * 12 + 4] = lo ? qj[j + 4] : 0u; q[hp * 12 + 5] = lo ? qj[j + 5] : 0u;
        q[hp * 12 + 6] = lo ? 0u : qj[j + 4]; q[hp * 12 + 7] = lo ? 0u : qj[j + 5];
        q[hp * 12 + 8] = qj[j + 6]; q[hp * 12 + 9] = qj[j + 7]; q[hp * 12 + 10] = qj[j + 8]; q[hp * 12 + 11] = qj[j + 9];
      }
    }
    STAMP(3);
    const uint32_t stg = sb + OFF_A + r * 61440;
    {
      float o0[12], o1[12], o2[12], o3[12], m[4][2];
#pragma unroll
      for (int i = 0; i < 12; i++) { o0[i] = 0.f; o1[i] = 0.f; o2[i] = 0.f; o3[i] = 0.f; }
#pragma unroll
      for (int i = 0; i < 4; i++) m[i][0] = m[i][1] = -INFINITY;
      float s0[32], s1[32];
      uint32_t p0[16], p1[16];
      const int dthr = w * 16 + gq - 2 * tq;
      mbar_wait(BAR(B_KVOWN + r), 0);
#pragma unroll 1
      for (int it = 0; it < 4; it++) {
        const int bi = ((r ? 0x3124u : 0x3102u) >> (4 * it)) & 15;
        const bool valid = 2 * rb - 4 + bi >= 0;
        if (bi == r) {
          if (valid) mbar_wait(BAR(B_KVFULL + bi), 0);
          const uint32_t kd = sb + kv_addr(4 + r), ka = valid ? sb + kv_addr(bi) : kd;
          comb_task<0>(s0, s1, p0, p1, q, o0, m[0], kd, ka, valid, dthr);
          comb_task<1>(s0, s1, p0, p1, q, o1, m[1], kd, ka, valid, dthr);
          comb_task<2>(s0, s1, p0, p1, q, o2, m[2], kd, ka, valid, dthr);
          comb_task<3>(s0, s1, p0, p1, q, o3, m[3], kd, ka, valid, dthr);
          WG_WAIT(0);
        } else if (valid) {
          mbar_wait(bi == 4 ? BAR(B_KVOWN) : BAR(B_KVFULL + bi), 0);
          const uint32_t kb = sb + kv_addr(bi);
          WG_FENCE();
          qk_issue<0>(s0, q, kb);
          WG_COMMIT();
          qk_issue<1>(s1, q, kb);
          WG_COMMIT();
          WG_WAIT(1);
          reg_fence(s0); reg_fence(o0);
          softmax_chunk(s0, p0, o0, m[0]);
          WG_FENCE();
          pv_issue<0>(o0, p0, kb);
          WG_COMMIT();
          qk_issue<2>(s0, q, kb);
          WG_COMMIT();
          WG_WAIT(2);
          reg_fence(s1); reg_fence(o1);
          softmax_chunk(s1, p1, o1, m[1]);
          WG_FENCE();
          pv_issue<1>(o1, p1, kb);
          WG_COMMIT();
          qk_issue<3>(s1, q, kb);
          WG_COMMIT();
          WG_WAIT(2);
          reg_fence(s0); reg_fence(o2);
          softmax_chunk(s0, p0, o2, m[2]);
          WG_FENCE();
          pv_issue<2>(o2, p0, kb);
          WG_COMMIT();
          WG_WAIT(1);
          reg_fence(s1); reg_fence(o3);
          softmax_chunk(s1, p1, o3, m[3]);
          WG_FENCE();
          pv_issue<3>(o3, p1, kb);
          WG_COMMIT();
          WG_WAIT(0);
        }
        reg_fence(o0); reg_fence(o1); reg_fence(o2); reg_fence(o3);
        if (it == 0) STAMP(4);
      }
      STAMP(5);
      float inv[4][2];
      inv[0][0] = 1.f / __shfl_sync(0xffffffffu, o0[8], (lane & 28) + 2);
      inv[0][1] = 1.f / __shfl_sync(0xffffffffu, o0[10], (lane & 28) + 2);
      inv[1][0] = 1.f / __shfl_sync(0xffffffffu, o1[0], lane & 28);
      inv[1][1] = 1.f / __shfl_sync(0xffffffffu, o1[2], lane & 28);
      inv[2][0] = 1.f / __shfl_sync(0xffffffffu, o2[8], (lane & 28) + 2);
      inv[2][1] = 1.f / __shfl_sync(0xffffffffu, o2[10], (lane & 28) + 2);
      inv[3][0] = 1.f / __shfl_sync(0xffffffffu, o3[0], lane & 28);
      inv[3][1] = 1.f / __shfl_sync(0xffffffffu, o3[2], lane & 28);
      uint32_t pk[20];
      const bool lo = tq < 2;
#define OPK(dst, o, t, h) do { pk[dst] = pack2(o[4 * (t)] * inv[h][0], o[4 * (t) + 1] * inv[h][0]); pk[dst + 1] = pack2(o[4 * (t) + 2] * inv[h][1], o[4 * (t) + 3] * inv[h][1]); } while (0)
#define OPK2(dst, oa, ha, ob, hb) do { \
        const float i0 = lo ? inv[ha][0] : inv[hb][0], i1 = lo ? inv[ha][1] : inv[hb][1]; \
        pk[dst] = pack2((lo ? oa[8] : ob[0]) * i0, (lo ? oa[9] : ob[1]) * i0); \
        pk[dst + 1] = pack2((lo ? oa[10] : ob[2]) * i1, (lo ? oa[11] : ob[3]) * i1); } while (0)
      OPK(0, o0, 0, 0); OPK(2, o0, 1, 0); OPK2(4, o0, 0, o1, 1); OPK(6, o1, 1, 1); OPK(8, o1, 2, 1);
      OPK(10, o2, 0, 2); OPK(12, o2, 1, 2); OPK2(14, o2, 2, o3, 3); OPK(16, o3, 1, 3); OPK(18, o3, 2, 3);
      mbar_wait(BAR(B_OSD + r), 0);
      asm volatile("bar.sync %0, 128;" ::"r"(r + 1) : "memory");
#pragma unroll
      for (int t = 0; t < 5; t++) stsm4(stg + stsm_off + t * 2048, pk[4 * t], pk[4 * t + 1], pk[4 * t + 2], pk[4 * t + 3]);
      fence_async_smem();
      __syncwarp();
      if (lane == 0) {
        mbar_arrive(BAR(B_OSTG + r));
        mbar_arrive(BAR(B_ATTL));
        mbar_arrive_pair(BAR(B_ATTP));
      }
    }
    STAMP(6);
    const int row_lo = b * 64 + w * 16 + gq;
    {
      uint32_t xr[20];
      const uint8_t* xp = reinterpret_cast<const uint8_t*>(P.x) + (size_t)row_lo * 1280 + c * 160 + tq * 4;
#pragma unroll
      for (int t = 0; t < 10; t++) {
        xr[2 * t] = __ldg(reinterpret_cast<const uint32_t*>(xp + t * 16));
        xr[2 * t + 1] = __ldg(reinterpret_cast<const uint32_t*>(xp + 8 * 1280 + t * 16));
      }
      float acc[40];
      mbar_wait(BAR(B_WOB), 0);
      mbar_wait(BAR(B_OSTG + r), 0);
      int prev = -1;
#pragma unroll 1
      for (int i = 0; i < 8; i++) {
        uint32_t a = stg;
        int idx = -1;
        if (i > 0) {
          const int j = i - 1;
          idx = r * 3 + j % 3;
          mbar_wait(BAR(B_AFULL + idx), (j / 3) & 1);
          a = sb + ring_addr(idx);
          if (i == 1) STAMP(7);
          if (i == 7) mbar_wait(BAR(B_WOB7), 0);
        }
        const uint64_t da = mkdesc(a, desc_hi(1024, 128, 0)), db = mkdesc(sb + OFF_WOB + i * 12800, desc_hi(2560, 256, 3));
        reg_fence(acc);
        WG_FENCE();
#pragma unroll
        for (int k = 0; k < 5; k++) wg_ss80(acc, da + k * 128, db + k * 32, i | k);
        WG_COMMIT();
        WG_WAIT(1);
        reg_fence(acc);
        if (prev >= 0 && lane == 0) mbar_arrive(BAR(B_AEMPTY + prev));
        prev = idx;
      }
      WG_WAIT(0);
      reg_fence(acc);
      if (lane == 0) {
        mbar_arrive(BAR(B_AEMPTY + prev));
        mbar_arrive_pair(BAR(B_WODP));
      }
      STAMP(8);
      uint32_t pk[20];
      float sum0 = 0.f, sum1 = 0.f;
#pragma unroll
      for (int t = 0; t < 10; t++) {
        pk[2 * t] = pack2(acc[4 * t] + bf_lo(xr[2 * t]), acc[4 * t + 1] + bf_hi(xr[2 * t]));
        pk[2 * t + 1] = pack2(acc[4 * t + 2] + bf_lo(xr[2 * t + 1]), acc[4 * t + 3] + bf_hi(xr[2 * t + 1]));
        sum0 += bf_lo(pk[2 * t]) + bf_hi(pk[2 * t]);
        sum1 += bf_lo(pk[2 * t + 1]) + bf_hi(pk[2 * t + 1]);
      }
      mbar_wait(BAR(B_OSD + r), 1);
      asm volatile("bar.sync %0, 128;" ::"r"(r + 1) : "memory");
#pragma unroll
      for (int t = 0; t < 5; t++) stsm4(stg + stsm_off + t * 2048, pk[4 * t], pk[4 * t + 1], pk[4 * t + 2], pk[4 * t + 3]);
      sum0 += __shfl_xor_sync(0xffffffffu, sum0, 1);
      sum1 += __shfl_xor_sync(0xffffffffu, sum1, 1);
      sum0 += __shfl_xor_sync(0xffffffffu, sum0, 2);
      sum1 += __shfl_xor_sync(0xffffffffu, sum1, 2);
      const float mu0 = sum0 * (1.f / 80.f), mu1 = sum1 * (1.f / 80.f);
      float v0 = 0.f, v1 = 0.f;
#pragma unroll
      for (int t = 0; t < 10; t++) {
        const float d0 = bf_lo(pk[2 * t]) - mu0, d1 = bf_hi(pk[2 * t]) - mu0, d2 = bf_lo(pk[2 * t + 1]) - mu1, d3 = bf_hi(pk[2 * t + 1]) - mu1;
        v0 += d0 * d0 + d1 * d1;
        v1 += d2 * d2 + d3 * d3;
      }
      v0 += __shfl_xor_sync(0xffffffffu, v0, 1);
      v1 += __shfl_xor_sync(0xffffffffu, v1, 1);
      v0 += __shfl_xor_sync(0xffffffffu, v0, 2);
      v1 += __shfl_xor_sync(0xffffffffu, v1, 2);
      if (tq == 0) {
        float2* hs = reinterpret_cast<float2*>(smem + OFF_SPARE + r * 512);
        hs[w * 16 + gq] = make_float2(mu0, v0);
        hs[w * 16 + gq + 8] = make_float2(mu1, v1);
      }
      fence_async_smem();
      __syncwarp();
      if (lane == 0) mbar_arrive(BAR(B_HSTG + r));
    }
    STAMP(9);
    uint32_t ha[56];
    {
      float acc[112];
      uint2 hs[4];
      mbar_wait(BAR(B_HSTG + r), 0);
      int prev = -1;
#pragma unroll 1
      for (int i = 0; i < 8; i++) {
        uint32_t a = stg;
        int idx = -1;
        mbar_wait(BAR(B_BFULL + (i & 3)), i >> 2);
        if (i > 0) {
          const int j = 6 + i;
          idx = r * 3 + j % 3;
          mbar_wait(BAR(B_AFULL + idx), (j / 3) & 1);
          a = sb + ring_addr(idx);
          if (i == 1) { mbar_wait(BAR(B_OSD + r), 0); STAMP(10); }
          if (i == 7) {
            const float2* hp = &g_hstat[(b * 8 + tq * 2) * 64 + w * 16 + gq];
            hs[0] = ldcg64(hp); hs[1] = ldcg64(hp + 64); hs[2] = ldcg64(hp + 8); hs[3] = ldcg64(hp + 72);
          }
        }
        const uint64_t da = mkdesc(a, desc_hi(1024, 128, 0)), db = mkdesc(sb + w1b_addr(i & 3), desc_hi(5120, 512, 2));
        reg_fence(acc);
        WG_FENCE();
#pragma unroll
        for (int k = 0; k < 5; k++) wg_ss224(acc, da + k * 128, db + k * 64, i | k);
        WG_COMMIT();
        WG_WAIT(1);
        reg_fence(acc);
        if (i > 0 && lane == 0) {
          if (prev >= 0) mbar_arrive(BAR(B_AEMPTY + prev));
          mbar_arrive_pair(BAR(B_BEMPTY + ((i - 1) & 3)));
        }
        prev = idx;
      }
      float mean0, mean1, rs0, rs1;
      {
        const float a0 = __uint_as_float(hs[0].x), a1 = __uint_as_float(hs[1].x), b0 = __uint_as_float(hs[2].x), b1 = __uint_as_float(hs[3].x);
        float t0 = a0 + a1, t1 = b0 + b1;
        t0 += __shfl_xor_sync(0xffffffffu, t0, 1);
        t1 += __shfl_xor_sync(0xffffffffu, t1, 1);
        t0 += __shfl_xor_sync(0xffffffffu, t0, 2);
        t1 += __shfl_xor_sync(0xffffffffu, t1, 2);
        mean0 = t0 * 0.125f;
        mean1 = t1 * 0.125f;
        float u0 = __uint_as_float(hs[0].y) + __uint_as_float(hs[1].y) + 80.f * ((a0 - mean0) * (a0 - mean0) + (a1 - mean0) * (a1 - mean0));
        float u1 = __uint_as_float(hs[2].y) + __uint_as_float(hs[3].y) + 80.f * ((b0 - mean1) * (b0 - mean1) + (b1 - mean1) * (b1 - mean1));
        u0 += __shfl_xor_sync(0xffffffffu, u0, 1);
        u1 += __shfl_xor_sync(0xffffffffu, u1, 1);
        u0 += __shfl_xor_sync(0xffffffffu, u0, 2);
        u1 += __shfl_xor_sync(0xffffffffu, u1, 2);
        rs0 = 0.5f / sqrtf(u0 * (1.f / 640.f) + 1e-5f);
        rs1 = 0.5f / sqrtf(u1 * (1.f / 640.f) + 1e-5f);
      }
      mbar_wait(BAR(B_CS1), 0);
      WG_WAIT(0);
      reg_fence(acc);
      if (lane == 0) mbar_arrive_pair(BAR(B_BEMPTY + 3));
      STAMP(11);
      const float n0 = -mean0 * rs0, n1 = -mean1 * rs1;
#pragma unroll
      for (int t = 0; t < 28; t++) {
        const float2 cs = lds64f(sb + OFF_XS + t * 32 + tq * 8);
        const float h0 = fmaf(acc[4 * t], rs0, cs.x * n0), h1 = fmaf(acc[4 * t + 1], rs0, cs.y * n0);
        const float h2 = fmaf(acc[4 * t + 2], rs1, cs.x * n1), h3 = fmaf(acc[4 * t + 3], rs1, cs.y * n1);
        ha[2 * t] = pack2(fmaf(h0, tanh_fast(h0), h0), fmaf(h1, tanh_fast(h1), h1));
        ha[2 * t + 1] = pack2(fmaf(h2, tanh_fast(h2), h2), fmaf(h3, tanh_fast(h3), h3));
      }
      if ((c & 3) == 3) {
#pragma unroll
        for (int t = 48; t < 56; t++) ha[t] = 0u;
      }
    }
    STAMP(12);
    {
      float accA[64], accB[64];
      constexpr uint64_t HI = desc_hi(28672, 1024, 1);
      const uint32_t lane_off = w * 2048 + lane * 16;
#define W2_ISSUE(acc, s) do { \
        mbar_wait(BAR(B_W2FULL + (s)), 0); \
        const uint64_t db = mkdesc(sb + ((0x23102u >> (4 * (s))) & 15u) * W2SLOT, HI); \
        WG_FENCE(); \
        _Pragma("unroll") for (int k = 0; k < 14; k++) wg_rs128(acc, ha[4 * k], ha[4 * k + 1], ha[4 * k + 2], ha[4 * k + 3], db + k * 128, k); \
        WG_COMMIT(); } while (0)
#define W2_STORE(acc, s) do { \
        store_partial64(&acc[0], g_part + (size_t)((b * 8 + ((c + 2 * (s) - 1) & 7)) * 8 + c) * 8192 + lane_off); \
        store_partial64(&acc[32], g_part + (size_t)((b * 8 + ((c + 2 * (s)) & 7)) * 8 + c) * 8192 + lane_off); \
        __syncwarp(); \
        if (lane == 0) mbar_arrive(BAR(B_PSTG + r * 5 + (s))); } while (0)
      W2_ISSUE(accA, 0);
      W2_ISSUE(accB, 1);
      WG_WAIT(1);
      reg_fence(accA);
      if (lane == 0) mbar_arrive_pair(BAR(B_W2E));
      {
        uint8_t* dst = g_p89 + (size_t)((b * 4 + w) * 8 + c) * 4096 + lane * 16;
        store_partial64(&accA[0], dst);
        store_partial64(&accA[32], dst + 2048);
        __syncwarp();
        if (lane == 0) mbar_arrive(BAR(B_PSTG + r * 5));
      }
      STAMP(13);
      W2_ISSUE(accA, 2);
      WG_WAIT(1);
      reg_fence(accB);
      W2_STORE(accB, 1);
      W2_ISSUE(accB, 3);
      WG_WAIT(1);
      reg_fence(accA);
      W2_STORE(accA, 2);
      float accR[32], accO[32];
      {
        mbar_wait(BAR(B_W2FULL + 4), 0);
        const uint64_t db = mkdesc(sb + 2 * W2SLOT, HI);
        WG_FENCE();
#pragma unroll
        for (int k = 0; k < 14; k++) wg_rs64(accR, ha[4 * k], ha[4 * k + 1], ha[4 * k + 2], ha[4 * k + 3], db + k * 128, k);
        WG_COMMIT();
#pragma unroll
        for (int k = 0; k < 14; k++) wg_rs64(accO, ha[4 * k], ha[4 * k + 1], ha[4 * k + 2], ha[4 * k + 3], db + 1792 + k * 128, k);
        WG_COMMIT();
      }
      WG_WAIT(2);
      reg_fence(accB);
      W2_STORE(accB, 3);
      WG_WAIT(1);
      reg_fence(accR);
      store_partial64(&accR[0], g_part + (size_t)((b * 8 + ((c + 7) & 7)) * 8 + c) * 8192 + lane_off);
      __syncwarp();
      if (lane == 0) mbar_arrive(BAR(B_PSTG + r * 5 + 4));
      STAMP(14);
      {
        const int b2 = rb * 2 + (c >> 2), w2 = c & 3;
        poll_all(&g_flags[F_P89 + b2 * 8 + (lane & 7)], true, epoch);
        uint4 v[8];
#pragma unroll
        for (int u = 0; u < 8; u++) v[u] = ldcg128(g_p89 + (size_t)((b2 * 4 + w2) * 8 + u) * 4096 + warp * 512 + lane * 16);
        const uint8_t* hp = g_h + (size_t)b2 * 81920 + (64 + 2 * warp) * 1024 + (w2 * 16 + gq) * 16 + tq * 4;
        const uint32_t h0 = ldcg32(hp), h1 = ldcg32(hp + 128), h2 = ldcg32(hp + 1024), h3 = ldcg32(hp + 1152);
        float f[8] = {bf_lo(h0), bf_hi(h0), bf_lo(h1), bf_hi(h1), bf_lo(h2), bf_hi(h2), bf_lo(h3), bf_hi(h3)};
#pragma unroll
        for (int u = 0; u < 8; u++) {
          f[0] += bf_lo(v[u].x); f[1] += bf_hi(v[u].x); f[2] += bf_lo(v[u].y); f[3] += bf_hi(v[u].y);
          f[4] += bf_lo(v[u].z); f[5] += bf_hi(v[u].z); f[6] += bf_lo(v[u].w); f[7] += bf_hi(v[u].w);
        }
        uint8_t* op = reinterpret_cast<uint8_t*>(P.out) + (size_t)(b2 * 64 + w2 * 16 + gq) * 1280 + 1024 + warp * 32 + tq * 4;
        *reinterpret_cast<uint32_t*>(op) = pack2(f[0], f[1]);
        *reinterpret_cast<uint32_t*>(op + 8 * 1280) = pack2(f[2], f[3]);
        *reinterpret_cast<uint32_t*>(op + 16) = pack2(f[4], f[5]);
        *reinterpret_cast<uint32_t*>(op + 8 * 1280 + 16) = pack2(f[6], f[7]);
      }
      uint32_t hr[16];
      {
        const uint8_t* hp = g_h + (size_t)b * 81920 + (8 * c) * 1024 + (w * 16 + gq) * 16 + tq * 4;
#pragma unroll
        for (int t = 0; t < 8; t++) { hr[2 * t] = ldcg32(hp + t * 1024); hr[2 * t + 1] = ldcg32(hp + t * 1024 + 128); }
      }
      WG_WAIT(0);
      reg_fence(accO);
      STAMP(15);
#pragma unroll
      for (int t = 0; t < 8; t++) {
        accO[4 * t] += bf_lo(hr[2 * t]); accO[4 * t + 1] += bf_hi(hr[2 * t]);
        accO[4 * t + 2] += bf_lo(hr[2 * t + 1]); accO[4 * t + 3] += bf_hi(hr[2 * t + 1]);
      }
      poll_all(&g_flags[F_PART + (b * 8 + c) * 8 + (lane & 7)], (lane & 7) != c, epoch);
      STAMP(16);
      const uint8_t* pp = g_part + (size_t)((b * 8 + c) * 8) * 8192 + lane_off;
      uint4 v[7][4];
#pragma unroll
      for (int u = 0; u < 7; u++) {
        const int src = u < c ? u : u + 1;
#pragma unroll
        for (int i = 0; i < 4; i++) v[u][i] = ldcg128(pp + src * 8192 + i * 512);
      }
#pragma unroll
      for (int u = 0; u < 7; u++)
#pragma unroll
        for (int i = 0; i < 4; i++) {
          accO[8 * i + 0] += bf_lo(v[u][i].x); accO[8 * i + 1] += bf_hi(v[u][i].x); accO[8 * i + 2] += bf_lo(v[u][i].y); accO[8 * i + 3] += bf_hi(v[u][i].y);
          accO[8 * i + 4] += bf_lo(v[u][i].z); accO[8 * i + 5] += bf_hi(v[u][i].z); accO[8 * i + 6] += bf_lo(v[u][i].w); accO[8 * i + 7] += bf_hi(v[u][i].w);
        }
      uint8_t* op = reinterpret_cast<uint8_t*>(P.out) + (size_t)row_lo * 1280 + c * 128 + tq * 4;
#pragma unroll
      for (int t = 0; t < 8; t++) {
        *reinterpret_cast<uint32_t*>(op + t * 16) = pack2(accO[4 * t], accO[4 * t + 1]);
        *reinterpret_cast<uint32_t*>(op + 8 * 1280 + t * 16) = pack2(accO[4 * t + 2], accO[4 * t + 3]);
      }
      STAMP(17);
    }
    asm volatile("barrier.cluster.arrive.aligned;\nbarrier.cluster.wait.aligned;" ::: "memory");
  }
}

typedef CUresult (*EncodeFn)(CUtensorMap*, CUtensorMapDataType, cuuint32_t, void*, const cuuint64_t*, const cuuint64_t*, const cuuint32_t*,
                             const cuuint32_t*, CUtensorMapInterleave, CUtensorMapSwizzle, CUtensorMapL2promotion, CUtensorMapFloatOOBfill);

static void make_map(EncodeFn enc, CUtensorMap* m, const void* p, int nd, const cuuint64_t* dims, const cuuint64_t* strides, const cuuint32_t* box,
                     CUtensorMapSwizzle sw) {
  const cuuint32_t es[5] = {1, 1, 1, 1, 1};
  enc(m, CU_TENSOR_MAP_DATA_TYPE_BFLOAT16, (cuuint32_t)nd, const_cast<void*>(p), dims, strides, box, es, CU_TENSOR_MAP_INTERLEAVE_NONE, sw,
      CU_TENSOR_MAP_L2_PROMOTION_L2_128B, CU_TENSOR_MAP_FLOAT_OOB_FILL_NONE);
}

extern "C" void kernel_launch(void* const* d_in, const int* in_sizes, int n_in, void* d_out, int out_size) {
  (void)in_sizes; (void)n_in; (void)out_size;
  static EncodeFn enc = nullptr;
  if (!enc) {
    void* f = nullptr;
    cudaDriverEntryPointQueryResult qr;
    cudaGetDriverEntryPoint("cuTensorMapEncodeTiled", &f, cudaEnableDefault, &qr);
    enc = (EncodeFn)f;
    cudaFuncSetAttribute(fused_block_kernel, cudaFuncAttributeMaxDynamicSharedMemorySize, (int)SMEM_BYTES);
  }
  Params P;
  P.x = (const __nv_bfloat16*)d_in[0];
  P.wqkv = (const __nv_bfloat16*)d_in[1];
  P.wo = (const __nv_bfloat16*)d_in[2];
  P.w1 = (const __nv_bfloat16*)d_in[4];
  P.w2 = (const __nv_bfloat16*)d_in[5];
  P.out = (__nv_bfloat16*)d_out;
  { const cuuint64_t d[2] = {640, 2048}, s[1] = {1280}; const cuuint32_t b[2] = {64, 128}; make_map(enc, &P.mX, P.x, 2, d, s, b, CU_TENSOR_MAP_SWIZZLE_128B); }
  { const cuuint64_t d[4] = {32, 640, 20, 3}, s[3] = {3840, 64, 1280}; const cuuint32_t b[4] = {32, 32, 2, 3}; make_map(enc, &P.mWqM, P.wqkv, 4, d, s, b, CU_TENSOR_MAP_SWIZZLE_64B); }
  { const cuuint64_t d[4] = {16, 640, 40, 3}, s[3] = {3840, 32, 1280}; const cuuint32_t b[4] = {16, 32, 1, 3}; make_map(enc, &P.mWqL, P.wqkv, 4, d, s, b, CU_TENSOR_MAP_SWIZZLE_32B); }
  { const cuuint64_t d[3] = {16, 640, 40}, s[2] = {1280, 32}; const cuuint32_t b[3] = {16, 80, 5}; make_map(enc, &P.mWo, P.wo, 3, d, s, b, CU_TENSOR_MAP_SWIZZLE_32B); }
  { const cuuint64_t d[3] = {32, 640, 54}, s[2] = {3456, 64}; const cuuint32_t b[3] = {32, 80, 4}; make_map(enc, &P.mW1a, P.w1, 3, d, s, b, CU_TENSOR_MAP_SWIZZLE_64B); }
  { const cuuint64_t d[3] = {32, 640, 54}, s[2] = {3456, 64}; const cuuint32_t b[3] = {32, 80, 3}; make_map(enc, &P.mW1b, P.w1, 3, d, s, b, CU_TENSOR_MAP_SWIZZLE_64B); }
  { const cuuint64_t d[2] = {640, 1728}, s[1] = {1280}; const cuuint32_t b[2] = {64, 112}; make_map(enc, &P.mW2, P.w2, 2, d, s, b, CU_TENSOR_MAP_SWIZZLE_128B); }
  fused_block_kernel<<<132, 384, SMEM_BYTES, cudaStreamPerThread>>>(P);
}
```

```cpp
#include <cuda_runtime.h>
#include <cuda.h>
#include <cuda_bf16.h>
#include <stdint.h>

#define PROF 0

__device__ __align__(1024) uint8_t g_kv[32 * 8 * 22528];
__device__ __align__(1024) uint8_t g_o[32 * 4 * 8 * 2560];
__device__ __align__(1024) uint8_t g_h[32 * 4 * 8 * 2560];
__device__ __align__(1024) float2 g_hstat[32 * 4 * 8 * 16];
__device__ __align__(1024) uint8_t g_part[32 * 8 * 8 * 8192];
__device__ __align__(1024) uint8_t g_p89[32 * 4 * 8 * 4096];
__device__ __align__(128) float2 g_xstat[2048];
__device__ __align__(128) float g_csq[16 * 8 * 240];
__device__ __align__(128) float g_cs1[16 * 8 * 224];
__device__ __align__(128) uint32_t g_epoch[128];
#define STAMP(slot)
#define STAMPW(slot)

struct Params {
  CUtensorMap mX, mWqM, mWqL, mWo, mW1a, mW1b, mW2;
  const __nv_bfloat16 *x, *wqkv, *wo, *w1, *w2;
  __nv_bfloat16* out;
};

constexpr uint32_t QST = 47104;
constexpr uint32_t KVB = 22528;
constexpr uint32_t OFF_WOB = 0;
constexpr uint32_t OFF_PRE = 188416;
constexpr uint32_t W2SLOT = 57344;
constexpr uint32_t OFF_MISC = 229376;
constexpr uint32_t OFF_CS = OFF_MISC + 512;
constexpr uint32_t OFF_XS = OFF_CS + 960;
constexpr uint32_t SMEM_BYTES = 232448;

enum {
  B_QFULL = 0, B_KVFULL = 4, B_KVLAND = 8, B_WOB = 12, B_WOB7 = 13, B_BFULL = 14, B_W2FULL = 22,
  B_KVOWN = 27,
  B_Q23 = 29, B_PRE = 30, B_STAT = 31, B_CS1 = 32,
  B_QEMPTY = 33, B_ATTP = 37, B_WODP = 38, B_BEMPTY = 39, B_W2E = 47,
  NBAR = 48
};
constexpr uint32_t TAGM = 0x00010001u;
constexpr uint32_t SPIN_MAX = 1u << 18;

__device__ __forceinline__ uint32_t s2u(const void* p) { return (uint32_t)__cvta_generic_to_shared(p); }
__device__ __forceinline__ void mbar_init(uint32_t b, int c) { asm volatile("mbarrier.init.shared::cta.b64 [%0], %1;" ::"r"(b), "r"(c)); }
__device__ __forceinline__ void mbar_expect(uint32_t b, int bytes) { asm volatile("mbarrier.arrive.expect_tx.shared::cta.b64 _, [%0], %1;" ::"r"(b), "r"(bytes) : "memory"); }
__device__ __forceinline__ void mbar_arrive(uint32_t b) { asm volatile("mbarrier.arrive.shared::cta.b64 _, [%0];" ::"r"(b) : "memory"); }
__device__ __forceinline__ void mbar_arrive_pair(uint32_t b) {
  asm volatile("{\n.reg .b32 r;\nmapa.shared::cluster.u32 r, %0, 0;\nmbarrier.arrive.shared::cluster.b64 _, [r];\n"
               "mapa.shared::cluster.u32 r, %0, 1;\nmbarrier.arrive.shared::cluster.b64 _, [r];\n}" ::"r"(b) : "memory");
}
__device__ __forceinline__ bool mbar_try(uint32_t b, uint32_t ph) {
  uint32_t ok;
  asm volatile("{\n.reg .pred p;\nmbarrier.try_wait.parity.shared::cta.b64 p, [%1], %2;\nselp.u32 %0, 1, 0, p;\n}" : "=r"(ok) : "r"(b), "r"(ph) : "memory");
  return ok != 0;
}
__device__ __forceinline__ void mbar_wait(uint32_t b, uint32_t ph) {
  if (mbar_try(b, ph)) return;
  const long long t0 = clock64();
  while (!mbar_try(b, ph)) { if (clock64() - t0 > 100000000LL) break; }
}
__device__ __forceinline__ void tma2d(uint32_t dst, const CUtensorMap* m, int c0, int c1, uint32_t bar) {
  asm volatile("cp.async.bulk.tensor.2d.shared::cluster.global.mbarrier::complete_tx::bytes [%0], [%1, {%3, %4}], [%2];" ::"r"(dst), "l"(m), "r"(bar), "r"(c0), "r"(c1) : "memory");
}
__device__ __forceinline__ void tma2d_mc(uint32_t dst, const CUtensorMap* m, int c0, int c1, uint32_t bar) {
  asm volatile("cp.async.bulk.tensor.2d.shared::cluster.global.mbarrier::complete_tx::bytes.multicast::cluster [%0], [%1, {%3, %4}], [%2], %5;" ::"r"(dst), "l"(m), "r"(bar), "r"(c0), "r"(c1), "h"((uint16_t)3) : "memory");
}
__device__ __forceinline__ void tma3d_mc(uint32_t dst, const CUtensorMap* m, int c0, int c1, int c2, uint32_t bar) {
  asm volatile("cp.async.bulk.tensor.3d.shared::cluster.global.mbarrier::complete_tx::bytes.multicast::cluster [%0], [%1, {%3, %4, %5}], [%2], %6;" ::"r"(dst), "l"(m), "r"(bar), "r"(c0), "r"(c1), "r"(c2), "h"((uint16_t)3) : "memory");
}
__device__ __forceinline__ void tma4d_mc(uint32_t dst, const CUtensorMap* m, int c0, int c1, int c2, int c3, uint32_t bar) {
  asm volatile("cp.async.bulk.tensor.4d.shared::cluster.global.mbarrier::complete_tx::bytes.multicast::cluster [%0], [%1, {%3, %4, %5, %6}], [%2], %7;" ::"r"(dst), "l"(m), "r"(bar), "r"(c0), "r"(c1), "r"(c2), "r"(c3), "h"((uint16_t)3) : "memory");
}
__device__ __forceinline__ void bulk_load(uint32_t dst, const void* src, int bytes, uint32_t bar) {
  asm volatile("cp.async.bulk.shared::cluster.global.mbarrier::complete_tx::bytes [%0], [%1], %2, [%3];" ::"r"(dst), "l"(src), "r"(bytes), "r"(bar) : "memory");
}
__device__ __forceinline__ void tma4d_pf(const CUtensorMap* m, int c0, int c1, int c2, int c3) {
  asm volatile("cp.async.bulk.prefetch.tensor.4d.L2.global [%0, {%1, %2, %3, %4}];" ::"l"(m), "r"(c0), "r"(c1), "r"(c2), "r"(c3) : "memory");
}
__device__ __forceinline__ void l2_prefetch_bulk(const void* p, int bytes) { asm volatile("cp.async.bulk.prefetch.L2.global [%0], %1;" ::"l"(p), "r"(bytes) : "memory"); }
__device__ __forceinline__ void l2_prefetch(const void* p) { asm volatile("prefetch.global.L2 [%0];" ::"l"(p)); }
__device__ __forceinline__ uint32_t ld_flag(const uint32_t* p) { uint32_t v; asm volatile("ld.acquire.gpu.global.u32 %0, [%1];" : "=r"(v) : "l"(p) : "memory"); return v; }
__device__ __forceinline__ void st_flag(uint32_t* p, uint32_t v) { asm volatile("st.relaxed.gpu.global.u32 [%0], %1;" ::"l"(p), "r"(v) : "memory"); }
__device__ __forceinline__ void fence_gpu() { asm volatile("fence.acq_rel.gpu;" ::: "memory"); }
__device__ __forceinline__ void fence_async_smem() { asm volatile("fence.proxy.async.shared::cta;" ::: "memory"); }
__device__ __forceinline__ void fence_async_glob() { asm volatile("fence.proxy.async.global;" ::: "memory"); }
__device__ __forceinline__ uint4 ldcg128(const void* p) { uint4 v; asm volatile("ld.relaxed.gpu.global.v4.u32 {%0,%1,%2,%3}, [%4];" : "=r"(v.x), "=r"(v.y), "=r"(v.z), "=r"(v.w) : "l"(p) : "memory"); return v; }
__device__ __forceinline__ uint2 ldcg64(const void* p) { uint2 v; asm volatile("ld.relaxed.gpu.global.v2.u32 {%0,%1}, [%2];" : "=r"(v.x), "=r"(v.y) : "l"(p) : "memory"); return v; }
__device__ __forceinline__ uint32_t ldcg32(const void* p) { uint32_t v; asm volatile("ld.relaxed.gpu.global.u32 %0, [%1];" : "=r"(v) : "l"(p) : "memory"); return v; }
__device__ __forceinline__ uint32_t pack2(float lo, float hi) { uint32_t r; asm("cvt.rn.bf16x2.f32 %0, %1, %2;" : "=r"(r) : "f"(hi), "f"(lo)); return r; }
__device__ __forceinline__ float bf_lo(uint32_t v) { return __uint_as_float(v << 16); }
__device__ __forceinline__ float bf_hi(uint32_t v) { return __uint_as_float(v & 0xffff0000u); }
__device__ __forceinline__ float ex2(float x) { float y; asm("ex2.approx.ftz.f32 %0, %1;" : "=f"(y) : "f"(x)); return y; }
__device__ __forceinline__ float tanh_fast(float x) { float y; asm("tanh.approx.f32 %0, %1;" : "=f"(y) : "f"(x)); return y; }
__device__ __forceinline__ void stsm4(uint32_t a, uint32_t r0, uint32_t r1, uint32_t r2, uint32_t r3) {
  asm volatile("stmatrix.sync.aligned.m8n8.x4.shared.b16 [%0], {%1,%2,%3,%4};" ::"r"(a), "r"(r0), "r"(r1), "r"(r2), "r"(r3) : "memory");
}
__device__ __forceinline__ float2 lds64f(uint32_t a) { float2 v; asm volatile("ld.shared.v2.f32 {%0,%1}, [%2];" : "=f"(v.x), "=f"(v.y) : "r"(a)); return v; }
__device__ __forceinline__ constexpr uint64_t desc_hi(uint32_t lbo, uint32_t sbo, uint32_t sw) {
  return ((uint64_t)(lbo >> 4) << 16) | ((uint64_t)(sbo >> 4) << 32) | ((uint64_t)sw << 62);
}
__device__ __forceinline__ uint64_t mkdesc(uint32_t addr, uint64_t hi) { return hi | (uint64_t)((addr & 0x3FFFF) >> 4); }
#define WG_FENCE() asm volatile("wgmma.fence.sync.aligned;" ::: "memory")
#define WG_COMMIT() asm volatile("wgmma.commit_group.sync.aligned;" ::: "memory")
#define WG_WAIT(n) asm volatile("wgmma.wait_group.sync.aligned " #n ";" ::: "memory")
template <int N> __device__ __forceinline__ void reg_fence(float (&a)[N]) {
#pragma unroll
  for (int i = 0; i < N; i++) asm volatile("" : "+f"(a[i])::"memory");
}

__device__ __forceinline__ void wg_ss192(float (&d)[96], uint64_t da, uint64_t db, int sd) {
  asm volatile("{\n.reg .pred p;\nsetp.ne.b32 p, %98, 0;\n"
  "wgmma.mma_async.sync.aligned.m64n192k16.f32.bf16.bf16 {%0, %1, %2, %3, %4, %5, %6, %7, %8, %9, %10, %11, %12, %13, %14, %15, %16, %17, %18, %19, %20, %21, %22, %23, %24, %25, %26, %27, %28, %29, %30, %31, %32, %33, %34, %35, %36, %37, %38, %39, %40, %41, %42, %43, %44, %45, %46, %47, %48, %49, %50, %51, %52, %53, %54, %55, %56, %57, %58, %59, %60, %61, %62, %63, %64, %65, %66, %67, %68, %69, %70, %71, %72, %73, %74, %75, %76, %77, %78, %79, %80, %81, %82, %83, %84, %85, %86, %87, %88, %89, %90, %91, %92, %93, %94, %95}, %96, %97, p, 1, 1, 0, 1;\n}\n"
  : "+f"(d[0]), "+f"(d[1]), "+f"(d[2]), "+f"(d[3]), "+f"(d[4]), "+f"(d[5]), "+f"(d[6]), "+f"(d[7]), "+f"(d[8]), "+f"(d[9]), "+f"(d[10]), "+f"(d[11]), "+f"(d[12]), "+f"(d[13]), "+f"(d[14]), "+f"(d[15]), "+f"(d[16]), "+f"(d[17]), "+f"(d[18]), "+f"(d[19]), "+f"(d[20]), "+f"(d[21]), "+f"(d[22]), "+f"(d[23]), "+f"(d[24]), "+f"(d[25]), "+f"(d[26]), "+f"(d[27]), "+f"(d[28]), "+f"(d[29]), "+f"(d[30]), "+f"(d[31]), "+f"(d[32]), "+f"(d[33]), "+f"(d[34]), "+f"(d[35]), "+f"(d[36]), "+f"(d[37]), "+f"(d[38]), "+f"(d[39]), "+f"(d[40]), "+f"(d[41]), "+f"(d[42]), "+f"(d[43]), "+f"(d[44]), "+f"(d[45]), "+f"(d[46]), "+f"(d[47]), "+f"(d[48]), "+f"(d[49]), "+f"(d[50]), "+f"(d[51]), "+f"(d[52]), "+f"(d[53]), "+f"(d[54]), "+f"(d[55]), "+f"(d[56]), "+f"(d[57]), "+f"(d[58]), "+f"(d[59]), "+f"(d[60]), "+f"(d[61]), "+f"(d[62]), "+f"(d[63]), "+f"(d[64]), "+f"(d[65]), "+f"(d[66]), "+f"(d[67]), "+f"(d[68]), "+f"(d[69]), "+f"(d[70]), "+f"(d[71]), "+f"(d[72]), "+f"(d[73]), "+f"(d[74]), "+f"(d[75]), "+f"(d[76]), "+f"(d[77]), "+f"(d[78]), "+f"(d[79]), "+f"(d[80]), "+f"(d[81]), "+f"(d[82]), "+f"(d[83]), "+f"(d[84]), "+f"(d[85]), "+f"(d[86]), "+f"(d[87]), "+f"(d[88]), "+f"(d[89]), "+f"(d[90]), "+f"(d[91]), "+f"(d[92]), "+f"(d[93]), "+f"(d[94]), "+f"(d[95]) : "l"(da), "l"(db), "r"(sd));
}
__device__ __forceinline__ void wg_ss48(float (&d)[24], uint64_t da, uint64_t db, int sd) {
  asm volatile("{\n.reg .pred p;\nsetp.ne.b32 p, %26, 0;\n"
  "wgmma.mma_async.sync.aligned.m64n48k16.f32.bf16.bf16 {%0, %1, %2, %3, %4, %5, %6, %7, %8, %9, %10, %11, %12, %13, %14, %15, %16, %17, %18, %19, %20, %21, %22, %23}, %24, %25, p, 1, 1, 0, 1;\n}\n"
  : "+f"(d[0]), "+f"(d[1]), "+f"(d[2]), "+f"(d[3]), "+f"(d[4]), "+f"(d[5]), "+f"(d[6]), "+f"(d[7]), "+f"(d[8]), "+f"(d[9]), "+f"(d[10]), "+f"(d[11]), "+f"(d[12]), "+f"(d[13]), "+f"(d[14]), "+f"(d[15]), "+f"(d[16]), "+f"(d[17]), "+f"(d[18]), "+f"(d[19]), "+f"(d[20]), "+f"(d[21]), "+f"(d[22]), "+f"(d[23]) : "l"(da), "l"(db), "r"(sd));
}
__device__ __forceinline__ void wg_rs80(float (&d)[40], uint32_t a0, uint32_t a1, uint32_t a2, uint32_t a3, uint64_t db, int sd) {
  asm volatile("{\n.reg .pred p;\nsetp.ne.b32 p, %45, 0;\n"
  "wgmma.mma_async.sync.aligned.m64n80k16.f32.bf16.bf16 {%0, %1, %2, %3, %4, %5, %6, %7, %8, %9, %10, %11, %12, %13, %14, %15, %16, %17, %18, %19, %20, %21, %22, %23, %24, %25, %26, %27, %28, %29, %30, %31, %32, %33, %34, %35, %36, %37, %38, %39}, {%40, %41, %42, %43}, %44, p, 1, 1, 1;\n}\n"
  : "+f"(d[0]), "+f"(d[1]), "+f"(d[2]), "+f"(d[3]), "+f"(d[4]), "+f"(d[5]), "+f"(d[6]), "+f"(d[7]), "+f"(d[8]), "+f"(d[9]), "+f"(d[10]), "+f"(d[11]), "+f"(d[12]), "+f"(d[13]), "+f"(d[14]), "+f"(d[15]), "+f"(d[16]), "+f"(d[17]), "+f"(d[18]), "+f"(d[19]), "+f"(d[20]), "+f"(d[21]), "+f"(d[22]), "+f"(d[23]), "+f"(d[24]), "+f"(d[25]), "+f"(d[26]), "+f"(d[27]), "+f"(d[28]), "+f"(d[29]), "+f"(d[30]), "+f"(d[31]), "+f"(d[32]), "+f"(d[33]), "+f"(d[34]), "+f"(d[35]), "+f"(d[36]), "+f"(d[37]), "+f"(d[38]), "+f"(d[39]) : "r"(a0), "r"(a1), "r"(a2), "r"(a3), "l"(db), "r"(sd));
}
__device__ __forceinline__ void wg_rs224(float (&d)[112], uint32_t a0, uint32_t a1, uint32_t a2, uint32_t a3, uint64_t db, int sd) {
  asm volatile("{\n.reg .pred p;\nsetp.ne.b32 p, %117, 0;\n"
  "wgmma.mma_async.sync.aligned.m64n224k16.f32.bf16.bf16 {%0, %1, %2, %3, %4, %5, %6, %7, %8, %9, %10, %11, %12, %13, %14, %15, %16, %17, %18, %19, %20, %21, %22, %23, %24, %25, %26, %27, %28, %29, %30, %31, %32, %33, %34, %35, %36, %37, %38, %39, %40, %41, %42, %43, %44, %45, %46, %47, %48, %49, %50, %51, %52, %53, %54, %55, %56, %57, %58, %59, %60, %61, %62, %63, %64, %65, %66, %67, %68, %69, %70, %71, %72, %73, %74, %75, %76, %77, %78, %79, %80, %81, %82, %83, %84, %85, %86, %87, %88, %89, %90, %91, %92, %93, %94, %95, %96, %97, %98, %99, %100, %101, %102, %103, %104, %105, %106, %107, %108, %109, %110, %111}, {%112, %113, %114, %115}, %116, p, 1, 1, 1;\n}\n"
  : "+f"(d[0]), "+f"(d[1]), "+f"(d[2]), "+f"(d[3]), "+f"(d[4]), "+f"(d[5]), "+f"(d[6]), "+f"(d[7]), "+f"(d[8]), "+f"(d[9]), "+f"(d[10]), "+f"(d[11]), "+f"(d[12]), "+f"(d[13]), "+f"(d[14]), "+f"(d[15]), "+f"(d[16]), "+f"(d[17]), "+f"(d[18]), "+f"(d[19]), "+f"(d[20]), "+f"(d[21]), "+f"(d[22]), "+f"(d[23]), "+f"(d[24]), "+f"(d[25]), "+f"(d[26]), "+f"(d[27]), "+f"(d[28]), "+f"(d[29]), "+f"(d[30]), "+f"(d[31]), "+f"(d[32]), "+f"(d[33]), "+f"(d[34]), "+f"(d[35]), "+f"(d[36]), "+f"(d[37]), "+f"(d[38]), "+f"(d[39]), "+f"(d[40]), "+f"(d[41]), "+f"(d[42]), "+f"(d[43]), "+f"(d[44]), "+f"(d[45]), "+f"(d[46]), "+f"(d[47]), "+f"(d[48]), "+f"(d[49]), "+f"(d[50]), "+f"(d[51]), "+f"(d[52]), "+f"(d[53]), "+f"(d[54]), "+f"(d[55]), "+f"(d[56]), "+f"(d[57]), "+f"(d[58]), "+f"(d[59]), "+f"(d[60]), "+f"(d[61]), "+f"(d[62]), "+f"(d[63]), "+f"(d[64]), "+f"(d[65]), "+f"(d[66]), "+f"(d[67]), "+f"(d[68]), "+f"(d[69]), "+f"(d[70]), "+f"(d[71]), "+f"(d[72]), "+f"(d[73]), "+f"(d[74]), "+f"(d[75]), "+f"(d[76]), "+f"(d[77]), "+f"(d[78]), "+f"(d[79]), "+f"(d[80]), "+f"(d[81]), "+f"(d[82]), "+f"(d[83]), "+f"(d[84]), "+f"(d[85]), "+f"(d[86]), "+f"(d[87]), "+f"(d[88]), "+f"(d[89]), "+f"(d[90]), "+f"(d[91]), "+f"(d[92]), "+f"(d[93]), "+f"(d[94]), "+f"(d[95]), "+f"(d[96]), "+f"(d[97]), "+f"(d[98]), "+f"(d[99]), "+f"(d[100]), "+f"(d[101]), "+f"(d[102]), "+f"(d[103]), "+f"(d[104]), "+f"(d[105]), "+f"(d[106]), "+f"(d[107]), "+f"(d[108]), "+f"(d[109]), "+f"(d[110]), "+f"(d[111]) : "r"(a0), "r"(a1), "r"(a2), "r"(a3), "l"(db), "r"(sd));
}
__device__ __forceinline__ void wg_rs64k(float (&d)[32], uint32_t a0, uint32_t a1, uint32_t a2, uint32_t a3, uint64_t db, int sd) {
  asm volatile("{\n.reg .pred p;\nsetp.ne.b32 p, %37, 0;\n"
  "wgmma.mma_async.sync.aligned.m64n64k16.f32.bf16.bf16 {%0, %1, %2, %3, %4, %5, %6, %7, %8, %9, %10, %11, %12, %13, %14, %15, %16, %17, %18, %19, %20, %21, %22, %23, %24, %25, %26, %27, %28, %29, %30, %31}, {%32, %33, %34, %35}, %36, p, 1, 1, 0;\n}\n"
  : "+f"(d[0]), "+f"(d[1]), "+f"(d[2]), "+f"(d[3]), "+f"(d[4]), "+f"(d[5]), "+f"(d[6]), "+f"(d[7]), "+f"(d[8]), "+f"(d[9]), "+f"(d[10]), "+f"(d[11]), "+f"(d[12]), "+f"(d[13]), "+f"(d[14]), "+f"(d[15]), "+f"(d[16]), "+f"(d[17]), "+f"(d[18]), "+f"(d[19]), "+f"(d[20]), "+f"(d[21]), "+f"(d[22]), "+f"(d[23]), "+f"(d[24]), "+f"(d[25]), "+f"(d[26]), "+f"(d[27]), "+f"(d[28]), "+f"(d[29]), "+f"(d[30]), "+f"(d[31]) : "r"(a0), "r"(a1), "r"(a2), "r"(a3), "l"(db), "r"(sd));
}
__device__ __forceinline__ void wg_rs24(float (&d)[12], uint32_t a0, uint32_t a1, uint32_t a2, uint32_t a3, uint64_t db, int sd) {
  asm volatile("{\n.reg .pred p;\nsetp.ne.b32 p, %17, 0;\n"
  "wgmma.mma_async.sync.aligned.m64n24k16.f32.bf16.bf16 {%0, %1, %2, %3, %4, %5, %6, %7, %8, %9, %10, %11}, {%12, %13, %14, %15}, %16, p, 1, 1, 1;\n}\n"
  : "+f"(d[0]), "+f"(d[1]), "+f"(d[2]), "+f"(d[3]), "+f"(d[4]), "+f"(d[5]), "+f"(d[6]), "+f"(d[7]), "+f"(d[8]), "+f"(d[9]), "+f"(d[10]), "+f"(d[11]) : "r"(a0), "r"(a1), "r"(a2), "r"(a3), "l"(db), "r"(sd));
}
__device__ __forceinline__ void wg_rs128(float (&d)[64], uint32_t a0, uint32_t a1, uint32_t a2, uint32_t a3, uint64_t db, int sd) {
  asm volatile("{\n.reg .pred p;\nsetp.ne.b32 p, %69, 0;\n"
  "wgmma.mma_async.sync.aligned.m64n128k16.f32.bf16.bf16 {%0, %1, %2, %3, %4, %5, %6, %7, %8, %9, %10, %11, %12, %13, %14, %15, %16, %17, %18, %19, %20, %21, %22, %23, %24, %25, %26, %27, %28, %29, %30, %31, %32, %33, %34, %35, %36, %37, %38, %39, %40, %41, %42, %43, %44, %45, %46, %47, %48, %49, %50, %51, %52, %53, %54, %55, %56, %57, %58, %59, %60, %61, %62, %63}, {%64, %65, %66, %67}, %68, p, 1, 1, 1;\n}\n"
  : "+f"(d[0]), "+f"(d[1]), "+f"(d[2]), "+f"(d[3]), "+f"(d[4]), "+f"(d[5]), "+f"(d[6]), "+f"(d[7]), "+f"(d[8]), "+f"(d[9]), "+f"(d[10]), "+f"(d[11]), "+f"(d[12]), "+f"(d[13]), "+f"(d[14]), "+f"(d[15]), "+f"(d[16]), "+f"(d[17]), "+f"(d[18]), "+f"(d[19]), "+f"(d[20]), "+f"(d[21]), "+f"(d[22]), "+f"(d[23]), "+f"(d[24]), "+f"(d[25]), "+f"(d[26]), "+f"(d[27]), "+f"(d[28]), "+f"(d[29]), "+f"(d[30]), "+f"(d[31]), "+f"(d[32]), "+f"(d[33]), "+f"(d[34]), "+f"(d[35]), "+f"(d[36]), "+f"(d[37]), "+f"(d[38]), "+f"(d[39]), "+f"(d[40]), "+f"(d[41]), "+f"(d[42]), "+f"(d[43]), "+f"(d[44]), "+f"(d[45]), "+f"(d[46]), "+f"(d[47]), "+f"(d[48]), "+f"(d[49]), "+f"(d[50]), "+f"(d[51]), "+f"(d[52]), "+f"(d[53]), "+f"(d[54]), "+f"(d[55]), "+f"(d[56]), "+f"(d[57]), "+f"(d[58]), "+f"(d[59]), "+f"(d[60]), "+f"(d[61]), "+f"(d[62]), "+f"(d[63]) : "r"(a0), "r"(a1), "r"(a2), "r"(a3), "l"(db), "r"(sd));
}
__device__ __forceinline__ void wg_rs64(float (&d)[32], uint32_t a0, uint32_t a1, uint32_t a2, uint32_t a3, uint64_t db, int sd) {
  asm volatile("{\n.reg .pred p;\nsetp.ne.b32 p, %37, 0;\n"
  "wgmma.mma_async.sync.aligned.m64n64k16.f32.bf16.bf16 {%0, %1, %2, %3, %4, %5, %6, %7, %8, %9, %10, %11, %12, %13, %14, %15, %16, %17, %18, %19, %20, %21, %22, %23, %24, %25, %26, %27, %28, %29, %30, %31}, {%32, %33, %34, %35}, %36, p, 1, 1, 1;\n}\n"
  : "+f"(d[0]), "+f"(d[1]), "+f"(d[2]), "+f"(d[3]), "+f"(d[4]), "+f"(d[5]), "+f"(d[6]), "+f"(d[7]), "+f"(d[8]), "+f"(d[9]), "+f"(d[10]), "+f"(d[11]), "+f"(d[12]), "+f"(d[13]), "+f"(d[14]), "+f"(d[15]), "+f"(d[16]), "+f"(d[17]), "+f"(d[18]), "+f"(d[19]), "+f"(d[20]), "+f"(d[21]), "+f"(d[22]), "+f"(d[23]), "+f"(d[24]), "+f"(d[25]), "+f"(d[26]), "+f"(d[27]), "+f"(d[28]), "+f"(d[29]), "+f"(d[30]), "+f"(d[31]) : "r"(a0), "r"(a1), "r"(a2), "r"(a3), "l"(db), "r"(sd));
}

__device__ __forceinline__ uint32_t kv_addr(int i) {
  return 94208u + KVB * (uint32_t)((0x541032u >> (4 * i)) & 15u);
}
__device__ __forceinline__ uint32_t w1b_addr(int s) {
  return (s == 3 || s == 4) ? (uint32_t)(s - 3) * 35840u : 102400u + (uint32_t)(s >= 5 ? s - 5 : s) * 35840u;
}
__device__ __forceinline__ void stg128(void* p, uint32_t a, uint32_t b, uint32_t c, uint32_t d) {
  asm volatile("st.global.v4.u32 [%0], {%1,%2,%3,%4};" ::"l"(p), "r"(a), "r"(b), "r"(c), "r"(d) : "memory");
}
__device__ __forceinline__ void stg32(void* p, uint32_t a) { asm volatile("st.global.u32 [%0], %1;" ::"l"(p), "r"(a) : "memory"); }
__device__ __forceinline__ void ld_tile(uint32_t (&a)[20], const uint8_t* p) {
#pragma unroll
  for (int k = 0; k < 5; k++)
    asm volatile("ld.relaxed.gpu.global.v4.u32 {%0,%1,%2,%3}, [%4];" : "=r"(a[4 * k]), "=r"(a[4 * k + 1]), "=r"(a[4 * k + 2]), "=r"(a[4 * k + 3]) : "l"(p + k * 512) : "memory");
}
__device__ __forceinline__ uint32_t tag16(uint32_t v, uint32_t tag) { return (v & ~TAGM) | tag; }
__device__ __forceinline__ float tag32(float v, uint32_t ep) { return __uint_as_float((__float_as_uint(v) & ~3u) | ep); }
__device__ __forceinline__ void fix_tile(uint32_t (&a)[20], const uint8_t* p, uint32_t tag) {
  uint32_t n = 0;
  while (__any_sync(0xffffffffu, (((a[0] ^ tag) | (a[4] ^ tag) | (a[8] ^ tag) | (a[12] ^ tag) | (a[16] ^ tag)) & TAGM) != 0u) && ++n < SPIN_MAX) ld_tile(a, p);
}
__device__ __forceinline__ void probe_wait(uint32_t& ready, int i, const void* p, uint32_t tag) {
  uint32_t n = 0;
  while (!((ready >> i) & 1u) && ++n < SPIN_MAX) ready = __ballot_sync(0xffffffffu, ((ldcg32(p) ^ tag) & TAGM) == 0u);
}
__device__ __forceinline__ float gather16(const float* p, int stride, uint32_t ep) {
  uint32_t v[16], n = 0;
  while (true) {
    uint32_t bad = 0;
#pragma unroll
    for (int i = 0; i < 16; i++) v[i] = ldcg32(p + i * stride);
#pragma unroll
    for (int i = 0; i < 16; i++) bad |= v[i] ^ ep;
    if (!__any_sync(0xffffffffu, (bad & 3u) != 0u) || ++n >= SPIN_MAX) break;
  }
  float s = 0.f;
#pragma unroll
  for (int i = 0; i < 16; i++) s += __uint_as_float(v[i]);
  return s;
}
__device__ __forceinline__ void ld4(uint4 (&v)[4], const uint8_t* p) {
#pragma unroll
  for (int i = 0; i < 4; i++) v[i] = ldcg128(p + i * 512);
}
__device__ __forceinline__ void fix4_add(float (&acc)[32], uint4 (&v)[4], const uint8_t* p, uint32_t tag) {
  uint32_t n = 0;
  while (__any_sync(0xffffffffu, (((v[0].x ^ tag) | (v[1].x ^ tag) | (v[2].x ^ tag) | (v[3].x ^ tag)) & TAGM) != 0u) && ++n < SPIN_MAX) ld4(v, p);
#pragma unroll
  for (int i = 0; i < 4; i++) {
    acc[8 * i + 0] += bf_lo(v[i].x); acc[8 * i + 1] += bf_hi(v[i].x); acc[8 * i + 2] += bf_lo(v[i].y); acc[8 * i + 3] += bf_hi(v[i].y);
    acc[8 * i + 4] += bf_lo(v[i].z); acc[8 * i + 5] += bf_hi(v[i].z); acc[8 * i + 6] += bf_lo(v[i].w); acc[8 * i + 7] += bf_hi(v[i].w);
  }
}

template <int H>
__device__ __forceinline__ void qk_issue(float (&s)[32], const uint32_t (&q)[24], uint32_t kb) {
  constexpr uint64_t HI = desc_hi(1024, 128, 0);
  constexpr int J0 = (H == 0) ? 0 : (H == 1) ? 2 : (H == 2) ? 5 : 7;
  wg_rs64k(s, q[H * 6 + 0], q[H * 6 + 1], q[H * 6 + 2], q[H * 6 + 3], mkdesc(kb + J0 * 1024, HI), 0);
  wg_rs64k(s, q[H * 6 + 4], q[H * 6 + 5], 0u, 0u, mkdesc(kb + (J0 + 2) * 1024, HI), 1);
}
template <int H>
__device__ __forceinline__ void pv_issue(float (&o)[12], const uint32_t (&p)[16], uint32_t kb) {
  constexpr uint64_t HI = desc_hi(128, 1024, 0);
  constexpr int J0 = 3 * H;
#pragma unroll
  for (int i = 0; i < 4; i++)
    wg_rs24(o, p[4 * i], p[4 * i + 1], p[4 * i + 2], p[4 * i + 3], mkdesc(kb + 10240 + J0 * 1024 + i * 256, HI), 1);
}
__device__ __forceinline__ void softmax_chunk(float (&s)[32], uint32_t (&p)[16], float (&o)[12], float (&m)[2]) {
  float a0 = fmaxf(s[0], s[1]), a1 = fmaxf(s[2], s[3]), b0 = fmaxf(s[4], s[5]), b1 = fmaxf(s[6], s[7]);
#pragma unroll
  for (int t = 2; t < 8; t += 2) {
    a0 = fmaxf(a0, fmaxf(s[4 * t], s[4 * t + 1]));
    a1 = fmaxf(a1, fmaxf(s[4 * t + 2], s[4 * t + 3]));
    b0 = fmaxf(b0, fmaxf(s[4 * t + 4], s[4 * t + 5]));
    b1 = fmaxf(b1, fmaxf(s[4 * t + 6], s[4 * t + 7]));
  }
  a0 = fmaxf(a0, b0);
  a1 = fmaxf(a1, b1);
  a0 = fmaxf(a0, __shfl_xor_sync(0xffffffffu, a0, 1));
  a1 = fmaxf(a1, __shfl_xor_sync(0xffffffffu, a1, 1));
  a0 = fmaxf(a0, __shfl_xor_sync(0xffffffffu, a0, 2));
  a1 = fmaxf(a1, __shfl_xor_sync(0xffffffffu, a1, 2));
  float n0 = fmaxf(m[0], a0), n1 = fmaxf(m[1], a1);
  float al0 = ex2(m[0] - n0), al1 = ex2(m[1] - n1);
  m[0] = n0;
  m[1] = n1;
#pragma unroll
  for (int t = 0; t < 8; t++) {
    float e0 = ex2(s[4 * t] - n0), e1 = ex2(s[4 * t + 1] - n0), e2 = ex2(s[4 * t + 2] - n1), e3 = ex2(s[4 * t + 3] - n1);
    p[2 * t] = pack2(e0, e1);
    p[2 * t + 1] = pack2(e2, e3);
  }
#pragma unroll
  for (int t = 0; t < 3; t++) {
    o[4 * t] *= al0; o[4 * t + 1] *= al0; o[4 * t + 2] *= al1; o[4 * t + 3] *= al1;
  }
}
template <int H>
__device__ __forceinline__ void comb_task(float (&s0)[32], float (&s1)[32], uint32_t (&p0)[16], uint32_t (&p1)[16], const uint32_t (&q)[24],
                                          float (&o)[12], float (&m)[2], uint32_t kd, uint32_t ka, bool anti, int dthr) {
  asm volatile("" : "+r"(dthr));
  WG_FENCE();
  qk_issue<H>(s0, q, kd);
  qk_issue<H>(s1, q, ka);
  WG_COMMIT();
  WG_WAIT(0);
  reg_fence(s0); reg_fence(s1); reg_fence(o);
  if (!anti) {
#pragma unroll
    for (int i = 0; i < 32; i++) asm volatile("mov.b32 %0, 0xff800000;" : "=f"(s1[i]));
  }
#pragma unroll
  for (int t = 0; t < 8; t++) {
    s0[4 * t + 0] = (8 * t + 0 <= dthr) ? s0[4 * t + 0] : s1[4 * t + 0];
    s0[4 * t + 1] = (8 * t + 1 <= dthr) ? s0[4 * t + 1] : s1[4 * t + 1];
    s0[4 * t + 2] = (8 * t - 8 <= dthr) ? s0[4 * t + 2] : s1[4 * t + 2];
    s0[4 * t + 3] = (8 * t - 7 <= dthr) ? s0[4 * t + 3] : s1[4 * t + 3];
  }
  softmax_chunk(s0, p0, o, m);
#pragma unroll
  for (int t = 0; t < 8; t++) {
    uint32_t k0 = (8 * t + 1 <= dthr) ? 0xffffffffu : ((8 * t <= dthr) ? 0x0000ffffu : 0u);
    uint32_t k1 = (8 * t - 7 <= dthr) ? 0xffffffffu : ((8 * t - 8 <= dthr) ? 0x0000ffffu : 0u);
    p1[2 * t] = p0[2 * t] & ~k0;
    p0[2 * t] &= k0;
    p1[2 * t + 1] = p0[2 * t + 1] & ~k1;
    p0[2 * t + 1] &= k1;
  }
  WG_FENCE();
  pv_issue<H>(o, p0, kd);
  pv_issue<H>(o, p1, ka);
  WG_COMMIT();
}

__device__ __forceinline__ void store_partial64(const float* a, uint8_t* dst, uint32_t tag) {
#pragma unroll
  for (int i = 0; i < 4; i++) {
    uint4 v;
    v.x = tag16(pack2(a[8 * i + 0], a[8 * i + 1]), tag);
    v.y = pack2(a[8 * i + 2], a[8 * i + 3]);
    v.z = pack2(a[8 * i + 4], a[8 * i + 5]);
    v.w = pack2(a[8 * i + 6], a[8 * i + 7]);
    *reinterpret_cast<uint4*>(dst + i * 512) = v;
  }
}

__global__ void __cluster_dims__(2, 1, 1) __launch_bounds__(384, 1) fused_block_kernel(const __grid_constant__ Params P) {
  extern __shared__ __align__(1024) uint8_t smem[];
  const uint32_t sb = s2u(smem);
  const int tid = threadIdx.x, lane = tid & 31, warp = __shfl_sync(0xffffffffu, tid >> 5, 0);
  uint32_t rank, smid;
  asm("mov.u32 %0, %%cluster_ctarank;" : "=r"(rank));
  asm("mov.u32 %0, %%smid;" : "=r"(smid));
  int g, c;
  {
    int pr = smid >> 1;
    if (pr < 32) { g = pr & 7; c = pr >> 3; }
    else if (pr < 60) { g = 1 + (pr - 32) % 7; c = 4 + (pr - 32) / 7; }
    else if (pr < 62) { return; }
    else { g = 0; c = 4 + (pr - 62); }
  }
  const int rb = 2 * g + (int)rank;
  const int tile = rb * 8 + c;
  const uint32_t bars = sb + OFF_MISC;
#define BAR(i) (bars + 8u * (uint32_t)(i))
  uint4 xv[5], wv[5];
  if (warp < 8) {
    const uint8_t* xb = reinterpret_cast<const uint8_t*>(P.x) + (size_t)(rb * 128 + c * 16 + warp * 2 + (lane >> 4)) * 1280 + (lane & 15) * 16;
    const int cl = lane < 30 ? lane : 29;
    const uint8_t* wb = reinterpret_cast<const uint8_t*>(P.wqkv) + (size_t)(rb * 40 + warp * 5) * 3840 + (cl / 10) * 1280 + c * 160 + (cl % 10) * 16;
#pragma unroll
    for (int i = 0; i < 5; i++) xv[i] = __ldg(reinterpret_cast<const uint4*>(xb + i * 256));
#pragma unroll
    for (int i = 0; i < 5; i++) wv[i] = __ldg(reinterpret_cast<const uint4*>(wb + i * 3840));
  }
  if (lane == 0) {
    const int i0 = (warp < 8 ? warp + 4 : warp - 8) * 4;
#pragma unroll
    for (int u = 0; u < 4; u++) {
      const int i = i0 + u;
      mbar_init(BAR(i), i < B_KVOWN ? 1 : i < B_Q23 ? 4 : i < B_QEMPTY ? 8 : 16);
    }
    asm volatile("fence.mbarrier_init.release.cluster;" ::: "memory");
  }
  __syncwarp();
  asm volatile("barrier.cluster.arrive.relaxed.aligned;" ::: "memory");
  const int odd = c & 1;
  const int sc = (27 * c + 3) >> 2;

  if (warp >= 8) {
    asm volatile("setmaxnreg.dec.sync.aligned.u32 56;");
    if (warp == 8) {
      const int mainch = (c >> 1) * 5 + (odd ? 3 : 0), leftch = (c >> 1) * 10 + (odd ? 5 : 4);
      if (lane == 0) {
        mbar_expect(BAR(B_QFULL), QST);
        tma2d(sb, &P.mX, 0, rb * 128, BAR(B_QFULL));
      }
      __syncwarp();
      STAMPW(7);
      asm volatile("barrier.cluster.wait.acquire.aligned;" ::: "memory");
      STAMPW(8);
      if (lane == 0) {
#pragma unroll 1
        for (int kt = 0; kt < 10; kt++) {
          const int st = kt & 3;
          if (kt >= 4) mbar_wait(BAR(B_QEMPTY + st), ((kt >> 2) - 1) & 1);
          const uint32_t a = sb + st * QST, fb = BAR(B_QFULL + st);
          if (kt) mbar_expect(fb, QST);
          tma4d_mc(a + 16384 + rank * 12288, &P.mWqM, 0, kt * 64 + rank * 32, mainch, 0, fb);
          tma4d_mc(a + 40960 + rank * 3072, &P.mWqL, 0, kt * 64 + rank * 32, leftch, 0, fb);
          if (kt) tma2d(a, &P.mX, kt * 64, rb * 128, fb);
          if (kt == 3) STAMPW(9);
        }
        const CUtensorMap* mW1 = rank ? &P.mW1b : &P.mW1a;
        asm volatile("prefetch.tensormap [%0];" ::"l"(&P.mWo) : "memory");
        asm volatile("prefetch.tensormap [%0];" ::"l"(mW1) : "memory");
        asm volatile("prefetch.tensormap [%0];" ::"l"(&P.mW2) : "memory");
        mbar_wait(BAR(B_QEMPTY + 0), 0);
        mbar_wait(BAR(B_QEMPTY + 1), 0);
        mbar_expect(BAR(B_WOB), 89600);
#pragma unroll 1
        for (int i = 0; i < 4 - (int)rank; i++) {
          const int pos = rank * 4 + i;
          tma3d_mc(sb + OFF_WOB + pos * 12800, &P.mWo, 0, ((c + pos) & 7) * 80, c * 5, BAR(B_WOB));
        }
#pragma unroll 1
        for (int s = 0; s < 8; s++) {
          if (s == 0) {
            mbar_wait(BAR(B_ATTP), 0);
            mbar_expect(BAR(B_WOB7), 12800);
            if (rank) tma3d_mc(sb + OFF_WOB + 7 * 12800, &P.mWo, 0, ((c + 7) & 7) * 80, c * 5, BAR(B_WOB7));
          } else if (s == 3) mbar_wait(BAR(B_WODP), 0);
          else if (s >= 5) mbar_wait(BAR(B_BEMPTY + s - 5), 0);
          const uint32_t fb = BAR(B_BFULL + s);
          mbar_expect(fb, 35840);
          tma3d_mc(sb + w1b_addr(s) + rank * 20480, mW1, 0, ((c + s) & 7) * 80, sc + rank * 4, fb);
        }
#pragma unroll 1
        for (int s = 0; s < 5; s++) {
          mbar_wait(s < 4 ? BAR(B_BEMPTY + 4 + s) : BAR(B_W2E), 0);
          const uint32_t dst = sb + (s & 3) * W2SLOT + rank * 14336, fb = BAR(B_W2FULL + s);
          const int bx0 = s == 0 ? 8 : ((c + 2 * s - 1) & 7), bx1 = s == 0 ? 9 : ((c + 2 * s) & 7);
          mbar_expect(fb, W2SLOT);
          tma2d_mc(dst, &P.mW2, bx0 * 64, sc * 32 + rank * 112, fb);
          tma2d_mc(dst + 28672, &P.mW2, bx1 * 64, sc * 32 + rank * 112, fb);
        }
      }
    } else {
      const uint32_t epoch = ldcg32(&g_epoch[tile]) + 1u;
      const uint32_t ep = epoch & 3u, tag = (epoch & 1u) | ((epoch & 2u) << 15);
      asm volatile("barrier.cluster.wait.acquire.aligned;" ::: "memory");
      if (warp == 11) {
        mbar_wait(BAR(B_PRE), 0);
#pragma unroll
        for (int u = 0; u < 2; u++) {
          const int q = lane + 32 * u;
          if (q < 60) {
            float4 a = make_float4(0.f, 0.f, 0.f, 0.f);
#pragma unroll
            for (int i = 0; i < 8; i++) {
              const float4 v = *reinterpret_cast<const float4*>(smem + OFF_PRE + i * 960 + q * 16);
              a.x += v.x; a.y += v.y; a.z += v.z; a.w += v.w;
            }
            *reinterpret_cast<float4*>(&g_csq[tile * 240 + q * 4]) = make_float4(tag32(a.x, ep), tag32(a.y, ep), tag32(a.z, ep), tag32(a.w, ep));
          }
        }
        STAMPW(0);
        mbar_wait(BAR(B_QFULL + 3), 0);
        if (lane == 0) {
          l2_prefetch_bulk(reinterpret_cast<const uint8_t*>(P.wo) + tile * 6400, 6400);
          l2_prefetch_bulk(reinterpret_cast<const uint8_t*>(P.w2) + tile * 17280, 17280);
        }
      } else if (warp == 10) {
        mbar_wait(BAR(B_QFULL + 3), 0);
        const int col = sc * 32 + lane * 8;
        const uint8_t* wb = reinterpret_cast<const uint8_t*>(P.w1) + (size_t)rb * 40 * 3456 + (size_t)col * 2;
        float acc[8];
#pragma unroll
        for (int i = 0; i < 8; i++) acc[i] = 0.f;
        if (lane < 28 && col < 1728) {
#pragma unroll 1
          for (int i = 0; i < 40; i += 8) {
            uint4 v[8];
#pragma unroll
            for (int u = 0; u < 8; u++) v[u] = __ldg(reinterpret_cast<const uint4*>(wb + (size_t)(i + u) * 3456));
#pragma unroll
            for (int u = 0; u < 8; u++) {
              acc[0] += bf_lo(v[u].x); acc[1] += bf_hi(v[u].x); acc[2] += bf_lo(v[u].y); acc[3] += bf_hi(v[u].y);
              acc[4] += bf_lo(v[u].z); acc[5] += bf_hi(v[u].z); acc[6] += bf_lo(v[u].w); acc[7] += bf_hi(v[u].w);
            }
          }
        }
        if (lane < 28) {
          float4* dst = reinterpret_cast<float4*>(&g_cs1[tile * 224 + lane * 8]);
          dst[0] = make_float4(tag32(acc[0], ep), tag32(acc[1], ep), tag32(acc[2], ep), tag32(acc[3], ep));
          dst[1] = make_float4(tag32(acc[4], ep), tag32(acc[5], ep), tag32(acc[6], ep), tag32(acc[7], ep));
        }
        STAMPW(4);
      }
      mbar_wait(BAR(B_Q23), 0);
#pragma unroll 1
      for (int bi = warp == 9 ? 2 : warp == 10 ? 3 : 1; bi >= 0; bi -= (warp == 9 ? 2 : 4)) {
        const int blk = 2 * rb - 4 + bi;
        if (blk < 0) continue;
        const uint8_t* src = g_kv + (size_t)(blk * 8 + c) * KVB;
        const uint32_t dst = sb + kv_addr(bi);
        uint32_t n = 0, ph = 0;
        while (!__all_sync(0xffffffffu, ((ldcg32(src + 21504 + ((lane & 3) * 16 + 15) * 16 + 4) ^ tag) & TAGM) == 0u) && ++n < SPIN_MAX) {}
        if (warp == 9 && bi == 2) STAMPW(3);
        while (true) {
          if (lane == 0) {
            fence_async_glob();
            mbar_expect(BAR(B_KVLAND + bi), KVB);
            bulk_load(dst, src, KVB, BAR(B_KVLAND + bi));
          }
          mbar_wait(BAR(B_KVLAND + bi), ph);
          ph ^= 1u;
          uint32_t bad = 0;
#pragma unroll 11
          for (int i = 0; i < 44; i++) {
            uint32_t v;
            asm volatile("ld.shared.u32 %0, [%1];" : "=r"(v) : "r"(dst + (i * 32 + lane) * 16 + 4) : "memory");
            bad |= v ^ tag;
          }
          if (!__any_sync(0xffffffffu, (bad & TAGM) != 0u) || ++n >= SPIN_MAX) break;
        }
        if (lane == 0) mbar_arrive(BAR(B_KVFULL + bi));
        if (warp == 9 && bi == 2) STAMPW(5);
      }
      if (warp == 11 && lane == 0) st_flag(&g_epoch[tile], epoch);
    }
  } else {
    const int r = warp >> 2, w = warp & 3, gq = lane >> 2, tq = lane & 3;
    const uint32_t epoch = ldcg32(&g_epoch[tile]) + 1u;
    const uint32_t ep = epoch & 3u, tag = (epoch & 1u) | ((epoch & 2u) << 15);
    {
      float s = 0.f;
#pragma unroll
      for (int i = 0; i < 5; i++)
        s += ((bf_lo(xv[i].x) + bf_hi(xv[i].x)) + (bf_lo(xv[i].y) + bf_hi(xv[i].y))) + ((bf_lo(xv[i].z) + bf_hi(xv[i].z)) + (bf_lo(xv[i].w) + bf_hi(xv[i].w)));
#pragma unroll
      for (int o = 8; o; o >>= 1) s += __shfl_xor_sync(0xffffffffu, s, o);
      const float mean = s * (1.f / 640.f);
      float m2 = 0.f;
#pragma unroll
      for (int i = 0; i < 5; i++) {
        const uint32_t u[4] = {xv[i].x, xv[i].y, xv[i].z, xv[i].w};
#pragma unroll
        for (int j = 0; j < 4; j++) {
          const float d0 = bf_lo(u[j]) - mean, d1 = bf_hi(u[j]) - mean;
          m2 += d0 * d0 + d1 * d1;
        }
      }
#pragma unroll
      for (int o = 8; o; o >>= 1) m2 += __shfl_xor_sync(0xffffffffu, m2, o);
      if ((lane & 15) == 0)
        g_xstat[rb * 128 + c * 16 + warp * 2 + (lane >> 4)] = make_float2(mean, tag32(1.f / sqrtf(m2 * (1.f / 640.f) + 1e-5f), ep));
      float a[8];
#pragma unroll
      for (int i = 0; i < 8; i++) a[i] = 0.f;
#pragma unroll
      for (int u = 0; u < 5; u++) {
        a[0] += bf_lo(wv[u].x); a[1] += bf_hi(wv[u].x); a[2] += bf_lo(wv[u].y); a[3] += bf_hi(wv[u].y);
        a[4] += bf_lo(wv[u].z); a[5] += bf_hi(wv[u].z); a[6] += bf_lo(wv[u].w); a[7] += bf_hi(wv[u].w);
      }
      if (lane < 30) {
        float4* dst = reinterpret_cast<float4*>(smem + OFF_PRE + warp * 960 + lane * 32);
        dst[0] = make_float4(a[0], a[1], a[2], a[3]);
        dst[1] = make_float4(a[4], a[5], a[6], a[7]);
      }
      __syncwarp();
      asm volatile("barrier.cluster.wait.acquire.aligned;" ::: "memory");
      if (lane == 0) mbar_arrive(BAR(B_PRE));
    }
    asm volatile("setmaxnreg.inc.sync.aligned.u32 224;");
    const int b = rb * 2 + r;
    uint32_t q[24];
    STAMP(0);
    {
      float accM[96], accL[24];
      uint2 s0u, s1u;
#pragma unroll 1
      for (int kt = 0; kt < 10; kt++) {
        const int st = kt & 3;
        mbar_wait(BAR(B_QFULL + st), (kt >> 2) & 1);
        if (kt == 0) STAMP(1);
        const uint32_t a = sb + st * QST;
        const uint64_t da = mkdesc(a + r * 8192, desc_hi(16, 1024, 1));
        const uint64_t dm = mkdesc(a + 16384, desc_hi(2048, 512, 2));
        const uint64_t dl = mkdesc(a + 40960, desc_hi(1024, 256, 3));
        reg_fence(accM); reg_fence(accL);
        WG_FENCE();
#pragma unroll
        for (int k = 0; k < 4; k++) {
          wg_ss192(accM, da + k * 2, dm + (k >> 1) * 768 + (k & 1) * 64, kt | k);
          wg_ss48(accL, da + k * 2, dl + (k >> 1) * 192 + (k & 1) * 32, kt | k);
        }
        WG_COMMIT();
        if (kt == 8) {
          const float cs = gather16(g_csq + c * 240 + (tid < 240 ? tid : 239), 1920, ep);
          if (tid < 240) *reinterpret_cast<float*>(smem + OFF_CS + tid * 4) = cs;
          uint32_t n = 0;
          do {
            s0u = ldcg64(&g_xstat[b * 64 + w * 16 + gq]);
            s1u = ldcg64(&g_xstat[b * 64 + w * 16 + gq + 8]);
          } while (__any_sync(0xffffffffu, (((s0u.y ^ ep) | (s1u.y ^ ep)) & 3u) != 0u) && ++n < SPIN_MAX);
          if (lane == 0) mbar_arrive(BAR(B_STAT));
        }
        WG_WAIT(0);
        reg_fence(accM); reg_fence(accL);
        if (lane == 0) {
          mbar_arrive_pair(BAR(B_QEMPTY + st));
          if (kt == 7) mbar_arrive(BAR(B_Q23));
        }
      }
      STAMP(2);
      mbar_wait(BAR(B_STAT), 0);
      mbar_wait(BAR(B_Q23), 0);
      const float2 s0 = make_float2(__uint_as_float(s0u.x), __uint_as_float(s0u.y)), s1 = make_float2(__uint_as_float(s1u.x), __uint_as_float(s1u.y));
      const uint32_t km = tq == 1 ? ~TAGM : 0xffffffffu, kt1 = tq == 1 ? tag : 0u;
      const uint32_t csM = sb + OFF_CS + (odd ? 64 : 0) + tq * 8, csL = sb + OFF_CS + (odd ? 0 : 256) + tq * 8;
      const uint32_t kvo = sb + kv_addr(4 + r) + (uint32_t)(w * 16 + ((lane >> 3) & 1) * 8 + (lane & 7)) * 16u + (uint32_t)(lane >> 4) * 1024u;
      uint8_t* kvg = g_kv + (size_t)(b * 8 + c) * KVB + w * 256 + lane * 4;
      const float qs = 0.22360679774997896f * 1.4426950408889634f;
      const bool lo = tq < 2;
      uint32_t qj[20];
#pragma unroll
      for (int mm = 0; mm < 3; mm++) {
        const int mat = (mm + 1) % 3;
        const float r0 = mat == 0 ? s0.y * qs : s0.y, r1 = mat == 0 ? s1.y * qs : s1.y;
        const float n0 = -s0.x * r0, n1 = -s1.x * r1;
        uint32_t pk[20];
#pragma unroll
        for (int t = 0; t < 10; t++) {
          const float* a = t < 8 ? &accM[(mat * 8 + t) * 4] : &accL[(mat * 2 + t - 8) * 4];
          const float2 cs = lds64f(t < 8 ? csM + mat * 320 + t * 32 : csL + mat * 320 + (t - 8) * 32);
          pk[2 * t] = pack2(fmaf(a[0], r0, cs.x * n0), fmaf(a[1], r0, cs.y * n0));
          pk[2 * t + 1] = pack2(fmaf(a[2], r1, cs.x * n1), fmaf(a[3], r1, cs.y * n1));
        }
        if (mat == 1) {
#pragma unroll
          for (int i = 0; i < 20; i++) pk[i] = (pk[i] & km) | kt1;
          uint8_t* gm = kvg + (odd ? 2048 : 0);
          uint8_t* gl = kvg + (odd ? 0 : 8192);
#pragma unroll
          for (int t = 0; t < 10; t++) {
            uint8_t* p = t < 8 ? gm + t * 1024 : gl + (t - 8) * 1024;
            stg32(p, pk[2 * t]);
            stg32(p + 128, pk[2 * t + 1]);
          }
#pragma unroll
          for (int t = 0; t < 8; t += 2) stsm4(kvo + (odd ? 2048 : 0) + t * 1024, pk[2 * t], pk[2 * t + 1], pk[2 * t + 2], pk[2 * t + 3]);
          stsm4(kvo + (odd ? 0 : 8192), pk[16], pk[17], pk[18], pk[19]);
        } else {
#pragma unroll
          for (int i = 0; i < 20; i++) qj[i] = odd ? pk[(i + 16) % 20] : pk[i];
        }
        if (mat == 2) {
          const uint32_t one = (tq & 1) ? 0u : 0x3f80u;
          uint32_t vv[24];
#pragma unroll
          for (int hp = 0; hp < 2; hp++) {
            const int j = hp * 10;
#pragma unroll
            for (int i = 0; i < 4; i++) { vv[hp * 12 + i] = qj[j + i]; vv[hp * 12 + 8 + i] = qj[j + 6 + i]; }
            vv[hp * 12 + 4] = lo ? qj[j + 4] : one; vv[hp * 12 + 5] = lo ? qj[j + 5] : one;
            vv[hp * 12 + 6] = lo ? one : qj[j + 4]; vv[hp * 12 + 7] = lo ? one : qj[j + 5];
          }
#pragma unroll
          for (int i = 0; i < 24; i++) vv[i] = (vv[i] & km) | kt1;
#pragma unroll
          for (int t = 0; t < 12; t++) {
            stg32(kvg + 10240 + t * 1024, vv[2 * t]);
            stg32(kvg + 10240 + t * 1024 + 128, vv[2 * t + 1]);
          }
#pragma unroll
          for (int t = 0; t < 6; t++) stsm4(kvo + 10240 + t * 2048, vv[4 * t], vv[4 * t + 1], vv[4 * t + 2], vv[4 * t + 3]);
          fence_async_smem();
          __syncwarp();
          if (lane == 0) mbar_arrive(BAR(B_KVOWN + r));
        }
      }
#pragma unroll
      for (int hp = 0; hp < 2; hp++) {
        const int j = hp * 10;
        q[hp * 12 + 0] = qj[j + 0]; q[hp * 12 + 1] = qj[j + 1]; q[hp * 12 + 2] = qj[j + 2]; q[hp * 12 + 3] = qj[j + 3];
        q[hp * 12 + 4] = lo ? qj[j + 4] : 0u; q[hp * 12 + 5] = lo ? qj[j + 5] : 0u;
        q[hp * 12 + 6] = lo ? 0u : qj[j + 4]; q[hp * 12 + 7] = lo ? 0u : qj[j + 5];
        q[hp * 12 + 8] = qj[j + 6]; q[hp * 12 + 9] = qj[j + 7]; q[hp * 12 + 10] = qj[j + 8]; q[hp * 12 + 11] = qj[j + 9];
      }
    }
    STAMP(3);
    uint32_t x0[20], xr[20];
    const int row_lo = b * 64 + w * 16 + gq;
    {
      float o0[12], o1[12], o2[12], o3[12], m[4][2];
#pragma unroll
      for (int i = 0; i < 12; i++) { o0[i] = 0.f; o1[i] = 0.f; o2[i] = 0.f; o3[i] = 0.f; }
#pragma unroll
      for (int i = 0; i < 4; i++) m[i][0] = m[i][1] = -INFINITY;
      float s0[32], s1[32];
      uint32_t p0[16], p1[16];
      const int dthr = w * 16 + gq - 2 * tq;
      mbar_wait(BAR(B_KVOWN + r), 0);
#pragma unroll 1
      for (int it = 0; it < 4; it++) {
        const int bi = ((r ? 0x3124u : 0x3102u) >> (4 * it)) & 15;
        const bool valid = 2 * rb - 4 + bi >= 0;
        if (bi == r) {
          if (valid) mbar_wait(BAR(B_KVFULL + bi), 0);
          const uint32_t kd = sb + kv_addr(4 + r), ka = valid ? sb + kv_addr(bi) : kd;
          comb_task<0>(s0, s1, p0, p1, q, o0, m[0], kd, ka, valid, dthr);
          comb_task<1>(s0, s1, p0, p1, q, o1, m[1], kd, ka, valid, dthr);
          comb_task<2>(s0, s1, p0, p1, q, o2, m[2], kd, ka, valid, dthr);
          comb_task<3>(s0, s1, p0, p1, q, o3, m[3], kd, ka, valid, dthr);
          WG_WAIT(0);
        } else if (valid) {
          mbar_wait(bi == 4 ? BAR(B_KVOWN) : BAR(B_KVFULL + bi), 0);
          if (it == 0) STAMP(18);
          const uint32_t kb = sb + kv_addr(bi);
          WG_FENCE();
          qk_issue<0>(s0, q, kb);
          WG_COMMIT();
          qk_issue<1>(s1, q, kb);
          WG_COMMIT();
          WG_WAIT(1);
          reg_fence(s0); reg_fence(o0);
          softmax_chunk(s0, p0, o0, m[0]);
          WG_FENCE();
          pv_issue<0>(o0, p0, kb);
          WG_COMMIT();
          qk_issue<2>(s0, q, kb);
          WG_COMMIT();
          WG_WAIT(2);
          reg_fence(s1); reg_fence(o1);
          softmax_chunk(s1, p1, o1, m[1]);
          WG_FENCE();
          pv_issue<1>(o1, p1, kb);
          WG_COMMIT();
          qk_issue<3>(s1, q, kb);
          WG_COMMIT();
          WG_WAIT(2);
          reg_fence(s0); reg_fence(o2);
          softmax_chunk(s0, p0, o2, m[2]);
          WG_FENCE();
          pv_issue<2>(o2, p0, kb);
          WG_COMMIT();
          WG_WAIT(1);
          reg_fence(s1); reg_fence(o3);
          softmax_chunk(s1, p1, o3, m[3]);
          WG_FENCE();
          pv_issue<3>(o3, p1, kb);
          WG_COMMIT();
          WG_WAIT(0);
        }
        reg_fence(o0); reg_fence(o1); reg_fence(o2); reg_fence(o3);
        STAMP(24 + it);
      }
      if (lane == 0) mbar_arrive_pair(BAR(B_ATTP));
      const uint8_t* xp = reinterpret_cast<const uint8_t*>(P.x) + (size_t)row_lo * 1280 + c * 160 + tq * 4;
#pragma unroll
      for (int t = 0; t < 10; t++) {
        xr[2 * t] = __ldg(reinterpret_cast<const uint32_t*>(xp + t * 16));
        xr[2 * t + 1] = __ldg(reinterpret_cast<const uint32_t*>(xp + 8 * 1280 + t * 16));
      }
      float inv[4][2];
      inv[0][0] = 1.f / __shfl_sync(0xffffffffu, o0[8], (lane & 28) + 2);
      inv[0][1] = 1.f / __shfl_sync(0xffffffffu, o0[10], (lane & 28) + 2);
      inv[1][0] = 1.f / __shfl_sync(0xffffffffu, o1[0], lane & 28);
      inv[1][1] = 1.f / __shfl_sync(0xffffffffu, o1[2], lane & 28);
      inv[2][0] = 1.f / __shfl_sync(0xffffffffu, o2[8], (lane & 28) + 2);
      inv[2][1] = 1.f / __shfl_sync(0xffffffffu, o2[10], (lane & 28) + 2);
      inv[3][0] = 1.f / __shfl_sync(0xffffffffu, o3[0], lane & 28);
      inv[3][1] = 1.f / __shfl_sync(0xffffffffu, o3[2], lane & 28);
      const bool lo = tq < 2;
#define OPK(dst, o, t, h) do { x0[dst] = pack2(o[4 * (t)] * inv[h][0], o[4 * (t) + 1] * inv[h][0]); x0[dst + 1] = pack2(o[4 * (t) + 2] * inv[h][1], o[4 * (t) + 3] * inv[h][1]); } while (0)
#define OPK2(dst, oa, ha, ob, hb) do { \
        const float i0 = lo ? inv[ha][0] : inv[hb][0], i1 = lo ? inv[ha][1] : inv[hb][1]; \
        x0[dst] = pack2((lo ? oa[8] : ob[0]) * i0, (lo ? oa[9] : ob[1]) * i0); \
        x0[dst + 1] = pack2((lo ? oa[10] : ob[2]) * i1, (lo ? oa[11] : ob[3]) * i1); } while (0)
      OPK(0, o0, 0, 0); OPK(2, o0, 1, 0); OPK2(4, o0, 0, o1, 1); OPK(6, o1, 1, 1); OPK(8, o1, 2, 1);
      OPK(10, o2, 0, 2); OPK(12, o2, 1, 2); OPK2(14, o2, 2, o3, 3); OPK(16, o3, 1, 3); OPK(18, o3, 2, 3);
    }
    const int bw = b * 4 + w;
    const size_t tile_off = (size_t)bw * 20480 + lane * 16;
    const size_t probe_off = (size_t)bw * 20480 + ((c + lane) & 7) * 2560 + 2544;
    {
#pragma unroll
      for (int k = 0; k < 5; k++) {
        x0[4 * k] = tag16(x0[4 * k], tag);
        stg128(g_o + tile_off + c * 2560 + k * 512, x0[4 * k], x0[4 * k + 1], x0[4 * k + 2], x0[4 * k + 3]);
      }
      STAMP(6);
      float acc[40];
#pragma unroll
      for (int t = 0; t < 10; t++) {
        acc[4 * t] = bf_lo(xr[2 * t]); acc[4 * t + 1] = bf_hi(xr[2 * t]); acc[4 * t + 2] = bf_lo(xr[2 * t + 1]); acc[4 * t + 3] = bf_hi(xr[2 * t + 1]);
      }
      constexpr uint64_t HI = desc_hi(2560, 256, 3);
      const uint64_t db = mkdesc(sb + OFF_WOB, HI);
      mbar_wait(BAR(B_WOB), 0);
      WG_FENCE();
#pragma unroll
      for (int k = 0; k < 5; k++) wg_rs80(acc, x0[4 * k], x0[4 * k + 1], x0[4 * k + 2], x0[4 * k + 3], db + k * 32, 1);
      WG_COMMIT();
      {
        const float cs = gather16(g_cs1 + c * 224 + (tid < 224 ? tid : 223), 1792, ep);
        if (tid < 224) *reinterpret_cast<float*>(smem + OFF_XS + tid * 4) = cs;
        __syncwarp();
        if (lane == 0) mbar_arrive(BAR(B_CS1));
      }
      WG_WAIT(0);
      uint32_t xa[7][20], ready = 0;
#pragma unroll
      for (int i = 1; i < 8; i++) {
        probe_wait(ready, i, g_o + probe_off, tag);
        ld_tile(xa[i - 1], g_o + tile_off + ((c + i) & 7) * 2560);
      }
      STAMP(7);
#pragma unroll
      for (int i = 1; i < 8; i++) {
        if (i == 7) mbar_wait(BAR(B_WOB7), 0);
        fix_tile(xa[i - 1], g_o + tile_off + ((c + i) & 7) * 2560, tag);
        WG_FENCE();
#pragma unroll
        for (int k = 0; k < 5; k++) wg_rs80(acc, xa[i - 1][4 * k], xa[i - 1][4 * k + 1], xa[i - 1][4 * k + 2], xa[i - 1][4 * k + 3], db + i * 800 + k * 32, 1);
        WG_COMMIT();
      }
      WG_WAIT(0);
      reg_fence(acc);
      if (lane == 0) mbar_arrive_pair(BAR(B_WODP));
      STAMP(8);
      float sum0 = 0.f, sum1 = 0.f;
#pragma unroll
      for (int t = 0; t < 10; t++) {
        x0[2 * t] = pack2(acc[4 * t], acc[4 * t + 1]);
        x0[2 * t + 1] = pack2(acc[4 * t + 2], acc[4 * t + 3]);
      }
#pragma unroll
      for (int k = 0; k < 5; k++) {
        x0[4 * k] = tag16(x0[4 * k], tag);
        stg128(g_h + tile_off + c * 2560 + k * 512, x0[4 * k], x0[4 * k + 1], x0[4 * k + 2], x0[4 * k + 3]);
      }
#pragma unroll
      for (int t = 0; t < 10; t++) {
        sum0 += bf_lo(x0[2 * t]) + bf_hi(x0[2 * t]);
        sum1 += bf_lo(x0[2 * t + 1]) + bf_hi(x0[2 * t + 1]);
      }
      sum0 += __shfl_xor_sync(0xffffffffu, sum0, 1);
      sum1 += __shfl_xor_sync(0xffffffffu, sum1, 1);
      sum0 += __shfl_xor_sync(0xffffffffu, sum0, 2);
      sum1 += __shfl_xor_sync(0xffffffffu, sum1, 2);
      const float mu0 = sum0 * (1.f / 80.f), mu1 = sum1 * (1.f / 80.f);
      float v0 = 0.f, v1 = 0.f;
#pragma unroll
      for (int t = 0; t < 10; t++) {
        const float d0 = bf_lo(x0[2 * t]) - mu0, d1 = bf_hi(x0[2 * t]) - mu0, d2 = bf_lo(x0[2 * t + 1]) - mu1, d3 = bf_hi(x0[2 * t + 1]) - mu1;
        v0 += d0 * d0 + d1 * d1;
        v1 += d2 * d2 + d3 * d3;
      }
      v0 += __shfl_xor_sync(0xffffffffu, v0, 1);
      v1 += __shfl_xor_sync(0xffffffffu, v1, 1);
      v0 += __shfl_xor_sync(0xffffffffu, v0, 2);
      v1 += __shfl_xor_sync(0xffffffffu, v1, 2);
      if (tq < 2) g_hstat[(bw * 8 + c) * 16 + gq + tq * 8] = make_float2(tq ? mu1 : mu0, tag32(tq ? v1 : v0, ep));
    }
    uint32_t ha[56];
    {
      float acc[112];
      constexpr uint64_t HI = desc_hi(5120, 512, 2);
#define W1_ISSUE(xx, i) do { \
        mbar_wait(BAR(B_BFULL + (i)), 0); \
        if (i) fix_tile(xx, g_h + tile_off + ((c + (i)) & 7) * 2560, tag); \
        const uint64_t db = mkdesc(sb + w1b_addr(i), HI); \
        WG_FENCE(); \
        _Pragma("unroll") for (int k = 0; k < 5; k++) wg_rs224(acc, xx[4 * k], xx[4 * k + 1], xx[4 * k + 2], xx[4 * k + 3], db + k * 64, (i) | k); \
        WG_COMMIT(); } while (0)
#define W1_NEXT(xx, i) do { \
        WG_WAIT(1); \
        if ((i) != 3 && lane == 0) mbar_arrive_pair(BAR(B_BEMPTY + (i))); \
        if ((i) + 4 < 8) ld_tile(xx, g_h + tile_off + ((c + (i) + 4) & 7) * 2560); } while (0)
      W1_ISSUE(x0, 0);
      STAMP(9);
      uint32_t x1[20], x2[20], x3[20], ready = 0;
      probe_wait(ready, 1, g_h + probe_off, tag);
      ld_tile(x1, g_h + tile_off + ((c + 1) & 7) * 2560);
      probe_wait(ready, 2, g_h + probe_off, tag);
      ld_tile(x2, g_h + tile_off + ((c + 2) & 7) * 2560);
      probe_wait(ready, 3, g_h + probe_off, tag);
      ld_tile(x3, g_h + tile_off + ((c + 3) & 7) * 2560);
      STAMP(10);
      W1_ISSUE(x1, 1); W1_NEXT(x0, 0);
      W1_ISSUE(x2, 2); W1_NEXT(x1, 1);
      W1_ISSUE(x3, 3); W1_NEXT(x2, 2);
      W1_ISSUE(x0, 4); W1_NEXT(x3, 3);
      W1_ISSUE(x1, 5); W1_NEXT(x0, 4);
      W1_ISSUE(x2, 6); W1_NEXT(x1, 5);
      W1_ISSUE(x3, 7);
      uint2 hs[4];
      {
        const float2* hp = &g_hstat[(bw * 8 + tq * 2) * 16 + gq];
        uint32_t n = 0;
        do {
          hs[0] = ldcg64(hp); hs[1] = ldcg64(hp + 16); hs[2] = ldcg64(hp + 8); hs[3] = ldcg64(hp + 24);
        } while (__any_sync(0xffffffffu, (((hs[0].y ^ ep) | (hs[1].y ^ ep) | (hs[2].y ^ ep) | (hs[3].y ^ ep)) & 3u) != 0u) && ++n < SPIN_MAX);
      }
      W1_NEXT(x2, 6);
      float mean0, mean1, rs0, rs1;
      {
        const float a0 = __uint_as_float(hs[0].x), a1 = __uint_as_float(hs[1].x), b0 = __uint_as_float(hs[2].x), b1 = __uint_as_float(hs[3].x);
        float t0 = a0 + a1, t1 = b0 + b1;
        t0 += __shfl_xor_sync(0xffffffffu, t0, 1);
        t1 += __shfl_xor_sync(0xffffffffu, t1, 1);
        t0 += __shfl_xor_sync(0xffffffffu, t0, 2);
        t1 += __shfl_xor_sync(0xffffffffu, t1, 2);
        mean0 = t0 * 0.125f;
        mean1 = t1 * 0.125f;
        float u0 = __uint_as_float(hs[0].y) + __uint_as_float(hs[1].y) + 80.f * ((a0 - mean0) * (a0 - mean0) + (a1 - mean0) * (a1 - mean0));
        float u1 = __uint_as_float(hs[2].y) + __uint_as_float(hs[3].y) + 80.f * ((b0 - mean1) * (b0 - mean1) + (b1 - mean1) * (b1 - mean1));
        u0 += __shfl_xor_sync(0xffffffffu, u0, 1);
        u1 += __shfl_xor_sync(0xffffffffu, u1, 1);
        u0 += __shfl_xor_sync(0xffffffffu, u0, 2);
        u1 += __shfl_xor_sync(0xffffffffu, u1, 2);
        rs0 = 0.5f / sqrtf(u0 * (1.f / 640.f) + 1e-5f);
        rs1 = 0.5f / sqrtf(u1 * (1.f / 640.f) + 1e-5f);
      }
      mbar_wait(BAR(B_CS1), 0);
      WG_WAIT(0);
      reg_fence(acc);
      if (lane == 0) mbar_arrive_pair(BAR(B_BEMPTY + 7));
      STAMP(11);
      const float n0 = -mean0 * rs0, n1 = -mean1 * rs1;
#pragma unroll
      for (int t = 0; t < 28; t++) {
        const float2 cs = lds64f(sb + OFF_XS + t * 32 + tq * 8);
        const float h0 = fmaf(acc[4 * t], rs0, cs.x * n0), h1 = fmaf(acc[4 * t + 1], rs0, cs.y * n0);
        const float h2 = fmaf(acc[4 * t + 2], rs1, cs.x * n1), h3 = fmaf(acc[4 * t + 3], rs1, cs.y * n1);
        ha[2 * t] = pack2(fmaf(h0, tanh_fast(h0), h0), fmaf(h1, tanh_fast(h1), h1));
        ha[2 * t + 1] = pack2(fmaf(h2, tanh_fast(h2), h2), fmaf(h3, tanh_fast(h3), h3));
      }
      if ((c & 3) == 3) {
#pragma unroll
        for (int t = 48; t < 56; t++) ha[t] = 0u;
      }
    }
    STAMP(12);
    {
      float accA[64], accB[64];
      constexpr uint64_t HI = desc_hi(28672, 1024, 1);
      const uint32_t lane_off = w * 2048 + lane * 16;
#define W2_ISSUE(acc, s) do { \
        mbar_wait(BAR(B_W2FULL + (s)), 0); \
        const uint64_t db = mkdesc(sb + ((s) & 3) * W2SLOT, HI); \
        WG_FENCE(); \
        _Pragma("unroll") for (int k = 0; k < 14; k++) wg_rs128(acc, ha[4 * k], ha[4 * k + 1], ha[4 * k + 2], ha[4 * k + 3], db + k * 128, k); \
        WG_COMMIT(); } while (0)
#define W2_STORE(acc, s) do { \
        const int d0 = b * 8 + ((c + 2 * (s) - 1) & 7), d1 = b * 8 + ((c + 2 * (s)) & 7); \
        store_partial64(&acc[0], g_part + (size_t)(d0 * 8 + c) * 8192 + lane_off, tag); \
        store_partial64(&acc[32], g_part + (size_t)(d1 * 8 + c) * 8192 + lane_off, tag); } while (0)
      W2_ISSUE(accA, 0);
      W2_ISSUE(accB, 1);
      WG_WAIT(1);
      reg_fence(accA);
      if (lane == 0) mbar_arrive_pair(BAR(B_W2E));
      {
        uint8_t* dst = g_p89 + (size_t)(bw * 8 + c) * 4096 + lane * 16;
        store_partial64(&accA[0], dst, tag);
        store_partial64(&accA[32], dst + 2048, tag);
      }
      STAMP(13);
      W2_ISSUE(accA, 2);
      WG_WAIT(1);
      reg_fence(accB);
      W2_STORE(accB, 1);
      W2_ISSUE(accB, 3);
      WG_WAIT(1);
      reg_fence(accA);
      W2_STORE(accA, 2);
      float accR[32], accO[32];
      {
        mbar_wait(BAR(B_W2FULL + 4), 0);
        const uint64_t db = mkdesc(sb, HI);
        WG_FENCE();
#pragma unroll
        for (int k = 0; k < 14; k++) wg_rs64(accR, ha[4 * k], ha[4 * k + 1], ha[4 * k + 2], ha[4 * k + 3], db + k * 128, k);
        WG_COMMIT();
#pragma unroll
        for (int k = 0; k < 14; k++) wg_rs64(accO, ha[4 * k], ha[4 * k + 1], ha[4 * k + 2], ha[4 * k + 3], db + 1792 + k * 128, k);
        WG_COMMIT();
      }
      WG_WAIT(2);
      reg_fence(accB);
      W2_STORE(accB, 3);
      WG_WAIT(1);
      reg_fence(accR);
      store_partial64(&accR[0], g_part + (size_t)((b * 8 + ((c + 7) & 7)) * 8 + c) * 8192 + lane_off, tag);
      STAMP(14);
      const uint8_t* pp = g_part + (size_t)((b * 8 + c) * 8) * 8192 + lane_off;
      uint4 v[7][4], hr[4];
#pragma unroll
      for (int u = 0; u < 4; u++) ld4(v[u], pp + ((c - 1 - u) & 7) * 8192);
      ld4(hr, g_h + tile_off + c * 2048);
      {
        const int bw2 = rb * 8 + c;
        uint4 v8[8], hv;
        uint32_t n = 0, bad;
        const uint8_t* p8 = g_p89 + (size_t)bw2 * 32768 + warp * 512 + lane * 16;
        const uint8_t* ph = g_h + (size_t)bw2 * 20480 + (32 + warp) * 512 + lane * 16;
        asm volatile("" : "+l"(p8), "+l"(ph));
        do {
#pragma unroll
          for (int u = 0; u < 8; u++) v8[u] = ldcg128(p8 + u * 4096);
          hv = ldcg128(ph);
          bad = hv.x ^ tag;
#pragma unroll
          for (int u = 0; u < 8; u++) bad |= v8[u].x ^ tag;
        } while (__any_sync(0xffffffffu, (bad & TAGM) != 0u) && ++n < SPIN_MAX);
        float f[8] = {bf_lo(hv.x), bf_hi(hv.x), bf_lo(hv.y), bf_hi(hv.y), bf_lo(hv.z), bf_hi(hv.z), bf_lo(hv.w), bf_hi(hv.w)};
#pragma unroll
        for (int u = 0; u < 8; u++) {
          f[0] += bf_lo(v8[u].x); f[1] += bf_hi(v8[u].x); f[2] += bf_lo(v8[u].y); f[3] += bf_hi(v8[u].y);
          f[4] += bf_lo(v8[u].z); f[5] += bf_hi(v8[u].z); f[6] += bf_lo(v8[u].w); f[7] += bf_hi(v8[u].w);
        }
        uint8_t* op = reinterpret_cast<uint8_t*>(P.out) + (size_t)(bw2 * 16 + gq) * 1280 + 1024 + warp * 32 + tq * 4;
        *reinterpret_cast<uint32_t*>(op) = pack2(f[0], f[1]);
        *reinterpret_cast<uint32_t*>(op + 8 * 1280) = pack2(f[2], f[3]);
        *reinterpret_cast<uint32_t*>(op + 16) = pack2(f[4], f[5]);
        *reinterpret_cast<uint32_t*>(op + 8 * 1280 + 16) = pack2(f[6], f[7]);
      }
      WG_WAIT(0);
      reg_fence(accO);
      STAMP(15);
#pragma unroll
      for (int u = 4; u < 7; u++) ld4(v[u], pp + ((c - 1 - u) & 7) * 8192);
      fix4_add(accO, hr, g_h + tile_off + c * 2048, tag);
#pragma unroll
      for (int u = 0; u < 7; u++) {
        fix4_add(accO, v[u], pp + ((c - 1 - u) & 7) * 8192, tag);
        if (u == 5) STAMP(16);
      }
      uint8_t* op = reinterpret_cast<uint8_t*>(P.out) + (size_t)row_lo * 1280 + c * 128 + tq * 4;
#pragma unroll
      for (int t = 0; t < 8; t++) {
        *reinterpret_cast<uint32_t*>(op + t * 16) = pack2(accO[4 * t], accO[4 * t + 1]);
        *reinterpret_cast<uint32_t*>(op + 8 * 1280 + t * 16) = pack2(accO[4 * t + 2], accO[4 * t + 3]);
      }
      STAMP(17);
    }
  }
}

typedef CUresult (*EncodeFn)(CUtensorMap*, CUtensorMapDataType, cuuint32_t, void*, const cuuint64_t*, const cuuint64_t*, const cuuint32_t*,
                             const cuuint32_t*, CUtensorMapInterleave, CUtensorMapSwizzle, CUtensorMapL2promotion, CUtensorMapFloatOOBfill);

static void make_map(EncodeFn enc, CUtensorMap* m, const void* p, int nd, const cuuint64_t* dims, const cuuint64_t* strides, const cuuint32_t* box,
                     CUtensorMapSwizzle sw) {
  const cuuint32_t es[5] = {1, 1, 1, 1, 1};
  enc(m, CU_TENSOR_MAP_DATA_TYPE_BFLOAT16, (cuuint32_t)nd, const_cast<void*>(p), dims, strides, box, es, CU_TENSOR_MAP_INTERLEAVE_NONE, sw,
      CU_TENSOR_MAP_L2_PROMOTION_L2_128B, CU_TENSOR_MAP_FLOAT_OOB_FILL_NONE);
}

extern "C" void kernel_launch(void* const* d_in, const int* in_sizes, int n_in, void* d_out, int out_size) {
  (void)in_sizes; (void)n_in; (void)out_size;
  static EncodeFn enc = nullptr;
  if (!enc) {
    void* f = nullptr;
    cudaDriverEntryPointQueryResult qr;
    cudaGetDriverEntryPoint("cuTensorMapEncodeTiled", &f, cudaEnableDefault, &qr);
    enc = (EncodeFn)f;
    cudaFuncSetAttribute(fused_block_kernel, cudaFuncAttributeMaxDynamicSharedMemorySize, (int)SMEM_BYTES);
  }
  Params P;
  P.x = (const __nv_bfloat16*)d_in[0];
  P.wqkv = (const __nv_bfloat16*)d_in[1];
  P.wo = (const __nv_bfloat16*)d_in[2];
  P.w1 = (const __nv_bfloat16*)d_in[4];
  P.w2 = (const __nv_bfloat16*)d_in[5];
  P.out = (__nv_bfloat16*)d_out;
  { const cuuint64_t d[2] = {640, 2048}, s[1] = {1280}; const cuuint32_t b[2] = {64, 128}; make_map(enc, &P.mX, P.x, 2, d, s, b, CU_TENSOR_MAP_SWIZZLE_128B); }
  { const cuuint64_t d[4] = {32, 640, 20, 3}, s[3] = {3840, 64, 1280}; const cuuint32_t b[4] = {32, 32, 2, 3}; make_map(enc, &P.mWqM, P.wqkv, 4, d, s, b, CU_TENSOR_MAP_SWIZZLE_64B); }
  { const cuuint64_t d[4] = {16, 640, 40, 3}, s[3] = {3840, 32, 1280}; const cuuint32_t b[4] = {16, 32, 1, 3}; make_map(enc, &P.mWqL, P.wqkv, 4, d, s, b, CU_TENSOR_MAP_SWIZZLE_32B); }
  { const cuuint64_t d[3] = {16, 640, 40}, s[2] = {1280, 32}; const cuuint32_t b[3] = {16, 80, 5}; make_map(enc, &P.mWo, P.wo, 3, d, s, b, CU_TENSOR_MAP_SWIZZLE_32B); }
  { const cuuint64_t d[3] = {32, 640, 54}, s[2] = {3456, 64}; const cuuint32_t b[3] = {32, 80, 4}; make_map(enc, &P.mW1a, P.w1, 3, d, s, b, CU_TENSOR_MAP_SWIZZLE_64B); }
  { const cuuint64_t d[3] = {32, 640, 54}, s[2] = {3456, 64}; const cuuint32_t b[3] = {32, 80, 3}; make_map(enc, &P.mW1b, P.w1, 3, d, s, b, CU_TENSOR_MAP_SWIZZLE_64B); }
  { const cuuint64_t d[2] = {640, 1728}, s[1] = {1280}; const cuuint32_t b[2] = {64, 112}; make_map(enc, &P.mW2, P.w2, 2, d, s, b, CU_TENSOR_MAP_SWIZZLE_128B); }
  fused_block_kernel<<<132, 384, SMEM_BYTES, cudaStreamPerThread>>>(P);
}
```

```cpp
#include <cuda_runtime.h>
#include <cuda.h>
#include <cuda_bf16.h>
#include <stdint.h>

#define PROF 0
#define STATKT 3
#define SMIDMAP 0

__device__ __align__(1024) uint8_t g_kv[32 * 8 * 22528];
__device__ __align__(1024) uint8_t g_o[32 * 4 * 8 * 2560];
__device__ __align__(1024) uint8_t g_h[32 * 4 * 8 * 2560];
__device__ __align__(1024) float2 g_hstat[32 * 4 * 8 * 16];
__device__ __align__(1024) uint8_t g_part[32 * 8 * 8 * 8192];
__device__ __align__(1024) uint8_t g_p89[32 * 4 * 8 * 4096];
__device__ __align__(128) float2 g_xstat[2048];
__device__ __align__(128) float g_csq[16 * 8 * 240];
__device__ __align__(128) float g_cs1[16 * 8 * 224];
__device__ __align__(128) uint32_t g_epoch[128];
#define STAMP(slot)
#define STAMPW(slot)

struct Params {
  CUtensorMap mX, mWqM, mWqL, mWo, mW1a, mW1b, mW2;
  const __nv_bfloat16 *x, *wqkv, *wo, *w1, *w2;
  __nv_bfloat16* out;
};

constexpr uint32_t QST = 47104;
constexpr uint32_t KVB = 22528;
constexpr uint32_t OFF_WOB = 0;
constexpr uint32_t OFF_PRE = 188416;
constexpr uint32_t W2SLOT = 57344;
constexpr uint32_t OFF_MISC = 229376;
constexpr uint32_t OFF_CS = OFF_MISC + 512;
constexpr uint32_t OFF_XS = OFF_CS + 960;
constexpr uint32_t SMEM_BYTES = 232448;

enum {
  B_QFULL = 0, B_KVFULL = 4, B_KVLAND = 8, B_WOB = 12, B_WOB7 = 13, B_BFULL = 14, B_W2FULL = 22, B_PL = 27, B_CS1 = 39,
  B_KVOWN = 40,
  B_Q23 = 42, B_PRE = 43, B_STAT = 44, B_W2D = 45,
  B_QEMPTY = 47, B_ATTP = 51, B_WODP = 52, B_BEMPTY = 53, B_W2E = 61,
  NBAR = 62
};
constexpr uint32_t TAGM = 0x00010001u;
constexpr uint32_t SPIN_MAX = 1u << 18;

__device__ __forceinline__ uint32_t s2u(const void* p) { return (uint32_t)__cvta_generic_to_shared(p); }
__device__ __forceinline__ void mbar_init(uint32_t b, int c) { asm volatile("mbarrier.init.shared::cta.b64 [%0], %1;" ::"r"(b), "r"(c)); }
__device__ __forceinline__ void mbar_expect(uint32_t b, int bytes) { asm volatile("mbarrier.arrive.expect_tx.shared::cta.b64 _, [%0], %1;" ::"r"(b), "r"(bytes) : "memory"); }
__device__ __forceinline__ void mbar_arrive(uint32_t b) { asm volatile("mbarrier.arrive.shared::cta.b64 _, [%0];" ::"r"(b) : "memory"); }
__device__ __forceinline__ void mbar_arrive_pair(uint32_t b) {
  asm volatile("{\n.reg .b32 r;\nmapa.shared::cluster.u32 r, %0, 0;\nmbarrier.arrive.shared::cluster.b64 _, [r];\n"
               "mapa.shared::cluster.u32 r, %0, 1;\nmbarrier.arrive.shared::cluster.b64 _, [r];\n}" ::"r"(b) : "memory");
}
__device__ __forceinline__ void mbar_wait(uint32_t b, uint32_t ph) {
  asm volatile("{\n.reg .pred p;\n.reg .u32 n;\nmov.u32 n, 0;\nW%=:\nmbarrier.try_wait.parity.shared::cta.b64 p, [%0], %1;\n"
               "add.u32 n, n, 1;\nsetp.lt.and.u32 p, n, 0x100000, !p;\n@p bra W%=;\n}" ::"r"(b), "r"(ph) : "memory");
}
__device__ __forceinline__ void tma2d(uint32_t dst, const CUtensorMap* m, int c0, int c1, uint32_t bar) {
  asm volatile("cp.async.bulk.tensor.2d.shared::cluster.global.mbarrier::complete_tx::bytes [%0], [%1, {%3, %4}], [%2];" ::"r"(dst), "l"(m), "r"(bar), "r"(c0), "r"(c1) : "memory");
}
__device__ __forceinline__ void tma2d_mc(uint32_t dst, const CUtensorMap* m, int c0, int c1, uint32_t bar) {
  asm volatile("cp.async.bulk.tensor.2d.shared::cluster.global.mbarrier::complete_tx::bytes.multicast::cluster [%0], [%1, {%3, %4}], [%2], %5;" ::"r"(dst), "l"(m), "r"(bar), "r"(c0), "r"(c1), "h"((uint16_t)3) : "memory");
}
__device__ __forceinline__ void tma3d_mc(uint32_t dst, const CUtensorMap* m, int c0, int c1, int c2, uint32_t bar) {
  asm volatile("cp.async.bulk.tensor.3d.shared::cluster.global.mbarrier::complete_tx::bytes.multicast::cluster [%0], [%1, {%3, %4, %5}], [%2], %6;" ::"r"(dst), "l"(m), "r"(bar), "r"(c0), "r"(c1), "r"(c2), "h"((uint16_t)3) : "memory");
}
__device__ __forceinline__ void tma4d_mc(uint32_t dst, const CUtensorMap* m, int c0, int c1, int c2, int c3, uint32_t bar) {
  asm volatile("cp.async.bulk.tensor.4d.shared::cluster.global.mbarrier::complete_tx::bytes.multicast::cluster [%0], [%1, {%3, %4, %5, %6}], [%2], %7;" ::"r"(dst), "l"(m), "r"(bar), "r"(c0), "r"(c1), "r"(c2), "r"(c3), "h"((uint16_t)3) : "memory");
}
__device__ __forceinline__ void bulk_load(uint32_t dst, const void* src, int bytes, uint32_t bar) {
  asm volatile("cp.async.bulk.shared::cluster.global.mbarrier::complete_tx::bytes [%0], [%1], %2, [%3];" ::"r"(dst), "l"(src), "r"(bytes), "r"(bar) : "memory");
}
__device__ __forceinline__ void tma4d_pf(const CUtensorMap* m, int c0, int c1, int c2, int c3) {
  asm volatile("cp.async.bulk.prefetch.tensor.4d.L2.global [%0, {%1, %2, %3, %4}];" ::"l"(m), "r"(c0), "r"(c1), "r"(c2), "r"(c3) : "memory");
}
__device__ __forceinline__ void l2_prefetch_bulk(const void* p, int bytes) { asm volatile("cp.async.bulk.prefetch.L2.global [%0], %1;" ::"l"(p), "r"(bytes) : "memory"); }
__device__ __forceinline__ void l2_prefetch(const void* p) { asm volatile("prefetch.global.L2 [%0];" ::"l"(p)); }
__device__ __forceinline__ uint32_t ld_flag(const uint32_t* p) { uint32_t v; asm volatile("ld.acquire.gpu.global.u32 %0, [%1];" : "=r"(v) : "l"(p) : "memory"); return v; }
__device__ __forceinline__ void st_flag(uint32_t* p, uint32_t v) { asm volatile("st.relaxed.gpu.global.u32 [%0], %1;" ::"l"(p), "r"(v) : "memory"); }
__device__ __forceinline__ void fence_gpu() { asm volatile("fence.acq_rel.gpu;" ::: "memory"); }
__device__ __forceinline__ void fence_async_smem() { asm volatile("fence.proxy.async.shared::cta;" ::: "memory"); }
__device__ __forceinline__ void fence_async_glob() { asm volatile("fence.proxy.async.global;" ::: "memory"); }
__device__ __forceinline__ uint4 ldcg128(const void* p) { uint4 v; asm volatile("ld.relaxed.gpu.global.v4.u32 {%0,%1,%2,%3}, [%4];" : "=r"(v.x), "=r"(v.y), "=r"(v.z), "=r"(v.w) : "l"(p) : "memory"); return v; }
__device__ __forceinline__ uint4 ldnc128(const void* p) { uint4 v; asm volatile("ld.global.nc.v4.u32 {%0,%1,%2,%3}, [%4];" : "=r"(v.x), "=r"(v.y), "=r"(v.z), "=r"(v.w) : "l"(p)); return v; }
__device__ __forceinline__ uint32_t ldnc32(const void* p) { uint32_t v; asm volatile("ld.global.nc.u32 %0, [%1];" : "=r"(v) : "l"(p)); return v; }
__device__ __forceinline__ uint2 ldcg64(const void* p) { uint2 v; asm volatile("ld.relaxed.gpu.global.v2.u32 {%0,%1}, [%2];" : "=r"(v.x), "=r"(v.y) : "l"(p) : "memory"); return v; }
__device__ __forceinline__ uint32_t ldcg32(const void* p) { uint32_t v; asm volatile("ld.relaxed.gpu.global.u32 %0, [%1];" : "=r"(v) : "l"(p) : "memory"); return v; }
__device__ __forceinline__ uint32_t pack2(float lo, float hi) { uint32_t r; asm("cvt.rn.bf16x2.f32 %0, %1, %2;" : "=r"(r) : "f"(hi), "f"(lo)); return r; }
__device__ __forceinline__ float bf_lo(uint32_t v) { return __uint_as_float(v << 16); }
__device__ __forceinline__ float bf_hi(uint32_t v) { return __uint_as_float(v & 0xffff0000u); }
__device__ __forceinline__ float ex2(float x) { float y; asm("ex2.approx.ftz.f32 %0, %1;" : "=f"(y) : "f"(x)); return y; }
__device__ __forceinline__ float rcp(float x) { float y; asm("rcp.approx.ftz.f32 %0, %1;" : "=f"(y) : "f"(x)); return y; }
__device__ __forceinline__ float tanh_fast(float x) { float y; asm("tanh.approx.f32 %0, %1;" : "=f"(y) : "f"(x)); return y; }
__device__ __forceinline__ void stsm4(uint32_t a, uint32_t r0, uint32_t r1, uint32_t r2, uint32_t r3) {
  asm volatile("stmatrix.sync.aligned.m8n8.x4.shared.b16 [%0], {%1,%2,%3,%4};" ::"r"(a), "r"(r0), "r"(r1), "r"(r2), "r"(r3) : "memory");
}
__device__ __forceinline__ float2 lds64f(uint32_t a) { float2 v; asm volatile("ld.shared.v2.f32 {%0,%1}, [%2];" : "=f"(v.x), "=f"(v.y) : "r"(a)); return v; }
__device__ __forceinline__ constexpr uint64_t desc_hi(uint32_t lbo, uint32_t sbo, uint32_t sw) {
  return ((uint64_t)(lbo >> 4) << 16) | ((uint64_t)(sbo >> 4) << 32) | ((uint64_t)sw << 62);
}
__device__ __forceinline__ uint64_t mkdesc(uint32_t addr, uint64_t hi) { return hi | (uint64_t)((addr & 0x3FFFF) >> 4); }
#define WG_FENCE() asm volatile("wgmma.fence.sync.aligned;" ::: "memory")
#define WG_COMMIT() asm volatile("wgmma.commit_group.sync.aligned;" ::: "memory")
#define WG_WAIT(n) asm volatile("wgmma.wait_group.sync.aligned " #n ";" ::: "memory")
template <int N> __device__ __forceinline__ void reg_fence(float (&a)[N]) {
#pragma unroll
  for (int i = 0; i < N; i++) asm volatile("" : "+f"(a[i])::"memory");
}

__device__ __forceinline__ void wg_ss192(float (&d)[96], uint64_t da, uint64_t db, int sd) {
  asm volatile("{\n.reg .pred p;\nsetp.ne.b32 p, %98, 0;\n"
  "wgmma.mma_async.sync.aligned.m64n192k16.f32.bf16.bf16 {%0, %1, %2, %3, %4, %5, %6, %7, %8, %9, %10, %11, %12, %13, %14, %15, %16, %17, %18, %19, %20, %21, %22, %23, %24, %25, %26, %27, %28, %29, %30, %31, %32, %33, %34, %35, %36, %37, %38, %39, %40, %41, %42, %43, %44, %45, %46, %47, %48, %49, %50, %51, %52, %53, %54, %55, %56, %57, %58, %59, %60, %61, %62, %63, %64, %65, %66, %67, %68, %69, %70, %71, %72, %73, %74, %75, %76, %77, %78, %79, %80, %81, %82, %83, %84, %85, %86, %87, %88, %89, %90, %91, %92, %93, %94, %95}, %96, %97, p, 1, 1, 0, 1;\n}\n"
  : "+f"(d[0]), "+f"(d[1]), "+f"(d[2]), "+f"(d[3]), "+f"(d[4]), "+f"(d[5]), "+f"(d[6]), "+f"(d[7]), "+f"(d[8]), "+f"(d[9]), "+f"(d[10]), "+f"(d[11]), "+f"(d[12]), "+f"(d[13]), "+f"(d[14]), "+f"(d[15]), "+f"(d[16]), "+f"(d[17]), "+f"(d[18]), "+f"(d[19]), "+f"(d[20]), "+f"(d[21]), "+f"(d[22]), "+f"(d[23]), "+f"(d[24]), "+f"(d[25]), "+f"(d[26]), "+f"(d[27]), "+f"(d[28]), "+f"(d[29]), "+f"(d[30]), "+f"(d[31]), "+f"(d[32]), "+f"(d[33]), "+f"(d[34]), "+f"(d[35]), "+f"(d[36]), "+f"(d[37]), "+f"(d[38]), "+f"(d[39]), "+f"(d[40]), "+f"(d[41]), "+f"(d[42]), "+f"(d[43]), "+f"(d[44]), "+f"(d[45]), "+f"(d[46]), "+f"(d[47]), "+f"(d[48]), "+f"(d[49]), "+f"(d[50]), "+f"(d[51]), "+f"(d[52]), "+f"(d[53]), "+f"(d[54]), "+f"(d[55]), "+f"(d[56]), "+f"(d[57]), "+f"(d[58]), "+f"(d[59]), "+f"(d[60]), "+f"(d[61]), "+f"(d[62]), "+f"(d[63]), "+f"(d[64]), "+f"(d[65]), "+f"(d[66]), "+f"(d[67]), "+f"(d[68]), "+f"(d[69]), "+f"(d[70]), "+f"(d[71]), "+f"(d[72]), "+f"(d[73]), "+f"(d[74]), "+f"(d[75]), "+f"(d[76]), "+f"(d[77]), "+f"(d[78]), "+f"(d[79]), "+f"(d[80]), "+f"(d[81]), "+f"(d[82]), "+f"(d[83]), "+f"(d[84]), "+f"(d[85]), "+f"(d[86]), "+f"(d[87]), "+f"(d[88]), "+f"(d[89]), "+f"(d[90]), "+f"(d[91]), "+f"(d[92]), "+f"(d[93]), "+f"(d[94]), "+f"(d[95]) : "l"(da), "l"(db), "r"(sd));
}
__device__ __forceinline__ void wg_ss48(float (&d)[24], uint64_t da, uint64_t db, int sd) {
  asm volatile("{\n.reg .pred p;\nsetp.ne.b32 p, %26, 0;\n"
  "wgmma.mma_async.sync.aligned.m64n48k16.f32.bf16.bf16 {%0, %1, %2, %3, %4, %5, %6, %7, %8, %9, %10, %11, %12, %13, %14, %15, %16, %17, %18, %19, %20, %21, %22, %23}, %24, %25, p, 1, 1, 0, 1;\n}\n"
  : "+f"(d[0]), "+f"(d[1]), "+f"(d[2]), "+f"(d[3]), "+f"(d[4]), "+f"(d[5]), "+f"(d[6]), "+f"(d[7]), "+f"(d[8]), "+f"(d[9]), "+f"(d[10]), "+f"(d[11]), "+f"(d[12]), "+f"(d[13]), "+f"(d[14]), "+f"(d[15]), "+f"(d[16]), "+f"(d[17]), "+f"(d[18]), "+f"(d[19]), "+f"(d[20]), "+f"(d[21]), "+f"(d[22]), "+f"(d[23]) : "l"(da), "l"(db), "r"(sd));
}
__device__ __forceinline__ void wg_rs80(float (&d)[40], uint32_t a0, uint32_t a1, uint32_t a2, uint32_t a3, uint64_t db, int sd) {
  asm volatile("{\n.reg .pred p;\nsetp.ne.b32 p, %45, 0;\n"
  "wgmma.mma_async.sync.aligned.m64n80k16.f32.bf16.bf16 {%0, %1, %2, %3, %4, %5, %6, %7, %8, %9, %10, %11, %12, %13, %14, %15, %16, %17, %18, %19, %20, %21, %22, %23, %24, %25, %26, %27, %28, %29, %30, %31, %32, %33, %34, %35, %36, %37, %38, %39}, {%40, %41, %42, %43}, %44, p, 1, 1, 1;\n}\n"
  : "+f"(d[0]), "+f"(d[1]), "+f"(d[2]), "+f"(d[3]), "+f"(d[4]), "+f"(d[5]), "+f"(d[6]), "+f"(d[7]), "+f"(d[8]), "+f"(d[9]), "+f"(d[10]), "+f"(d[11]), "+f"(d[12]), "+f"(d[13]), "+f"(d[14]), "+f"(d[15]), "+f"(d[16]), "+f"(d[17]), "+f"(d[18]), "+f"(d[19]), "+f"(d[20]), "+f"(d[21]), "+f"(d[22]), "+f"(d[23]), "+f"(d[24]), "+f"(d[25]), "+f"(d[26]), "+f"(d[27]), "+f"(d[28]), "+f"(d[29]), "+f"(d[30]), "+f"(d[31]), "+f"(d[32]), "+f"(d[33]), "+f"(d[34]), "+f"(d[35]), "+f"(d[36]), "+f"(d[37]), "+f"(d[38]), "+f"(d[39]) : "r"(a0), "r"(a1), "r"(a2), "r"(a3), "l"(db), "r"(sd));
}
__device__ __forceinline__ void wg_rs224(float (&d)[112], uint32_t a0, uint32_t a1, uint32_t a2, uint32_t a3, uint64_t db, int sd) {
  asm volatile("{\n.reg .pred p;\nsetp.ne.b32 p, %117, 0;\n"
  "wgmma.mma_async.sync.aligned.m64n224k16.f32.bf16.bf16 {%0, %1, %2, %3, %4, %5, %6, %7, %8, %9, %10, %11, %12, %13, %14, %15, %16, %17, %18, %19, %20, %21, %22, %23, %24, %25, %26, %27, %28, %29, %30, %31, %32, %33, %34, %35, %36, %37, %38, %39, %40, %41, %42, %43, %44, %45, %46, %47, %48, %49, %50, %51, %52, %53, %54, %55, %56, %57, %58, %59, %60, %61, %62, %63, %64, %65, %66, %67, %68, %69, %70, %71, %72, %73, %74, %75, %76, %77, %78, %79, %80, %81, %82, %83, %84, %85, %86, %87, %88, %89, %90, %91, %92, %93, %94, %95, %96, %97, %98, %99, %100, %101, %102, %103, %104, %105, %106, %107, %108, %109, %110, %111}, {%112, %113, %114, %115}, %116, p, 1, 1, 1;\n}\n"
  : "+f"(d[0]), "+f"(d[1]), "+f"(d[2]), "+f"(d[3]), "+f"(d[4]), "+f"(d[5]), "+f"(d[6]), "+f"(d[7]), "+f"(d[8]), "+f"(d[9]), "+f"(d[10]), "+f"(d[11]), "+f"(d[12]), "+f"(d[13]), "+f"(d[14]), "+f"(d[15]), "+f"(d[16]), "+f"(d[17]), "+f"(d[18]), "+f"(d[19]), "+f"(d[20]), "+f"(d[21]), "+f"(d[22]), "+f"(d[23]), "+f"(d[24]), "+f"(d[25]), "+f"(d[26]), "+f"(d[27]), "+f"(d[28]), "+f"(d[29]), "+f"(d[30]), "+f"(d[31]), "+f"(d[32]), "+f"(d[33]), "+f"(d[34]), "+f"(d[35]), "+f"(d[36]), "+f"(d[37]), "+f"(d[38]), "+f"(d[39]), "+f"(d[40]), "+f"(d[41]), "+f"(d[42]), "+f"(d[43]), "+f"(d[44]), "+f"(d[45]), "+f"(d[46]), "+f"(d[47]), "+f"(d[48]), "+f"(d[49]), "+f"(d[50]), "+f"(d[51]), "+f"(d[52]), "+f"(d[53]), "+f"(d[54]), "+f"(d[55]), "+f"(d[56]), "+f"(d[57]), "+f"(d[58]), "+f"(d[59]), "+f"(d[60]), "+f"(d[61]), "+f"(d[62]), "+f"(d[63]), "+f"(d[64]), "+f"(d[65]), "+f"(d[66]), "+f"(d[67]), "+f"(d[68]), "+f"(d[69]), "+f"(d[70]), "+f"(d[71]), "+f"(d[72]), "+f"(d[73]), "+f"(d[74]), "+f"(d[75]), "+f"(d[76]), "+f"(d[77]), "+f"(d[78]), "+f"(d[79]), "+f"(d[80]), "+f"(d[81]), "+f"(d[82]), "+f"(d[83]), "+f"(d[84]), "+f"(d[85]), "+f"(d[86]), "+f"(d[87]), "+f"(d[88]), "+f"(d[89]), "+f"(d[90]), "+f"(d[91]), "+f"(d[92]), "+f"(d[93]), "+f"(d[94]), "+f"(d[95]), "+f"(d[96]), "+f"(d[97]), "+f"(d[98]), "+f"(d[99]), "+f"(d[100]), "+f"(d[101]), "+f"(d[102]), "+f"(d[103]), "+f"(d[104]), "+f"(d[105]), "+f"(d[106]), "+f"(d[107]), "+f"(d[108]), "+f"(d[109]), "+f"(d[110]), "+f"(d[111]) : "r"(a0), "r"(a1), "r"(a2), "r"(a3), "l"(db), "r"(sd));
}
__device__ __forceinline__ void wg_rs64k(float (&d)[32], uint32_t a0, uint32_t a1, uint32_t a2, uint32_t a3, uint64_t db, int sd) {
  asm volatile("{\n.reg .pred p;\nsetp.ne.b32 p, %37, 0;\n"
  "wgmma.mma_async.sync.aligned.m64n64k16.f32.bf16.bf16 {%0, %1, %2, %3, %4, %5, %6, %7, %8, %9, %10, %11, %12, %13, %14, %15, %16, %17, %18, %19, %20, %21, %22, %23, %24, %25, %26, %27, %28, %29, %30, %31}, {%32, %33, %34, %35}, %36, p, 1, 1, 0;\n}\n"
  : "+f"(d[0]), "+f"(d[1]), "+f"(d[2]), "+f"(d[3]), "+f"(d[4]), "+f"(d[5]), "+f"(d[6]), "+f"(d[7]), "+f"(d[8]), "+f"(d[9]), "+f"(d[10]), "+f"(d[11]), "+f"(d[12]), "+f"(d[13]), "+f"(d[14]), "+f"(d[15]), "+f"(d[16]), "+f"(d[17]), "+f"(d[18]), "+f"(d[19]), "+f"(d[20]), "+f"(d[21]), "+f"(d[22]), "+f"(d[23]), "+f"(d[24]), "+f"(d[25]), "+f"(d[26]), "+f"(d[27]), "+f"(d[28]), "+f"(d[29]), "+f"(d[30]), "+f"(d[31]) : "r"(a0), "r"(a1), "r"(a2), "r"(a3), "l"(db), "r"(sd));
}
__device__ __forceinline__ void wg_rs24(float (&d)[12], uint32_t a0, uint32_t a1, uint32_t a2, uint32_t a3, uint64_t db, int sd) {
  asm volatile("{\n.reg .pred p;\nsetp.ne.b32 p, %17, 0;\n"
  "wgmma.mma_async.sync.aligned.m64n24k16.f32.bf16.bf16 {%0, %1, %2, %3, %4, %5, %6, %7, %8, %9, %10, %11}, {%12, %13, %14, %15}, %16, p, 1, 1, 1;\n}\n"
  : "+f"(d[0]), "+f"(d[1]), "+f"(d[2]), "+f"(d[3]), "+f"(d[4]), "+f"(d[5]), "+f"(d[6]), "+f"(d[7]), "+f"(d[8]), "+f"(d[9]), "+f"(d[10]), "+f"(d[11]) : "r"(a0), "r"(a1), "r"(a2), "r"(a3), "l"(db), "r"(sd));
}
__device__ __forceinline__ void wg_rs128(float (&d)[64], uint32_t a0, uint32_t a1, uint32_t a2, uint32_t a3, uint64_t db, int sd) {
  asm volatile("{\n.reg .pred p;\nsetp.ne.b32 p, %69, 0;\n"
  "wgmma.mma_async.sync.aligned.m64n128k16.f32.bf16.bf16 {%0, %1, %2, %3, %4, %5, %6, %7, %8, %9, %10, %11, %12, %13, %14, %15, %16, %17, %18, %19, %20, %21, %22, %23, %24, %25, %26, %27, %28, %29, %30, %31, %32, %33, %34, %35, %36, %37, %38, %39, %40, %41, %42, %43, %44, %45, %46, %47, %48, %49, %50, %51, %52, %53, %54, %55, %56, %57, %58, %59, %60, %61, %62, %63}, {%64, %65, %66, %67}, %68, p, 1, 1, 1;\n}\n"
  : "+f"(d[0]), "+f"(d[1]), "+f"(d[2]), "+f"(d[3]), "+f"(d[4]), "+f"(d[5]), "+f"(d[6]), "+f"(d[7]), "+f"(d[8]), "+f"(d[9]), "+f"(d[10]), "+f"(d[11]), "+f"(d[12]), "+f"(d[13]), "+f"(d[14]), "+f"(d[15]), "+f"(d[16]), "+f"(d[17]), "+f"(d[18]), "+f"(d[19]), "+f"(d[20]), "+f"(d[21]), "+f"(d[22]), "+f"(d[23]), "+f"(d[24]), "+f"(d[25]), "+f"(d[26]), "+f"(d[27]), "+f"(d[28]), "+f"(d[29]), "+f"(d[30]), "+f"(d[31]), "+f"(d[32]), "+f"(d[33]), "+f"(d[34]), "+f"(d[35]), "+f"(d[36]), "+f"(d[37]), "+f"(d[38]), "+f"(d[39]), "+f"(d[40]), "+f"(d[41]), "+f"(d[42]), "+f"(d[43]), "+f"(d[44]), "+f"(d[45]), "+f"(d[46]), "+f"(d[47]), "+f"(d[48]), "+f"(d[49]), "+f"(d[50]), "+f"(d[51]), "+f"(d[52]), "+f"(d[53]), "+f"(d[54]), "+f"(d[55]), "+f"(d[56]), "+f"(d[57]), "+f"(d[58]), "+f"(d[59]), "+f"(d[60]), "+f"(d[61]), "+f"(d[62]), "+f"(d[63]) : "r"(a0), "r"(a1), "r"(a2), "r"(a3), "l"(db), "r"(sd));
}
__device__ __forceinline__ void wg_rs64(float (&d)[32], uint32_t a0, uint32_t a1, uint32_t a2, uint32_t a3, uint64_t db, int sd) {
  asm volatile("{\n.reg .pred p;\nsetp.ne.b32 p, %37, 0;\n"
  "wgmma.mma_async.sync.aligned.m64n64k16.f32.bf16.bf16 {%0, %1, %2, %3, %4, %5, %6, %7, %8, %9, %10, %11, %12, %13, %14, %15, %16, %17, %18, %19, %20, %21, %22, %23, %24, %25, %26, %27, %28, %29, %30, %31}, {%32, %33, %34, %35}, %36, p, 1, 1, 1;\n}\n"
  : "+f"(d[0]), "+f"(d[1]), "+f"(d[2]), "+f"(d[3]), "+f"(d[4]), "+f"(d[5]), "+f"(d[6]), "+f"(d[7]), "+f"(d[8]), "+f"(d[9]), "+f"(d[10]), "+f"(d[11]), "+f"(d[12]), "+f"(d[13]), "+f"(d[14]), "+f"(d[15]), "+f"(d[16]), "+f"(d[17]), "+f"(d[18]), "+f"(d[19]), "+f"(d[20]), "+f"(d[21]), "+f"(d[22]), "+f"(d[23]), "+f"(d[24]), "+f"(d[25]), "+f"(d[26]), "+f"(d[27]), "+f"(d[28]), "+f"(d[29]), "+f"(d[30]), "+f"(d[31]) : "r"(a0), "r"(a1), "r"(a2), "r"(a3), "l"(db), "r"(sd));
}

__device__ __forceinline__ uint32_t kv_addr(int i) {
  return 94208u + KVB * (uint32_t)((0x541032u >> (4 * i)) & 15u);
}
__device__ __forceinline__ uint32_t w1b_addr(int s) {
  return (s == 3 || s == 4) ? (uint32_t)(s - 3) * 35840u : 102400u + (uint32_t)(s >= 5 ? s - 5 : s) * 35840u;
}
__device__ __forceinline__ void stg128(void* p, uint32_t a, uint32_t b, uint32_t c, uint32_t d) {
  asm volatile("st.global.v4.u32 [%0], {%1,%2,%3,%4};" ::"l"(p), "r"(a), "r"(b), "r"(c), "r"(d) : "memory");
}
__device__ __forceinline__ void stg32(void* p, uint32_t a) { asm volatile("st.global.u32 [%0], %1;" ::"l"(p), "r"(a) : "memory"); }
__device__ __forceinline__ void ld_tile(uint32_t (&a)[20], const uint8_t* p) {
#pragma unroll
  for (int k = 0; k < 5; k++)
    asm volatile("ld.relaxed.gpu.global.v4.u32 {%0,%1,%2,%3}, [%4];" : "=r"(a[4 * k]), "=r"(a[4 * k + 1]), "=r"(a[4 * k + 2]), "=r"(a[4 * k + 3]) : "l"(p + k * 512) : "memory");
}
__device__ __forceinline__ uint32_t tag16(uint32_t v, uint32_t tag) { return (v & ~TAGM) | tag; }
__device__ __forceinline__ float tag32(float v, uint32_t ep) { return __uint_as_float((__float_as_uint(v) & ~3u) | ep); }
__device__ __forceinline__ void fix_tile(uint32_t (&a)[20], const uint8_t* p, uint32_t tag) {
  uint32_t n = 0;
  while (__any_sync(0xffffffffu, (((a[0] ^ tag) | (a[4] ^ tag) | (a[8] ^ tag) | (a[12] ^ tag) | (a[16] ^ tag)) & TAGM) != 0u) && ++n < SPIN_MAX) ld_tile(a, p);
}
__device__ __forceinline__ void probe_wait(uint32_t& ready, int i, const void* p, uint32_t tag) {
  uint32_t n = 0;
  while (!((ready >> i) & 1u) && ++n < SPIN_MAX) ready = __ballot_sync(0xffffffffu, ((ldcg32(p) ^ tag) & TAGM) == 0u);
}
__device__ __forceinline__ float gather16(const float* p, int stride, uint32_t ep) {
  uint32_t v[16], n = 0;
  while (true) {
    uint32_t bad = 0;
#pragma unroll
    for (int i = 0; i < 16; i++) v[i] = ldcg32(p + i * stride);
#pragma unroll
    for (int i = 0; i < 16; i++) bad |= v[i] ^ ep;
    if (!__any_sync(0xffffffffu, (bad & 3u) != 0u) || ++n >= SPIN_MAX) break;
  }
  float s = 0.f;
#pragma unroll
  for (int i = 0; i < 16; i++) s += __uint_as_float(v[i]);
  return s;
}
__device__ __forceinline__ void ld4(uint4 (&v)[4], const uint8_t* p) {
#pragma unroll
  for (int i = 0; i < 4; i++) v[i] = ldcg128(p + i * 512);
}
__device__ __forceinline__ void add4(float (&acc)[32], const uint4 (&v)[4]) {
#pragma unroll
  for (int i = 0; i < 4; i++) {
    acc[8 * i + 0] += bf_lo(v[i].x); acc[8 * i + 1] += bf_hi(v[i].x); acc[8 * i + 2] += bf_lo(v[i].y); acc[8 * i + 3] += bf_hi(v[i].y);
    acc[8 * i + 4] += bf_lo(v[i].z); acc[8 * i + 5] += bf_hi(v[i].z); acc[8 * i + 6] += bf_lo(v[i].w); acc[8 * i + 7] += bf_hi(v[i].w);
  }
}

template <int H>
__device__ __forceinline__ void qk_issue(float (&s)[32], const uint32_t (&q)[24], uint32_t kb) {
  constexpr uint64_t HI = desc_hi(1024, 128, 0);
  constexpr int J0 = (H == 0) ? 0 : (H == 1) ? 2 : (H == 2) ? 5 : 7;
  wg_rs64k(s, q[H * 6 + 0], q[H * 6 + 1], q[H * 6 + 2], q[H * 6 + 3], mkdesc(kb + J0 * 1024, HI), 0);
  wg_rs64k(s, q[H * 6 + 4], q[H * 6 + 5], 0u, 0u, mkdesc(kb + (J0 + 2) * 1024, HI), 1);
}
template <int H>
__device__ __forceinline__ void pv_issue(float (&o)[12], const uint32_t (&p)[16], uint32_t kb) {
  constexpr uint64_t HI = desc_hi(128, 1024, 0);
  constexpr int J0 = 3 * H;
#pragma unroll
  for (int i = 0; i < 4; i++)
    wg_rs24(o, p[4 * i], p[4 * i + 1], p[4 * i + 2], p[4 * i + 3], mkdesc(kb + 10240 + J0 * 1024 + i * 256, HI), 1);
}
__device__ __forceinline__ void softmax_chunk(float (&s)[32], uint32_t (&p)[16], float (&o)[12], float (&m)[2]) {
  float a0 = fmaxf(s[0], s[1]), a1 = fmaxf(s[2], s[3]), b0 = fmaxf(s[4], s[5]), b1 = fmaxf(s[6], s[7]);
#pragma unroll
  for (int t = 2; t < 8; t += 2) {
    a0 = fmaxf(a0, fmaxf(s[4 * t], s[4 * t + 1]));
    a1 = fmaxf(a1, fmaxf(s[4 * t + 2], s[4 * t + 3]));
    b0 = fmaxf(b0, fmaxf(s[4 * t + 4], s[4 * t + 5]));
    b1 = fmaxf(b1, fmaxf(s[4 * t + 6], s[4 * t + 7]));
  }
  a0 = fmaxf(a0, b0);
  a1 = fmaxf(a1, b1);
  a0 = fmaxf(a0, __shfl_xor_sync(0xffffffffu, a0, 1));
  a1 = fmaxf(a1, __shfl_xor_sync(0xffffffffu, a1, 1));
  a0 = fmaxf(a0, __shfl_xor_sync(0xffffffffu, a0, 2));
  a1 = fmaxf(a1, __shfl_xor_sync(0xffffffffu, a1, 2));
  float n0 = fmaxf(m[0], a0), n1 = fmaxf(m[1], a1);
  float al0 = ex2(m[0] - n0), al1 = ex2(m[1] - n1);
  m[0] = n0;
  m[1] = n1;
#pragma unroll
  for (int t = 0; t < 8; t++) {
    float e0 = ex2(s[4 * t] - n0), e1 = ex2(s[4 * t + 1] - n0), e2 = ex2(s[4 * t + 2] - n1), e3 = ex2(s[4 * t + 3] - n1);
    p[2 * t] = pack2(e0, e1);
    p[2 * t + 1] = pack2(e2, e3);
  }
#pragma unroll
  for (int t = 0; t < 3; t++) {
    o[4 * t] *= al0; o[4 * t + 1] *= al0; o[4 * t + 2] *= al1; o[4 * t + 3] *= al1;
  }
}
template <int H>
__device__ __forceinline__ void head_task(float (&s)[32], uint32_t (&p)[16], const uint32_t (&q)[24], float (&o)[12], float (&m)[2],
                                          uint32_t kb, uint32_t kn, int mode, int dthr) {
  if (H) WG_WAIT(1);
  reg_fence(s); reg_fence(o);
  if (mode) {
    asm volatile("" : "+r"(dthr));
#pragma unroll
    for (int t = 0; t < 8; t++) {
      s[4 * t + 0] = ((8 * t + 0 <= dthr) != (mode == 2)) ? s[4 * t + 0] : -INFINITY;
      s[4 * t + 1] = ((8 * t + 1 <= dthr) != (mode == 2)) ? s[4 * t + 1] : -INFINITY;
      s[4 * t + 2] = ((8 * t - 8 <= dthr) != (mode == 2)) ? s[4 * t + 2] : -INFINITY;
      s[4 * t + 3] = ((8 * t - 7 <= dthr) != (mode == 2)) ? s[4 * t + 3] : -INFINITY;
    }
  }
  softmax_chunk(s, p, o, m);
  if (H < 3) {
    WG_FENCE();
    qk_issue<(H + 2) & 3>(s, q, kn);
    pv_issue<H>(o, p, kb);
    WG_COMMIT();
  }
}

__device__ __forceinline__ void store_partial64(const float* a, uint8_t* dst, uint32_t tag) {
#pragma unroll
  for (int i = 0; i < 4; i++) {
    uint4 v;
    v.x = tag16(pack2(a[8 * i + 0], a[8 * i + 1]), tag);
    v.y = pack2(a[8 * i + 2], a[8 * i + 3]);
    v.z = pack2(a[8 * i + 4], a[8 * i + 5]);
    v.w = pack2(a[8 * i + 6], a[8 * i + 7]);
    *reinterpret_cast<uint4*>(dst + i * 512) = v;
  }
}

__global__ void __cluster_dims__(2, 1, 1) __launch_bounds__(384, 1) fused_block_kernel(const __grid_constant__ Params P) {
  extern __shared__ __align__(1024) uint8_t smem[];
  const uint32_t sb = s2u(smem);
  const int tid = threadIdx.x, lane = tid & 31, warp = __shfl_sync(0xffffffffu, tid >> 5, 0);
  const uint32_t rank = blockIdx.x & 1;
  const int rb = blockIdx.x & 15, c = blockIdx.x >> 4;
  const int tile = rb * 8 + c;
  const uint32_t bars = sb + OFF_MISC;
#define BAR(i) (bars + 8u * (uint32_t)(i))
  const int odd = c & 1;
  const int mainch = (c >> 1) * 5 + (odd ? 3 : 0), leftch = (c >> 1) * 10 + (odd ? 5 : 4);
  if (warp >= 8) asm volatile("setmaxnreg.dec.sync.aligned.u32 56;");
  if (lane == 0) {
    if (warp == 8) {
      asm volatile("prefetch.tensormap [%0];" ::"l"(&P.mWqM) : "memory");
      asm volatile("prefetch.tensormap [%0];" ::"l"(&P.mWqL) : "memory");
    } else {
      const int i0 = (warp < 8 ? warp + 3 : warp - 9) * 6;
#pragma unroll
      for (int u = 0; u < 6; u++) {
        const int i = i0 + u;
        if (i < 64) mbar_init(BAR(i), i < B_KVOWN ? 1 : i < B_Q23 ? 4 : i < B_QEMPTY ? 8 : 16);
      }
    }
    asm volatile("fence.mbarrier_init.release.cluster;" ::: "memory");
    if (warp == 9) {
      mbar_expect(BAR(B_QFULL), QST);
      tma2d(sb, &P.mX, 0, rb * 128, BAR(B_QFULL));
    }
  }
  __syncwarp();
  if (warp == 8) STAMPW(11);
  asm volatile("barrier.cluster.arrive.relaxed.aligned;" ::: "memory");
  if (warp == 8) {
    asm volatile("barrier.cluster.wait.acquire.aligned;\nbar.arrive 1, 384;" ::: "memory");
    STAMPW(8);
    if (lane == 0) {
#pragma unroll 1
      for (int kt = 0; kt < 4; kt++) {
        const uint32_t a = sb + kt * QST, fb = BAR(B_QFULL + kt);
        if (kt) mbar_expect(fb, QST);
        tma4d_mc(a + 16384 + rank * 12288, &P.mWqM, 0, kt * 64 + rank * 32, mainch, 0, fb);
        tma4d_mc(a + 40960 + rank * 3072, &P.mWqL, 0, kt * 64 + rank * 32, leftch, 0, fb);
        if (kt) tma2d(a, &P.mX, kt * 64, rb * 128, fb);
        if (kt == 0) STAMPW(10);
      }
    }
    __syncwarp();
    STAMPW(9);
  } else {
    asm volatile("bar.sync 1, 384;" ::: "memory");
  }
  const int sc = (27 * c + 3) >> 2;

  if (warp >= 8) {
    const uint32_t epoch = ldcg32(&g_epoch[tile]) + 1u;
    const uint32_t ep = epoch & 3u, tag = (epoch & 1u) | ((epoch & 2u) << 15);
    if (warp == 8) {
      if (lane == 0) {
#pragma unroll 1
        for (int kt = 4; kt < 10; kt++) {
          const int st = kt & 3;
          mbar_wait(BAR(B_QEMPTY + st), ((kt >> 2) - 1) & 1);
          const uint32_t a = sb + st * QST, fb = BAR(B_QFULL + st);
          mbar_expect(fb, QST);
          tma4d_mc(a + 16384 + rank * 12288, &P.mWqM, 0, kt * 64 + rank * 32, mainch, 0, fb);
          tma4d_mc(a + 40960 + rank * 3072, &P.mWqL, 0, kt * 64 + rank * 32, leftch, 0, fb);
          tma2d(a, &P.mX, kt * 64, rb * 128, fb);
        }
        const CUtensorMap* mW1 = rank ? &P.mW1b : &P.mW1a;
        asm volatile("prefetch.tensormap [%0];" ::"l"(&P.mWo) : "memory");
        asm volatile("prefetch.tensormap [%0];" ::"l"(mW1) : "memory");
        asm volatile("prefetch.tensormap [%0];" ::"l"(&P.mW2) : "memory");
        mbar_wait(BAR(B_QEMPTY + 0), 0);
        mbar_wait(BAR(B_QEMPTY + 1), 0);
        if (rb) mbar_wait(BAR(B_KVFULL + 3), 0);
        mbar_expect(BAR(B_WOB), 89600);
#pragma unroll 1
        for (int i = 0; i < 4 - (int)rank; i++) {
          const int pos = rank * 4 + i;
          tma3d_mc(sb + OFF_WOB + pos * 12800, &P.mWo, 0, ((c + pos) & 7) * 80, c * 5, BAR(B_WOB));
        }
#pragma unroll 1
        for (int s = 0; s < 8; s++) {
          if (s == 0) {
            mbar_wait(BAR(B_ATTP), 0);
            mbar_expect(BAR(B_WOB7), 12800);
            if (rank) tma3d_mc(sb + OFF_WOB + 7 * 12800, &P.mWo, 0, ((c + 7) & 7) * 80, c * 5, BAR(B_WOB7));
          } else if (s == 3) mbar_wait(BAR(B_WODP), 0);
          else if (s >= 5) mbar_wait(BAR(B_BEMPTY + s - 5), 0);
          const uint32_t fb = BAR(B_BFULL + s);
          mbar_expect(fb, 35840);
          tma3d_mc(sb + w1b_addr(s) + rank * 20480, mW1, 0, ((c + s) & 7) * 80, sc + rank * 4, fb);
        }
#pragma unroll 1
        for (int s = 0; s < 5; s++) {
          mbar_wait(s < 4 ? BAR(B_BEMPTY + 4 + s) : BAR(B_W2E), 0);
          const uint32_t dst = sb + (s & 3) * W2SLOT + rank * 14336, fb = BAR(B_W2FULL + s);
          const int bx0 = s == 0 ? 8 : ((c + 2 * s - 1) & 7), bx1 = s == 0 ? 9 : ((c + 2 * s) & 7);
          mbar_expect(fb, W2SLOT);
          tma2d_mc(dst, &P.mW2, bx0 * 64, sc * 32 + rank * 112, fb);
          tma2d_mc(dst + 28672, &P.mW2, bx1 * 64, sc * 32 + rank * 112, fb);
        }
      }
      __syncwarp();
    } else {
      if (warp == 11) {
        mbar_wait(BAR(B_QFULL + 3), 0);
        if (lane == 0) {
          l2_prefetch_bulk(reinterpret_cast<const uint8_t*>(P.wo) + tile * 6400, 6400);
          l2_prefetch_bulk(reinterpret_cast<const uint8_t*>(P.w1) + tile * 17280, 17280);
          l2_prefetch_bulk(reinterpret_cast<const uint8_t*>(P.w2) + tile * 17280, 17280);
        }
        mbar_wait(BAR(B_PRE), 0);
#pragma unroll 1
        for (int q = lane; q < 60; q += 32) {
          float4 a = make_float4(0.f, 0.f, 0.f, 0.f);
#pragma unroll
          for (int i = 0; i < 8; i++) {
            const float4 v = *reinterpret_cast<const float4*>(smem + OFF_PRE + i * 960 + q * 16);
            a.x += v.x; a.y += v.y; a.z += v.z; a.w += v.w;
          }
          *reinterpret_cast<float4*>(&g_csq[tile * 240 + q * 4]) = make_float4(tag32(a.x, ep), tag32(a.y, ep), tag32(a.z, ep), tag32(a.w, ep));
        }
        __syncwarp();
        STAMPW(0);
        mbar_wait(BAR(B_Q23), 0);
      } else {
        mbar_wait(BAR(B_KVOWN + warp - 9), 0);
        if (lane == 0) {
          asm volatile("cp.async.bulk.global.shared::cta.bulk_group [%0], [%1], %2;\ncp.async.bulk.commit_group;"
                       ::"l"(g_kv + (size_t)((rb * 2 + warp - 9) * 8 + c) * KVB), "r"(sb + kv_addr(warp - 5)), "r"(KVB) : "memory");
        }
      }
#pragma unroll 1
      for (int bi = warp == 9 ? 2 : warp == 10 ? 3 : 1; bi >= 0; bi -= (warp == 9 ? 2 : 4)) {
        const int blk = 2 * rb - 4 + bi;
        if (blk < 0) continue;
        const uint8_t* src = g_kv + (size_t)(blk * 8 + c) * KVB;
        const uint32_t dst = sb + kv_addr(bi);
        uint32_t n = 0, ph = 0;
        while (!__all_sync(0xffffffffu, ((ldcg32(src + lane * 704 + 692) ^ tag) & TAGM) == 0u) && ++n < SPIN_MAX) {}
        if (warp == 9 && bi == 2) STAMPW(3);
        while (true) {
          if (lane == 0) {
            fence_async_glob();
            mbar_expect(BAR(B_KVLAND + bi), KVB);
            bulk_load(dst, src, KVB, BAR(B_KVLAND + bi));
          }
          mbar_wait(BAR(B_KVLAND + bi), ph);
          ph ^= 1u;
          uint32_t bad = 0;
#pragma unroll 11
          for (int i = 0; i < 44; i++) {
            uint32_t v;
            asm volatile("ld.shared.u32 %0, [%1];" : "=r"(v) : "r"(dst + (i * 32 + lane) * 16 + 4) : "memory");
            bad |= v ^ tag;
          }
          if (!__any_sync(0xffffffffu, (bad & TAGM) != 0u) || ++n >= SPIN_MAX) break;
        }
        if (lane == 0) {
          asm volatile("cp.async.bulk.wait_group.read 0;" ::: "memory");
          mbar_arrive(BAR(B_KVFULL + bi));
        }
        if (warp == 9 && bi == 2) STAMPW(5);
      }
      __syncwarp();
      asm volatile("barrier.cluster.wait.acquire.aligned;" ::: "memory");
      if (warp == 10) {
        const int col = sc * 32 + lane * 8;
        const uint8_t* wb = reinterpret_cast<const uint8_t*>(P.w1) + (size_t)rb * 40 * 3456 + (size_t)col * 2;
        float acc[8];
#pragma unroll
        for (int i = 0; i < 8; i++) acc[i] = 0.f;
        if (lane < 28 && col < 1728) {
#pragma unroll 1
          for (int i = 0; i < 40; i += 8) {
            uint4 v[8];
#pragma unroll
            for (int u = 0; u < 8; u++) v[u] = __ldg(reinterpret_cast<const uint4*>(wb + (size_t)(i + u) * 3456));
#pragma unroll
            for (int u = 0; u < 8; u++) {
              acc[0] += bf_lo(v[u].x); acc[1] += bf_hi(v[u].x); acc[2] += bf_lo(v[u].y); acc[3] += bf_hi(v[u].y);
              acc[4] += bf_lo(v[u].z); acc[5] += bf_hi(v[u].z); acc[6] += bf_lo(v[u].w); acc[7] += bf_hi(v[u].w);
            }
          }
        }
        if (lane < 28) {
          float4* dst = reinterpret_cast<float4*>(&g_cs1[tile * 224 + lane * 8]);
          dst[0] = make_float4(tag32(acc[0], ep), tag32(acc[1], ep), tag32(acc[2], ep), tag32(acc[3], ep));
          dst[1] = make_float4(tag32(acc[4], ep), tag32(acc[5], ep), tag32(acc[6], ep), tag32(acc[7], ep));
        }
        STAMPW(4);
      } else if (warp == 11) {
        mbar_wait(BAR(B_ATTP), 0);
#pragma unroll 1
        for (int u = lane; u < 224; u += 32) *reinterpret_cast<float*>(smem + OFF_XS + u * 4) = gather16(g_cs1 + c * 224 + u, 1792, ep);
        __syncwarp();
        if (lane == 0) mbar_arrive(BAR(B_CS1));
        STAMPW(1);
      }
    }
    mbar_wait(BAR(B_W2D), 0);
    if (warp == 9 || warp == 10) {
      const uint8_t* src = g_part + (size_t)((rb * 2 + warp - 9) * 8 + c) * 65536;
      const uint8_t* pw = src + ((c - 1 - (lane >> 2)) & 7) * 8192 + (lane & 3) * 2048 + 2032;
      uint32_t ready = 0;
#pragma unroll 1
      for (int u = 0; u < 6; u++) {
        if (u == 3) mbar_wait(BAR(B_W2D + 1), 0);
        uint32_t n = 0;
        while (((~ready >> (4 * u)) & 15u) && ++n < SPIN_MAX) ready = __ballot_sync(0xffffffffu, ((ldcg32(pw) ^ tag) & TAGM) == 0u);
        if (lane == 0) {
          const uint32_t fb = BAR(B_PL + 2 * u + warp - 9);
          fence_async_glob();
          mbar_expect(fb, 8192);
          bulk_load(sb + W2SLOT + u * 16384 + (u >= 3 ? 8192 : 0) + (warp - 9) * 8192, src + ((c - 1 - u) & 7) * 8192, 8192, fb);
        }
      }
    } else {
#pragma unroll 1
      for (int j = warp == 8 ? 0 : 4, je = j + 4; j < je; j++) {
        uint4 v8[8], hv;
        uint32_t n = 0, bad;
        const uint8_t* p8 = g_p89 + (size_t)tile * 32768 + j * 512 + lane * 16;
        const uint8_t* ph = g_h + (size_t)tile * 20480 + (32 + j) * 512 + lane * 16;
        asm volatile("" : "+l"(p8), "+l"(ph));
        do {
#pragma unroll
          for (int u = 0; u < 8; u++) v8[u] = ldcg128(p8 + u * 4096);
          hv = ldcg128(ph);
          bad = hv.x ^ tag;
#pragma unroll
          for (int u = 0; u < 8; u++) bad |= v8[u].x ^ tag;
        } while (__any_sync(0xffffffffu, (bad & TAGM) != 0u) && ++n < SPIN_MAX);
        float f[8] = {bf_lo(hv.x), bf_hi(hv.x), bf_lo(hv.y), bf_hi(hv.y), bf_lo(hv.z), bf_hi(hv.z), bf_lo(hv.w), bf_hi(hv.w)};
#pragma unroll
        for (int u = 0; u < 8; u++) {
          f[0] += bf_lo(v8[u].x); f[1] += bf_hi(v8[u].x); f[2] += bf_lo(v8[u].y); f[3] += bf_hi(v8[u].y);
          f[4] += bf_lo(v8[u].z); f[5] += bf_hi(v8[u].z); f[6] += bf_lo(v8[u].w); f[7] += bf_hi(v8[u].w);
        }
        uint8_t* op = reinterpret_cast<uint8_t*>(P.out) + (size_t)(tile * 16 + (lane >> 2)) * 1280 + 1024 + j * 32 + (lane & 3) * 4;
        *reinterpret_cast<uint32_t*>(op) = pack2(f[0], f[1]);
        *reinterpret_cast<uint32_t*>(op + 8 * 1280) = pack2(f[2], f[3]);
        *reinterpret_cast<uint32_t*>(op + 16) = pack2(f[4], f[5]);
        *reinterpret_cast<uint32_t*>(op + 8 * 1280 + 16) = pack2(f[6], f[7]);
      }
      if (warp == 11) STAMPW(2);
      if (warp == 11 && lane == 0) st_flag(&g_epoch[tile], epoch);
    }
  } else {
    const int r = warp >> 2, w = warp & 3, gq = lane >> 2, tq = lane & 3;
    asm volatile("setmaxnreg.inc.sync.aligned.u32 224;");
    STAMP(4);
    uint4 xv[5], wv[5];
    uint32_t ep;
    const int b = rb * 2 + r;
    uint32_t q[24], tag;
    STAMP(0);
    {
      float accM[96], accL[24];
      uint2 s0u, s1u;
#define QKV_ISSUE(kt) do { \
        const uint32_t a = sb + ((kt) & 3) * QST; \
        const uint64_t da = mkdesc(a + r * 8192, desc_hi(16, 1024, 1)); \
        const uint64_t dm = mkdesc(a + 16384, desc_hi(2048, 512, 2)); \
        const uint64_t dl = mkdesc(a + 40960, desc_hi(1024, 256, 3)); \
        mbar_wait(BAR(B_QFULL + ((kt) & 3)), ((kt) >> 2) & 1); \
        WG_FENCE(); \
        _Pragma("unroll") for (int k = 0; k < 4; k++) { \
          wg_ss192(accM, da + k * 2, dm + (k >> 1) * 768 + (k & 1) * 64, (kt) | k); \
          wg_ss48(accL, da + k * 2, dl + (k >> 1) * 192 + (k & 1) * 32, (kt) | k); \
        } \
        WG_COMMIT(); } while (0)
      QKV_ISSUE(0);
      STAMP(1);
      {
          const uint8_t* xb = reinterpret_cast<const uint8_t*>(P.x) + (size_t)(rb * 128 + c * 16 + warp * 2 + (lane >> 4)) * 1280 + (lane & 15) * 16;
          const int cl = lane < 30 ? lane : 29;
          const uint8_t* wb = reinterpret_cast<const uint8_t*>(P.wqkv) + (size_t)(rb * 40 + warp * 5) * 3840 + (cl / 10) * 1280 + c * 160 + (cl % 10) * 16;
#pragma unroll
          for (int i = 0; i < 5; i++) wv[i] = ldnc128(wb + i * 3840);
#pragma unroll
          for (int i = 0; i < 5; i++) xv[i] = ldnc128(xb + i * 256);
          ep = ldcg32(&g_epoch[tile]);
      }
#pragma unroll 1
      for (int kt = 1; kt < 10; kt++) {
        QKV_ISSUE(kt);
        if (kt == STATKT) {
          STAMP(19);
#pragma unroll
          for (int i = 0; i < 5; i++) asm volatile("" : "+r"(wv[i].x), "+r"(wv[i].y), "+r"(wv[i].z), "+r"(wv[i].w));
          float a[8];
#pragma unroll
          for (int i = 0; i < 8; i++) a[i] = 0.f;
#pragma unroll
          for (int u = 0; u < 5; u++) {
            a[0] += bf_lo(wv[u].x); a[1] += bf_hi(wv[u].x); a[2] += bf_lo(wv[u].y); a[3] += bf_hi(wv[u].y);
            a[4] += bf_lo(wv[u].z); a[5] += bf_hi(wv[u].z); a[6] += bf_lo(wv[u].w); a[7] += bf_hi(wv[u].w);
          }
          if (lane < 30) {
            float4* dst = reinterpret_cast<float4*>(smem + OFF_PRE + warp * 960 + lane * 32);
            dst[0] = make_float4(a[0], a[1], a[2], a[3]);
            dst[1] = make_float4(a[4], a[5], a[6], a[7]);
          }
          __syncwarp();
          if (lane == 0) mbar_arrive(BAR(B_PRE));
          STAMP(5);
        } else if (kt == STATKT + 1) {
          asm volatile("" : "+r"(ep));
#pragma unroll
          for (int i = 0; i < 5; i++) asm volatile("" : "+r"(xv[i].x), "+r"(xv[i].y), "+r"(xv[i].z), "+r"(xv[i].w));
          ep = (ep + 1u) & 3u;
          float s = 0.f;
#pragma unroll
          for (int i = 0; i < 5; i++)
            s += ((bf_lo(xv[i].x) + bf_hi(xv[i].x)) + (bf_lo(xv[i].y) + bf_hi(xv[i].y))) + ((bf_lo(xv[i].z) + bf_hi(xv[i].z)) + (bf_lo(xv[i].w) + bf_hi(xv[i].w)));
#pragma unroll
          for (int o = 8; o; o >>= 1) s += __shfl_xor_sync(0xffffffffu, s, o);
          const float mean = s * (1.f / 640.f);
          float m2 = 0.f;
#pragma unroll
          for (int i = 0; i < 5; i++) {
            const uint32_t u[4] = {xv[i].x, xv[i].y, xv[i].z, xv[i].w};
#pragma unroll
            for (int j = 0; j < 4; j++) {
              const float d0 = bf_lo(u[j]) - mean, d1 = bf_hi(u[j]) - mean;
              m2 += d0 * d0 + d1 * d1;
            }
          }
#pragma unroll
          for (int o = 8; o; o >>= 1) m2 += __shfl_xor_sync(0xffffffffu, m2, o);
          if ((lane & 15) == 0)
            g_xstat[rb * 128 + c * 16 + warp * 2 + (lane >> 4)] = make_float2(mean, tag32(rsqrtf(m2 * (1.f / 640.f) + 1e-5f), ep));
        } else if (kt == STATKT + 2) {
          asm volatile("barrier.cluster.wait.acquire.aligned;" ::: "memory");
        } else
        if (kt == 9) {
          const float cs = gather16(g_csq + c * 240 + (tid < 240 ? tid : 239), 1920, ep);
          if (tid < 240) *reinterpret_cast<float*>(smem + OFF_CS + tid * 4) = cs;
          uint32_t n = 0;
          do {
            s0u = ldcg64(&g_xstat[b * 64 + w * 16 + gq]);
            s1u = ldcg64(&g_xstat[b * 64 + w * 16 + gq + 8]);
          } while (__any_sync(0xffffffffu, (((s0u.y ^ ep) | (s1u.y ^ ep)) & 3u) != 0u) && ++n < SPIN_MAX);
          if (lane == 0) mbar_arrive(BAR(B_STAT));
        }
        WG_WAIT(1);
        if (lane == 0) {
          mbar_arrive_pair(BAR(B_QEMPTY + ((kt - 1) & 3)));
          if (kt == 8) mbar_arrive(BAR(B_Q23));
        }
      }
      WG_WAIT(0);
      reg_fence(accM); reg_fence(accL);
      if (lane == 0) mbar_arrive_pair(BAR(B_QEMPTY + 1));
      STAMP(2);
      tag = (ep & 1u) | ((ep & 2u) << 15);
      mbar_wait(BAR(B_STAT), 0);
      mbar_wait(BAR(B_Q23), 0);
      const float2 s0 = make_float2(__uint_as_float(s0u.x), __uint_as_float(s0u.y)), s1 = make_float2(__uint_as_float(s1u.x), __uint_as_float(s1u.y));
      const uint32_t km = tq == 1 ? ~TAGM : 0xffffffffu, kt1 = tq == 1 ? tag : 0u;
      const uint32_t csM = sb + OFF_CS + (odd ? 64 : 0) + tq * 8, csL = sb + OFF_CS + (odd ? 0 : 256) + tq * 8;
      const uint32_t kvo = sb + kv_addr(4 + r) + (uint32_t)(w * 16 + ((lane >> 3) & 1) * 8 + (lane & 7)) * 16u + (uint32_t)(lane >> 4) * 1024u;
      const float qs = 0.22360679774997896f * 1.4426950408889634f;
      const bool lo = tq < 2;
      uint32_t qj[20];
#pragma unroll
      for (int mm = 0; mm < 3; mm++) {
        const int mat = (mm + 1) % 3;
        const float r0 = mat == 0 ? s0.y * qs : s0.y, r1 = mat == 0 ? s1.y * qs : s1.y;
        const float n0 = -s0.x * r0, n1 = -s1.x * r1;
        uint32_t pk[20];
#pragma unroll
        for (int t = 0; t < 10; t++) {
          const float* a = t < 8 ? &accM[(mat * 8 + t) * 4] : &accL[(mat * 2 + t - 8) * 4];
          const float2 cs = lds64f(t < 8 ? csM + mat * 320 + t * 32 : csL + mat * 320 + (t - 8) * 32);
          pk[2 * t] = pack2(fmaf(a[0], r0, cs.x * n0), fmaf(a[1], r0, cs.y * n0));
          pk[2 * t + 1] = pack2(fmaf(a[2], r1, cs.x * n1), fmaf(a[3], r1, cs.y * n1));
        }
        if (mat == 1) {
#pragma unroll
          for (int i = 0; i < 20; i++) pk[i] = (pk[i] & km) | kt1;
#pragma unroll
          for (int t = 0; t < 8; t += 2) stsm4(kvo + (odd ? 2048 : 0) + t * 1024, pk[2 * t], pk[2 * t + 1], pk[2 * t + 2], pk[2 * t + 3]);
          stsm4(kvo + (odd ? 0 : 8192), pk[16], pk[17], pk[18], pk[19]);
        } else {
#pragma unroll
          for (int i = 0; i < 20; i++) qj[i] = odd ? pk[(i + 16) % 20] : pk[i];
        }
        if (mat == 2) {
          const uint32_t one = (tq & 1) ? 0u : 0x3f80u;
          uint32_t vv[24];
#pragma unroll
          for (int hp = 0; hp < 2; hp++) {
            const int j = hp * 10;
#pragma unroll
            for (int i = 0; i < 4; i++) { vv[hp * 12 + i] = qj[j + i]; vv[hp * 12 + 8 + i] = qj[j + 6 + i]; }
            vv[hp * 12 + 4] = lo ? qj[j + 4] : one; vv[hp * 12 + 5] = lo ? qj[j + 5] : one;
            vv[hp * 12 + 6] = lo ? one : qj[j + 4]; vv[hp * 12 + 7] = lo ? one : qj[j + 5];
          }
#pragma unroll
          for (int i = 0; i < 24; i++) vv[i] = (vv[i] & km) | kt1;
#pragma unroll
          for (int t = 0; t < 6; t++) stsm4(kvo + 10240 + t * 2048, vv[4 * t], vv[4 * t + 1], vv[4 * t + 2], vv[4 * t + 3]);
          fence_async_smem();
          __syncwarp();
          if (lane == 0) mbar_arrive(BAR(B_KVOWN + r));
        }
      }
#pragma unroll
      for (int hp = 0; hp < 2; hp++) {
        const int j = hp * 10;
        q[hp * 12 + 0] = qj[j + 0]; q[hp * 12 + 1] = qj[j + 1]; q[hp * 12 + 2] = qj[j + 2]; q[hp * 12 + 3] = qj[j + 3];
        q[hp * 12 + 4] = lo ? qj[j + 4] : 0u; q[hp * 12 + 5] = lo ? qj[j + 5] : 0u;
        q[hp * 12 + 6] = lo ? 0u : qj[j + 4]; q[hp * 12 + 7] = lo ? 0u : qj[j + 5];
        q[hp * 12 + 8] = qj[j + 6]; q[hp * 12 + 9] = qj[j + 7]; q[hp * 12 + 10] = qj[j + 8]; q[hp * 12 + 11] = qj[j + 9];
      }
    }
    STAMP(3);
    uint32_t x0[20], xr[20];
    const int row_lo = b * 64 + w * 16 + gq;
    {
      float o0[12], o1[12], o2[12], o3[12], m[4][2];
#pragma unroll
      for (int i = 0; i < 12; i++) { o0[i] = 0.f; o1[i] = 0.f; o2[i] = 0.f; o3[i] = 0.f; }
#pragma unroll
      for (int i = 0; i < 4; i++) m[i][0] = m[i][1] = -INFINITY;
      float s0[32], s1[32];
      uint32_t p0[16], p1[16];
      const int dthr = w * 16 + gq - 2 * tq;
      const uint32_t seq = r ? 0x13245u : 0x01324u;
      const int nit = rb >= 2 ? 5 : 2 * rb + 1 + r;
      mbar_wait(BAR(B_KVOWN + r), 0);
      uint32_t kb = sb + kv_addr(4 + r), kp = kb;
      WG_FENCE();
      qk_issue<0>(s0, q, kb);
      WG_COMMIT();
#pragma unroll
      for (int i = 0; i < 16; i++) p1[i] = 0u;
      WG_WAIT(0);
#pragma unroll 1
      for (int it = 0; it < nit; it++) {
        const int mode = it == 0 ? 1 : it == 4 ? 2 : 0;
        WG_FENCE();
        qk_issue<1>(s1, q, kb);
        pv_issue<3>(o3, p1, kp);
        WG_COMMIT();
        head_task<0>(s0, p0, q, o0, m[0], kb, kb, mode, dthr);
        head_task<1>(s1, p1, q, o1, m[1], kb, kb, mode, dthr);
        kp = kb;
        if (it + 1 < nit) {
          const int bi = (seq >> (4 * it + 4)) & 15;
          mbar_wait(bi == 4 ? BAR(B_KVOWN) : BAR(B_KVFULL + bi), 0);
          kb = sb + kv_addr(bi);
        }
        head_task<2>(s0, p0, q, o2, m[2], kp, kb, mode, dthr);
        head_task<3>(s1, p1, q, o3, m[3], kp, kb, mode, dthr);
        WG_WAIT(0);
      }
      WG_FENCE();
      pv_issue<3>(o3, p1, kp);
      WG_COMMIT();
      const uint8_t* xp = reinterpret_cast<const uint8_t*>(P.x) + (size_t)row_lo * 1280 + c * 160 + tq * 4;
#pragma unroll
      for (int t = 0; t < 10; t++) {
        xr[2 * t] = ldnc32(xp + t * 16);
        xr[2 * t + 1] = ldnc32(xp + 8 * 1280 + t * 16);
      }
      WG_WAIT(0);
      reg_fence(o0); reg_fence(o1); reg_fence(o2); reg_fence(o3); reg_fence(s0); reg_fence(s1);
      if (lane == 0) mbar_arrive_pair(BAR(B_ATTP));
      float inv[4][2];
      inv[0][0] = rcp(__shfl_sync(0xffffffffu, o0[8], (lane & 28) + 2));
      inv[0][1] = rcp(__shfl_sync(0xffffffffu, o0[10], (lane & 28) + 2));
      inv[1][0] = rcp(__shfl_sync(0xffffffffu, o1[0], lane & 28));
      inv[1][1] = rcp(__shfl_sync(0xffffffffu, o1[2], lane & 28));
      inv[2][0] = rcp(__shfl_sync(0xffffffffu, o2[8], (lane & 28) + 2));
      inv[2][1] = rcp(__shfl_sync(0xffffffffu, o2[10], (lane & 28) + 2));
      inv[3][0] = rcp(__shfl_sync(0xffffffffu, o3[0], lane & 28));
      inv[3][1] = rcp(__shfl_sync(0xffffffffu, o3[2], lane & 28));
      const bool lo = tq < 2;
#define OPK(dst, o, t, h) do { x0[dst] = pack2(o[4 * (t)] * inv[h][0], o[4 * (t) + 1] * inv[h][0]); x0[dst + 1] = pack2(o[4 * (t) + 2] * inv[h][1], o[4 * (t) + 3] * inv[h][1]); } while (0)
#define OPK2(dst, oa, ha, ob, hb) do { \
        const float i0 = lo ? inv[ha][0] : inv[hb][0], i1 = lo ? inv[ha][1] : inv[hb][1]; \
        x0[dst] = pack2((lo ? oa[8] : ob[0]) * i0, (lo ? oa[9] : ob[1]) * i0); \
        x0[dst + 1] = pack2((lo ? oa[10] : ob[2]) * i1, (lo ? oa[11] : ob[3]) * i1); } while (0)
      OPK(0, o0, 0, 0); OPK(2, o0, 1, 0); OPK2(4, o0, 0, o1, 1); OPK(6, o1, 1, 1); OPK(8, o1, 2, 1);
      OPK(10, o2, 0, 2); OPK(12, o2, 1, 2); OPK2(14, o2, 2, o3, 3); OPK(16, o3, 1, 3); OPK(18, o3, 2, 3);
    }
    const int bw = b * 4 + w;
    const size_t tile_off = (size_t)bw * 20480 + lane * 16;
    const size_t probe_off = (size_t)bw * 20480 + ((c + lane) & 7) * 2560 + 2544;
    {
#pragma unroll
      for (int k = 0; k < 5; k++) {
        x0[4 * k] = tag16(x0[4 * k], tag);
        stg128(g_o + tile_off + c * 2560 + k * 512, x0[4 * k], x0[4 * k + 1], x0[4 * k + 2], x0[4 * k + 3]);
      }
      STAMP(6);
      const uint32_t pv = ldcg32(g_o + probe_off);
      float acc[40];
#pragma unroll
      for (int t = 0; t < 10; t++) {
        acc[4 * t] = bf_lo(xr[2 * t]); acc[4 * t + 1] = bf_hi(xr[2 * t]); acc[4 * t + 2] = bf_lo(xr[2 * t + 1]); acc[4 * t + 3] = bf_hi(xr[2 * t + 1]);
      }
      constexpr uint64_t HI = desc_hi(2560, 256, 3);
      const uint64_t db = mkdesc(sb + OFF_WOB, HI);
      mbar_wait(BAR(B_WOB), 0);
      WG_FENCE();
#pragma unroll
      for (int k = 0; k < 5; k++) wg_rs80(acc, x0[4 * k], x0[4 * k + 1], x0[4 * k + 2], x0[4 * k + 3], db + k * 32, 1);
      WG_COMMIT();
      uint32_t xa[7][20], ready = __ballot_sync(0xffffffffu, ((pv ^ tag) & TAGM) == 0u);
#pragma unroll
      for (int i = 1; i < 8; i++) {
        probe_wait(ready, i, g_o + probe_off, tag);
        if (i == 7) WG_WAIT(0);
        ld_tile(xa[i - 1], g_o + tile_off + ((c + i) & 7) * 2560);
      }
      STAMP(7);
#pragma unroll
      for (int i = 1; i < 8; i++) {
        if (i == 7) mbar_wait(BAR(B_WOB7), 0);
        fix_tile(xa[i - 1], g_o + tile_off + ((c + i) & 7) * 2560, tag);
        WG_FENCE();
#pragma unroll
        for (int k = 0; k < 5; k++) wg_rs80(acc, xa[i - 1][4 * k], xa[i - 1][4 * k + 1], xa[i - 1][4 * k + 2], xa[i - 1][4 * k + 3], db + i * 800 + k * 32, 1);
        WG_COMMIT();
      }
      WG_WAIT(0);
      reg_fence(acc);
      if (lane == 0) mbar_arrive_pair(BAR(B_WODP));
      STAMP(8);
      float sum0 = 0.f, sum1 = 0.f;
#pragma unroll
      for (int t = 0; t < 10; t++) {
        x0[2 * t] = pack2(acc[4 * t], acc[4 * t + 1]);
        x0[2 * t + 1] = pack2(acc[4 * t + 2], acc[4 * t + 3]);
      }
#pragma unroll
      for (int k = 0; k < 5; k++) {
        x0[4 * k] = tag16(x0[4 * k], tag);
        stg128(g_h + tile_off + c * 2560 + k * 512, x0[4 * k], x0[4 * k + 1], x0[4 * k + 2], x0[4 * k + 3]);
      }
#pragma unroll
      for (int t = 0; t < 10; t++) {
        sum0 += bf_lo(x0[2 * t]) + bf_hi(x0[2 * t]);
        sum1 += bf_lo(x0[2 * t + 1]) + bf_hi(x0[2 * t + 1]);
      }
      sum0 += __shfl_xor_sync(0xffffffffu, sum0, 1);
      sum1 += __shfl_xor_sync(0xffffffffu, sum1, 1);
      sum0 += __shfl_xor_sync(0xffffffffu, sum0, 2);
      sum1 += __shfl_xor_sync(0xffffffffu, sum1, 2);
      const float mu0 = sum0 * (1.f / 80.f), mu1 = sum1 * (1.f / 80.f);
      float v0 = 0.f, v1 = 0.f;
#pragma unroll
      for (int t = 0; t < 10; t++) {
        const float d0 = bf_lo(x0[2 * t]) - mu0, d1 = bf_hi(x0[2 * t]) - mu0, d2 = bf_lo(x0[2 * t + 1]) - mu1, d3 = bf_hi(x0[2 * t + 1]) - mu1;
        v0 += d0 * d0 + d1 * d1;
        v1 += d2 * d2 + d3 * d3;
      }
      v0 += __shfl_xor_sync(0xffffffffu, v0, 1);
      v1 += __shfl_xor_sync(0xffffffffu, v1, 1);
      v0 += __shfl_xor_sync(0xffffffffu, v0, 2);
      v1 += __shfl_xor_sync(0xffffffffu, v1, 2);
      if (tq < 2) g_hstat[(bw * 8 + c) * 16 + gq + tq * 8] = make_float2(tq ? mu1 : mu0, tag32(tq ? v1 : v0, ep));
    }
    uint32_t ha[56];
    {
      float acc[112];
      constexpr uint64_t HI = desc_hi(5120, 512, 2);
#define W1_ISSUE(xx, i) do { \
        const uint64_t db = mkdesc(sb + w1b_addr(i), HI); \
        mbar_wait(BAR(B_BFULL + (i)), 0); \
        WG_FENCE(); \
        _Pragma("unroll") for (int k = 0; k < 5; k++) wg_rs224(acc, xx[4 * k], xx[4 * k + 1], xx[4 * k + 2], xx[4 * k + 3], db + k * 64, (i) | k); \
        WG_COMMIT(); } while (0)
#define W1_STEP(xx, xp, i) do { \
        fix_tile(xx, ht + ((c + (i)) & 7) * 2560, tag); \
        W1_ISSUE(xx, i); \
        WG_WAIT(1); \
        if ((i) != 4 && lane == 0) mbar_arrive_pair(BAR(B_BEMPTY - 1 + (i))); \
        if ((i) < 5) ld_tile(xp, ht + ((c + (i) + 3) & 7) * 2560); } while (0)
      W1_ISSUE(x0, 0);
      STAMP(9);
      const uint8_t* ht = g_h + tile_off;
      uint32_t x1[20], x2[20], x3[20], ready = 0;
      probe_wait(ready, 1, g_h + probe_off, tag);
      ld_tile(x1, ht + ((c + 1) & 7) * 2560);
      probe_wait(ready, 2, g_h + probe_off, tag);
      ld_tile(x2, ht + ((c + 2) & 7) * 2560);
      probe_wait(ready, 3, g_h + probe_off, tag);
      ld_tile(x3, ht + ((c + 3) & 7) * 2560);
      STAMP(10);
#pragma unroll 1
      for (int i = 1; ; i += 4) {
        W1_STEP(x1, x0, i);
        W1_STEP(x2, x1, i + 1);
        W1_STEP(x3, x2, i + 2);
        if (i == 5) break;
        W1_STEP(x0, x3, i + 3);
      }
      uint2 hs[4];
      {
        const float2* hp = &g_hstat[(bw * 8 + tq * 2) * 16 + gq];
        uint32_t n = 0;
        do {
          hs[0] = ldcg64(hp); hs[1] = ldcg64(hp + 16); hs[2] = ldcg64(hp + 8); hs[3] = ldcg64(hp + 24);
        } while (__any_sync(0xffffffffu, (((hs[0].y ^ ep) | (hs[1].y ^ ep) | (hs[2].y ^ ep) | (hs[3].y ^ ep)) & 3u) != 0u) && ++n < SPIN_MAX);
      }
      float mean0, mean1, rs0, rs1;
      {
        const float a0 = __uint_as_float(hs[0].x), a1 = __uint_as_float(hs[1].x), b0 = __uint_as_float(hs[2].x), b1 = __uint_as_float(hs[3].x);
        float t0 = a0 + a1, t1 = b0 + b1;
        t0 += __shfl_xor_sync(0xffffffffu, t0, 1);
        t1 += __shfl_xor_sync(0xffffffffu, t1, 1);
        t0 += __shfl_xor_sync(0xffffffffu, t0, 2);
        t1 += __shfl_xor_sync(0xffffffffu, t1, 2);
        mean0 = t0 * 0.125f;
        mean1 = t1 * 0.125f;
        float u0 = __uint_as_float(hs[0].y) + __uint_as_float(hs[1].y) + 80.f * ((a0 - mean0) * (a0 - mean0) + (a1 - mean0) * (a1 - mean0));
        float u1 = __uint_as_float(hs[2].y) + __uint_as_float(hs[3].y) + 80.f * ((b0 - mean1) * (b0 - mean1) + (b1 - mean1) * (b1 - mean1));
        u0 += __shfl_xor_sync(0xffffffffu, u0, 1);
        u1 += __shfl_xor_sync(0xffffffffu, u1, 1);
        u0 += __shfl_xor_sync(0xffffffffu, u0, 2);
        u1 += __shfl_xor_sync(0xffffffffu, u1, 2);
        rs0 = 0.5f * rsqrtf(u0 * (1.f / 640.f) + 1e-5f);
        rs1 = 0.5f * rsqrtf(u1 * (1.f / 640.f) + 1e-5f);
      }
      mbar_wait(BAR(B_CS1), 0);
      WG_WAIT(0);
      reg_fence(acc);
      if (lane == 0) mbar_arrive_pair(BAR(B_BEMPTY + 7));
      STAMP(11);
      const float n0 = -mean0 * rs0, n1 = -mean1 * rs1;
#pragma unroll
      for (int t = 0; t < 28; t++) {
        const float2 cs = lds64f(sb + OFF_XS + t * 32 + tq * 8);
        const float h0 = fmaf(acc[4 * t], rs0, cs.x * n0), h1 = fmaf(acc[4 * t + 1], rs0, cs.y * n0);
        const float h2 = fmaf(acc[4 * t + 2], rs1, cs.x * n1), h3 = fmaf(acc[4 * t + 3], rs1, cs.y * n1);
        ha[2 * t] = pack2(fmaf(h0, tanh_fast(h0), h0), fmaf(h1, tanh_fast(h1), h1));
        ha[2 * t + 1] = pack2(fmaf(h2, tanh_fast(h2), h2), fmaf(h3, tanh_fast(h3), h3));
      }
      if ((c & 3) == 3) {
#pragma unroll
        for (int t = 48; t < 56; t++) ha[t] = 0u;
      }
    }
    STAMP(12);
    {
      float accA[64], accB[64];
      constexpr uint64_t HI = desc_hi(28672, 1024, 1);
      const uint32_t lane_off = w * 2048 + lane * 16;
#define W2_ISSUE(acc, s) do { \
        mbar_wait(BAR(B_W2FULL + (s)), 0); \
        const uint64_t db = mkdesc(sb + ((s) & 3) * W2SLOT, HI); \
        WG_FENCE(); \
        _Pragma("unroll") for (int k = 0; k < 14; k++) wg_rs128(acc, ha[4 * k], ha[4 * k + 1], ha[4 * k + 2], ha[4 * k + 3], db + k * 128, k); \
        WG_COMMIT(); } while (0)
      uint8_t* const gp = g_part + (size_t)(b * 64 + c) * 8192 + lane_off;
#define W2_STORE(acc, s) do { \
        store_partial64(&acc[0], gp + ((c + 2 * (s) - 1) & 7) * 65536, tag); \
        store_partial64(&acc[32], gp + ((c + 2 * (s)) & 7) * 65536, tag); } while (0)
      W2_ISSUE(accA, 0);
      W2_ISSUE(accB, 1);
      WG_WAIT(1);
      reg_fence(accA);
      if (lane == 0) mbar_arrive_pair(BAR(B_W2E));
      {
        uint8_t* dst = g_p89 + (size_t)(bw * 8 + c) * 4096 + lane * 16;
        store_partial64(&accA[0], dst, tag);
        store_partial64(&accA[32], dst + 2048, tag);
      }
      STAMP(13);
      W2_ISSUE(accA, 2);
      WG_WAIT(1);
      reg_fence(accB);
      if (lane == 0) mbar_arrive(BAR(B_W2D));
      W2_STORE(accB, 1);
      W2_ISSUE(accB, 3);
      WG_WAIT(1);
      reg_fence(accA);
      if (lane == 0) mbar_arrive(BAR(B_W2D + 1));
      W2_STORE(accA, 2);
      float accR[32], accO[32];
      {
        mbar_wait(BAR(B_W2FULL + 4), 0);
        const uint64_t db = mkdesc(sb, HI);
        WG_FENCE();
#pragma unroll
        for (int k = 0; k < 14; k++) wg_rs64(accR, ha[4 * k], ha[4 * k + 1], ha[4 * k + 2], ha[4 * k + 3], db + k * 128, k);
        WG_COMMIT();
#pragma unroll
        for (int k = 0; k < 14; k++) wg_rs64(accO, ha[4 * k], ha[4 * k + 1], ha[4 * k + 2], ha[4 * k + 3], db + 1792 + k * 128, k);
        WG_COMMIT();
      }
      WG_WAIT(2);
      reg_fence(accB);
      W2_STORE(accB, 3);
      uint4 v[4];
      ld4(v, g_h + tile_off + c * 2048);
      WG_WAIT(1);
      reg_fence(accR);
      store_partial64(&accR[0], gp + ((c + 7) & 7) * 65536, tag);
      STAMP(14);
      WG_WAIT(0);
      reg_fence(accO);
      add4(accO, v);
      STAMP(15);
      const uint8_t* pp = g_part + (size_t)(b * 8 + c) * 65536 + lane_off;
#pragma unroll 1
      for (int u = 0; u < 7; u++) {
        if (u < 6) {
          const uint32_t z = sb + W2SLOT + u * 16384 + (u >= 3 ? 8192 : 0) + r * 8192 + lane_off;
          mbar_wait(BAR(B_PL + 2 * u + r), 0);
#pragma unroll
          for (int i = 0; i < 4; i++)
            asm volatile("ld.shared.v4.u32 {%0,%1,%2,%3}, [%4];" : "=r"(v[i].x), "=r"(v[i].y), "=r"(v[i].z), "=r"(v[i].w) : "r"(z + i * 512) : "memory");
        } else {
          STAMP(16);
          v[0].x = ~tag;
        }
        uint32_t n = 0;
        while (__any_sync(0xffffffffu, (((v[0].x ^ tag) | (v[1].x ^ tag) | (v[2].x ^ tag) | (v[3].x ^ tag)) & TAGM) != 0u) && ++n < SPIN_MAX)
          ld4(v, pp + ((c - 1 - u) & 7) * 8192);
        add4(accO, v);
      }
      uint8_t* op = reinterpret_cast<uint8_t*>(P.out) + (size_t)row_lo * 1280 + c * 128 + tq * 4;
#pragma unroll
      for (int t = 0; t < 8; t++) {
        *reinterpret_cast<uint32_t*>(op + t * 16) = pack2(accO[4 * t], accO[4 * t + 1]);
        *reinterpret_cast<uint32_t*>(op + 8 * 1280 + t * 16) = pack2(accO[4 * t + 2], accO[4 * t + 3]);
      }
      STAMP(17);
    }
  }
}

typedef CUresult (*EncodeFn)(CUtensorMap*, CUtensorMapDataType, cuuint32_t, void*, const cuuint64_t*, const cuuint64_t*, const cuuint32_t*,
                             const cuuint32_t*, CUtensorMapInterleave, CUtensorMapSwizzle, CUtensorMapL2promotion, CUtensorMapFloatOOBfill);

static void make_map(EncodeFn enc, CUtensorMap* m, const void* p, int nd, const cuuint64_t* dims, const cuuint64_t* strides, const cuuint32_t* box,
                     CUtensorMapSwizzle sw) {
  const cuuint32_t es[5] = {1, 1, 1, 1, 1};
  enc(m, CU_TENSOR_MAP_DATA_TYPE_BFLOAT16, (cuuint32_t)nd, const_cast<void*>(p), dims, strides, box, es, CU_TENSOR_MAP_INTERLEAVE_NONE, sw,
      CU_TENSOR_MAP_L2_PROMOTION_L2_128B, CU_TENSOR_MAP_FLOAT_OOB_FILL_NONE);
}

extern "C" void kernel_launch(void* const* d_in, const int* in_sizes, int n_in, void* d_out, int out_size) {
  (void)in_sizes; (void)n_in; (void)out_size;
  static EncodeFn enc = nullptr;
  if (!enc) {
    void* f = nullptr;
    cudaDriverEntryPointQueryResult qr;
    cudaGetDriverEntryPoint("cuTensorMapEncodeTiled", &f, cudaEnableDefault, &qr);
    enc = (EncodeFn)f;
    cudaFuncSetAttribute(fused_block_kernel, cudaFuncAttributeMaxDynamicSharedMemorySize, (int)SMEM_BYTES);
  }
  Params P;
  P.x = (const __nv_bfloat16*)d_in[0];
  P.wqkv = (const __nv_bfloat16*)d_in[1];
  P.wo = (const __nv_bfloat16*)d_in[2];
  P.w1 = (const __nv_bfloat16*)d_in[4];
  P.w2 = (const __nv_bfloat16*)d_in[5];
  P.out = (__nv_bfloat16*)d_out;
  { const cuuint64_t d[2] = {640, 2048}, s[1] = {1280}; const cuuint32_t b[2] = {64, 128}; make_map(enc, &P.mX, P.x, 2, d, s, b, CU_TENSOR_MAP_SWIZZLE_128B); }
  { const cuuint64_t d[4] = {32, 640, 20, 3}, s[3] = {3840, 64, 1280}; const cuuint32_t b[4] = {32, 32, 2, 3}; make_map(enc, &P.mWqM, P.wqkv, 4, d, s, b, CU_TENSOR_MAP_SWIZZLE_64B); }
  { const cuuint64_t d[4] = {16, 640, 40, 3}, s[3] = {3840, 32, 1280}; const cuuint32_t b[4] = {16, 32, 1, 3}; make_map(enc, &P.mWqL, P.wqkv, 4, d, s, b, CU_TENSOR_MAP_SWIZZLE_32B); }
  { const cuuint64_t d[3] = {16, 640, 40}, s[2] = {1280, 32}; const cuuint32_t b[3] = {16, 80, 5}; make_map(enc, &P.mWo, P.wo, 3, d, s, b, CU_TENSOR_MAP_SWIZZLE_32B); }
  { const cuuint64_t d[3] = {32, 640, 54}, s[2] = {3456, 64}; const cuuint32_t b[3] = {32, 80, 4}; make_map(enc, &P.mW1a, P.w1, 3, d, s, b, CU_TENSOR_MAP_SWIZZLE_64B); }
  { const cuuint64_t d[3] = {32, 640, 54}, s[2] = {3456, 64}; const cuuint32_t b[3] = {32, 80, 3}; make_map(enc, &P.mW1b, P.w1, 3, d, s, b, CU_TENSOR_MAP_SWIZZLE_64B); }
  { const cuuint64_t d[2] = {640, 1728}, s[1] = {1280}; const cuuint32_t b[2] = {64, 112}; make_map(enc, &P.mW2, P.w2, 2, d, s, b, CU_TENSOR_MAP_SWIZZLE_128B); }
  fused_block_kernel<<<SMIDMAP ? 132 : 128, 384, SMEM_BYTES, cudaStreamPerThread>>>(P);
}
```

```cpp
#include <cuda_runtime.h>
#include <cuda.h>
#include <cuda_bf16.h>
#include <stdint.h>

#define PROF 0
#define STATKT 3
#define EXP1 3
#define SMIDMAP 0

__device__ __align__(1024) uint8_t g_kv[32 * 8 * 22528];
__device__ __align__(1024) uint8_t g_o[32 * 4 * 8 * 2560];
__device__ __align__(1024) uint8_t g_h[32 * 4 * 8 * 2560];
__device__ __align__(1024) float2 g_hstat[32 * 4 * 8 * 16];
__device__ __align__(1024) uint8_t g_part[32 * 8 * 8 * 8192];
__device__ __align__(1024) uint8_t g_p89[32 * 4 * 8 * 4096];
__device__ __align__(128) float2 g_xstat[2048];
__device__ __align__(128) float g_csq[16 * 8 * 240];
__device__ __align__(128) float g_cs1[16 * 8 * 224];
__device__ __align__(128) uint32_t g_epoch[128];
#define STAMP(slot)
#define STAMPW(slot)

struct Params {
  CUtensorMap mX, mWqM, mWqL, mWo, mW1a, mW1b, mW2;
  const __nv_bfloat16 *x, *wqkv, *wo, *w1, *w2;
  __nv_bfloat16* out;
};

constexpr uint32_t QST = 47104;
constexpr uint32_t KVB = 22528;
constexpr uint32_t OFF_WOB = 0;
constexpr uint32_t OFF_PRE = 188416;
constexpr uint32_t W2SLOT = 57344;
constexpr uint32_t OFF_MISC = 229376;
constexpr uint32_t OFF_CS = OFF_MISC + 512;
constexpr uint32_t OFF_XS = OFF_CS + 960;
constexpr uint32_t SMEM_BYTES = 232448;

enum {
  B_QFULL = 0, B_KVFULL = 4, B_KVLAND = 8, B_WOB = 12, B_WOB7 = 13, B_BFULL = 14, B_W2FULL = 22, B_PL = 27, B_CS1 = 39,
  B_KVOWN = 40,
  B_Q23 = 42, B_PRE = 43, B_STAT = 44, B_W2D = 45,
  B_QEMPTY = 47, B_ATTP = 51, B_WODP = 52, B_BEMPTY = 53, B_W2E = 61,
  NBAR = 62
};
constexpr uint32_t TAGM = 0x00010001u;
constexpr uint32_t SPIN_MAX = 1u << 18;

__device__ __forceinline__ uint32_t s2u(const void* p) { return (uint32_t)__cvta_generic_to_shared(p); }
__device__ __forceinline__ void mbar_init(uint32_t b, int c) { asm volatile("mbarrier.init.shared::cta.b64 [%0], %1;" ::"r"(b), "r"(c)); }
__device__ __forceinline__ void mbar_expect(uint32_t b, int bytes) { asm volatile("mbarrier.arrive.expect_tx.shared::cta.b64 _, [%0], %1;" ::"r"(b), "r"(bytes) : "memory"); }
__device__ __forceinline__ void mbar_arrive(uint32_t b) { asm volatile("mbarrier.arrive.shared::cta.b64 _, [%0];" ::"r"(b) : "memory"); }
__device__ __forceinline__ void mbar_arrive_pair(uint32_t b) {
  asm volatile("{\n.reg .b32 r;\nmapa.shared::cluster.u32 r, %0, 0;\nmbarrier.arrive.shared::cluster.b64 _, [r];\n"
               "mapa.shared::cluster.u32 r, %0, 1;\nmbarrier.arrive.shared::cluster.b64 _, [r];\n}" ::"r"(b) : "memory");
}
__device__ __forceinline__ void mbar_wait(uint32_t b, uint32_t ph) {
  asm volatile("{\n.reg .pred p;\n.reg .u32 n;\nmov.u32 n, 0;\nW%=:\nmbarrier.try_wait.parity.shared::cta.b64 p, [%0], %1;\n"
               "add.u32 n, n, 1;\nsetp.lt.and.u32 p, n, 0x100000, !p;\n@p bra W%=;\n}" ::"r"(b), "r"(ph) : "memory");
}
__device__ __forceinline__ void tma2d(uint32_t dst, const CUtensorMap* m, int c0, int c1, uint32_t bar) {
  asm volatile("cp.async.bulk.tensor.2d.shared::cluster.global.mbarrier::complete_tx::bytes [%0], [%1, {%3, %4}], [%2];" ::"r"(dst), "l"(m), "r"(bar), "r"(c0), "r"(c1) : "memory");
}
__device__ __forceinline__ void tma2d_mc(uint32_t dst, const CUtensorMap* m, int c0, int c1, uint32_t bar) {
  asm volatile("cp.async.bulk.tensor.2d.shared::cluster.global.mbarrier::complete_tx::bytes.multicast::cluster [%0], [%1, {%3, %4}], [%2], %5;" ::"r"(dst), "l"(m), "r"(bar), "r"(c0), "r"(c1), "h"((uint16_t)3) : "memory");
}
__device__ __forceinline__ void tma3d_mc(uint32_t dst, const CUtensorMap* m, int c0, int c1, int c2, uint32_t bar) {
  asm volatile("cp.async.bulk.tensor.3d.shared::cluster.global.mbarrier::complete_tx::bytes.multicast::cluster [%0], [%1, {%3, %4, %5}], [%2], %6;" ::"r"(dst), "l"(m), "r"(bar), "r"(c0), "r"(c1), "r"(c2), "h"((uint16_t)3) : "memory");
}
__device__ __forceinline__ void tma4d_mc(uint32_t dst, const CUtensorMap* m, int c0, int c1, int c2, int c3, uint32_t bar) {
  asm volatile("cp.async.bulk.tensor.4d.shared::cluster.global.mbarrier::complete_tx::bytes.multicast::cluster [%0], [%1, {%3, %4, %5, %6}], [%2], %7;" ::"r"(dst), "l"(m), "r"(bar), "r"(c0), "r"(c1), "r"(c2), "r"(c3), "h"((uint16_t)3) : "memory");
}
__device__ __forceinline__ void bulk_load(uint32_t dst, const void* src, int bytes, uint32_t bar) {
  asm volatile("cp.async.bulk.shared::cluster.global.mbarrier::complete_tx::bytes [%0], [%1], %2, [%3];" ::"r"(dst), "l"(src), "r"(bytes), "r"(bar) : "memory");
}
__device__ __forceinline__ void tma4d_pf(const CUtensorMap* m, int c0, int c1, int c2, int c3) {
  asm volatile("cp.async.bulk.prefetch.tensor.4d.L2.global [%0, {%1, %2, %3, %4}];" ::"l"(m), "r"(c0), "r"(c1), "r"(c2), "r"(c3) : "memory");
}
__device__ __forceinline__ void l2_prefetch_bulk(const void* p, int bytes) { asm volatile("cp.async.bulk.prefetch.L2.global [%0], %1;" ::"l"(p), "r"(bytes) : "memory"); }
__device__ __forceinline__ void l2_prefetch(const void* p) { asm volatile("prefetch.global.L2 [%0];" ::"l"(p)); }
__device__ __forceinline__ uint32_t ld_flag(const uint32_t* p) { uint32_t v; asm volatile("ld.acquire.gpu.global.u32 %0, [%1];" : "=r"(v) : "l"(p) : "memory"); return v; }
__device__ __forceinline__ void st_flag(uint32_t* p, uint32_t v) { asm volatile("st.relaxed.gpu.global.u32 [%0], %1;" ::"l"(p), "r"(v) : "memory"); }
__device__ __forceinline__ void fence_gpu() { asm volatile("fence.acq_rel.gpu;" ::: "memory"); }
__device__ __forceinline__ void fence_async_smem() { asm volatile("fence.proxy.async.shared::cta;" ::: "memory"); }
__device__ __forceinline__ void fence_async_glob() { asm volatile("fence.proxy.async.global;" ::: "memory"); }
__device__ __forceinline__ uint4 ldcg128(const void* p) { uint4 v; asm volatile("ld.relaxed.gpu.global.v4.u32 {%0,%1,%2,%3}, [%4];" : "=r"(v.x), "=r"(v.y), "=r"(v.z), "=r"(v.w) : "l"(p) : "memory"); return v; }
__device__ __forceinline__ uint4 ldnc128(const void* p) { uint4 v; asm volatile("ld.global.nc.v4.u32 {%0,%1,%2,%3}, [%4];" : "=r"(v.x), "=r"(v.y), "=r"(v.z), "=r"(v.w) : "l"(p)); return v; }
__device__ __forceinline__ uint32_t ldnc32(const void* p) { uint32_t v; asm volatile("ld.global.nc.u32 %0, [%1];" : "=r"(v) : "l"(p)); return v; }
__device__ __forceinline__ uint2 ldcg64(const void* p) { uint2 v; asm volatile("ld.relaxed.gpu.global.v2.u32 {%0,%1}, [%2];" : "=r"(v.x), "=r"(v.y) : "l"(p) : "memory"); return v; }
__device__ __forceinline__ uint32_t ldcg32(const void* p) { uint32_t v; asm volatile("ld.relaxed.gpu.global.u32 %0, [%1];" : "=r"(v) : "l"(p) : "memory"); return v; }
__device__ __forceinline__ uint32_t pack2(float lo, float hi) { uint32_t r; asm("cvt.rn.bf16x2.f32 %0, %1, %2;" : "=r"(r) : "f"(hi), "f"(lo)); return r; }
__device__ __forceinline__ float bf_lo(uint32_t v) { return __uint_as_float(v << 16); }
__device__ __forceinline__ float bf_hi(uint32_t v) { return __uint_as_float(v & 0xffff0000u); }
__device__ __forceinline__ float ex2(float x) { float y; asm("ex2.approx.ftz.f32 %0, %1;" : "=f"(y) : "f"(x)); return y; }
__device__ __forceinline__ float rcp(float x) { float y; asm("rcp.approx.ftz.f32 %0, %1;" : "=f"(y) : "f"(x)); return y; }
__device__ __forceinline__ float tanh_fast(float x) { float y; asm("tanh.approx.f32 %0, %1;" : "=f"(y) : "f"(x)); return y; }
__device__ __forceinline__ void stsm4(uint32_t a, uint32_t r0, uint32_t r1, uint32_t r2, uint32_t r3) {
  asm volatile("stmatrix.sync.aligned.m8n8.x4.shared.b16 [%0], {%1,%2,%3,%4};" ::"r"(a), "r"(r0), "r"(r1), "r"(r2), "r"(r3) : "memory");
}
__device__ __forceinline__ float2 lds64f(uint32_t a) { float2 v; asm volatile("ld.shared.v2.f32 {%0,%1}, [%2];" : "=f"(v.x), "=f"(v.y) : "r"(a)); return v; }
__device__ __forceinline__ constexpr uint64_t desc_hi(uint32_t lbo, uint32_t sbo, uint32_t sw) {
  return ((uint64_t)(lbo >> 4) << 16) | ((uint64_t)(sbo >> 4) << 32) | ((uint64_t)sw << 62);
}
__device__ __forceinline__ uint64_t mkdesc(uint32_t addr, uint64_t hi) { return hi | (uint64_t)((addr & 0x3FFFF) >> 4); }
#define WG_FENCE() asm volatile("wgmma.fence.sync.aligned;" ::: "memory")
#define WG_COMMIT() asm volatile("wgmma.commit_group.sync.aligned;" ::: "memory")
#define WG_WAIT(n) asm volatile("wgmma.wait_group.sync.aligned " #n ";" ::: "memory")
template <int N> __device__ __forceinline__ void reg_fence(float (&a)[N]) {
#pragma unroll
  for (int i = 0; i < N; i++) asm volatile("" : "+f"(a[i])::"memory");
}

__device__ __forceinline__ void wg_ss192(float (&d)[96], uint64_t da, uint64_t db, int sd) {
  asm volatile("{\n.reg .pred p;\nsetp.ne.b32 p, %98, 0;\n"
  "wgmma.mma_async.sync.aligned.m64n192k16.f32.bf16.bf16 {%0, %1, %2, %3, %4, %5, %6, %7, %8, %9, %10, %11, %12, %13, %14, %15, %16, %17, %18, %19, %20, %21, %22, %23, %24, %25, %26, %27, %28, %29, %30, %31, %32, %33, %34, %35, %36, %37, %38, %39, %40, %41, %42, %43, %44, %45, %46, %47, %48, %49, %50, %51, %52, %53, %54, %55, %56, %57, %58, %59, %60, %61, %62, %63, %64, %65, %66, %67, %68, %69, %70, %71, %72, %73, %74, %75, %76, %77, %78, %79, %80, %81, %82, %83, %84, %85, %86, %87, %88, %89, %90, %91, %92, %93, %94, %95}, %96, %97, p, 1, 1, 0, 1;\n}\n"
  : "+f"(d[0]), "+f"(d[1]), "+f"(d[2]), "+f"(d[3]), "+f"(d[4]), "+f"(d[5]), "+f"(d[6]), "+f"(d[7]), "+f"(d[8]), "+f"(d[9]), "+f"(d[10]), "+f"(d[11]), "+f"(d[12]), "+f"(d[13]), "+f"(d[14]), "+f"(d[15]), "+f"(d[16]), "+f"(d[17]), "+f"(d[18]), "+f"(d[19]), "+f"(d[20]), "+f"(d[21]), "+f"(d[22]), "+f"(d[23]), "+f"(d[24]), "+f"(d[25]), "+f"(d[26]), "+f"(d[27]), "+f"(d[28]), "+f"(d[29]), "+f"(d[30]), "+f"(d[31]), "+f"(d[32]), "+f"(d[33]), "+f"(d[34]), "+f"(d[35]), "+f"(d[36]), "+f"(d[37]), "+f"(d[38]), "+f"(d[39]), "+f"(d[40]), "+f"(d[41]), "+f"(d[42]), "+f"(d[43]), "+f"(d[44]), "+f"(d[45]), "+f"(d[46]), "+f"(d[47]), "+f"(d[48]), "+f"(d[49]), "+f"(d[50]), "+f"(d[51]), "+f"(d[52]), "+f"(d[53]), "+f"(d[54]), "+f"(d[55]), "+f"(d[56]), "+f"(d[57]), "+f"(d[58]), "+f"(d[59]), "+f"(d[60]), "+f"(d[61]), "+f"(d[62]), "+f"(d[63]), "+f"(d[64]), "+f"(d[65]), "+f"(d[66]), "+f"(d[67]), "+f"(d[68]), "+f"(d[69]), "+f"(d[70]), "+f"(d[71]), "+f"(d[72]), "+f"(d[73]), "+f"(d[74]), "+f"(d[75]), "+f"(d[76]), "+f"(d[77]), "+f"(d[78]), "+f"(d[79]), "+f"(d[80]), "+f"(d[81]), "+f"(d[82]), "+f"(d[83]), "+f"(d[84]), "+f"(d[85]), "+f"(d[86]), "+f"(d[87]), "+f"(d[88]), "+f"(d[89]), "+f"(d[90]), "+f"(d[91]), "+f"(d[92]), "+f"(d[93]), "+f"(d[94]), "+f"(d[95]) : "l"(da), "l"(db), "r"(sd));
}
__device__ __forceinline__ void wg_ss48(float (&d)[24], uint64_t da, uint64_t db, int sd) {
  asm volatile("{\n.reg .pred p;\nsetp.ne.b32 p, %26, 0;\n"
  "wgmma.mma_async.sync.aligned.m64n48k16.f32.bf16.bf16 {%0, %1, %2, %3, %4, %5, %6, %7, %8, %9, %10, %11, %12, %13, %14, %15, %16, %17, %18, %19, %20, %21, %22, %23}, %24, %25, p, 1, 1, 0, 1;\n}\n"
  : "+f"(d[0]), "+f"(d[1]), "+f"(d[2]), "+f"(d[3]), "+f"(d[4]), "+f"(d[5]), "+f"(d[6]), "+f"(d[7]), "+f"(d[8]), "+f"(d[9]), "+f"(d[10]), "+f"(d[11]), "+f"(d[12]), "+f"(d[13]), "+f"(d[14]), "+f"(d[15]), "+f"(d[16]), "+f"(d[17]), "+f"(d[18]), "+f"(d[19]), "+f"(d[20]), "+f"(d[21]), "+f"(d[22]), "+f"(d[23]) : "l"(da), "l"(db), "r"(sd));
}
__device__ __forceinline__ void wg_rs80(float (&d)[40], uint32_t a0, uint32_t a1, uint32_t a2, uint32_t a3, uint64_t db, int sd) {
  asm volatile("{\n.reg .pred p;\nsetp.ne.b32 p, %45, 0;\n"
  "wgmma.mma_async.sync.aligned.m64n80k16.f32.bf16.bf16 {%0, %1, %2, %3, %4, %5, %6, %7, %8, %9, %10, %11, %12, %13, %14, %15, %16, %17, %18, %19, %20, %21, %22, %23, %24, %25, %26, %27, %28, %29, %30, %31, %32, %33, %34, %35, %36, %37, %38, %39}, {%40, %41, %42, %43}, %44, p, 1, 1, 1;\n}\n"
  : "+f"(d[0]), "+f"(d[1]), "+f"(d[2]), "+f"(d[3]), "+f"(d[4]), "+f"(d[5]), "+f"(d[6]), "+f"(d[7]), "+f"(d[8]), "+f"(d[9]), "+f"(d[10]), "+f"(d[11]), "+f"(d[12]), "+f"(d[13]), "+f"(d[14]), "+f"(d[15]), "+f"(d[16]), "+f"(d[17]), "+f"(d[18]), "+f"(d[19]), "+f"(d[20]), "+f"(d[21]), "+f"(d[22]), "+f"(d[23]), "+f"(d[24]), "+f"(d[25]), "+f"(d[26]), "+f"(d[27]), "+f"(d[28]), "+f"(d[29]), "+f"(d[30]), "+f"(d[31]), "+f"(d[32]), "+f"(d[33]), "+f"(d[34]), "+f"(d[35]), "+f"(d[36]), "+f"(d[37]), "+f"(d[38]), "+f"(d[39]) : "r"(a0), "r"(a1), "r"(a2), "r"(a3), "l"(db), "r"(sd));
}
__device__ __forceinline__ void wg_rs224(float (&d)[112], uint32_t a0, uint32_t a1, uint32_t a2, uint32_t a3, uint64_t db, int sd) {
  asm volatile("{\n.reg .pred p;\nsetp.ne.b32 p, %117, 0;\n"
  "wgmma.mma_async.sync.aligned.m64n224k16.f32.bf16.bf16 {%0, %1, %2, %3, %4, %5, %6, %7, %8, %9, %10, %11, %12, %13, %14, %15, %16, %17, %18, %19, %20, %21, %22, %23, %24, %25, %26, %27, %28, %29, %30, %31, %32, %33, %34, %35, %36, %37, %38, %39, %40, %41, %42, %43, %44, %45, %46, %47, %48, %49, %50, %51, %52, %53, %54, %55, %56, %57, %58, %59, %60, %61, %62, %63, %64, %65, %66, %67, %68, %69, %70, %71, %72, %73, %74, %75, %76, %77, %78, %79, %80, %81, %82, %83, %84, %85, %86, %87, %88, %89, %90, %91, %92, %93, %94, %95, %96, %97, %98, %99, %100, %101, %102, %103, %104, %105, %106, %107, %108, %109, %110, %111}, {%112, %113, %114, %115}, %116, p, 1, 1, 1;\n}\n"
  : "+f"(d[0]), "+f"(d[1]), "+f"(d[2]), "+f"(d[3]), "+f"(d[4]), "+f"(d[5]), "+f"(d[6]), "+f"(d[7]), "+f"(d[8]), "+f"(d[9]), "+f"(d[10]), "+f"(d[11]), "+f"(d[12]), "+f"(d[13]), "+f"(d[14]), "+f"(d[15]), "+f"(d[16]), "+f"(d[17]), "+f"(d[18]), "+f"(d[19]), "+f"(d[20]), "+f"(d[21]), "+f"(d[22]), "+f"(d[23]), "+f"(d[24]), "+f"(d[25]), "+f"(d[26]), "+f"(d[27]), "+f"(d[28]), "+f"(d[29]), "+f"(d[30]), "+f"(d[31]), "+f"(d[32]), "+f"(d[33]), "+f"(d[34]), "+f"(d[35]), "+f"(d[36]), "+f"(d[37]), "+f"(d[38]), "+f"(d[39]), "+f"(d[40]), "+f"(d[41]), "+f"(d[42]), "+f"(d[43]), "+f"(d[44]), "+f"(d[45]), "+f"(d[46]), "+f"(d[47]), "+f"(d[48]), "+f"(d[49]), "+f"(d[50]), "+f"(d[51]), "+f"(d[52]), "+f"(d[53]), "+f"(d[54]), "+f"(d[55]), "+f"(d[56]), "+f"(d[57]), "+f"(d[58]), "+f"(d[59]), "+f"(d[60]), "+f"(d[61]), "+f"(d[62]), "+f"(d[63]), "+f"(d[64]), "+f"(d[65]), "+f"(d[66]), "+f"(d[67]), "+f"(d[68]), "+f"(d[69]), "+f"(d[70]), "+f"(d[71]), "+f"(d[72]), "+f"(d[73]), "+f"(d[74]), "+f"(d[75]), "+f"(d[76]), "+f"(d[77]), "+f"(d[78]), "+f"(d[79]), "+f"(d[80]), "+f"(d[81]), "+f"(d[82]), "+f"(d[83]), "+f"(d[84]), "+f"(d[85]), "+f"(d[86]), "+f"(d[87]), "+f"(d[88]), "+f"(d[89]), "+f"(d[90]), "+f"(d[91]), "+f"(d[92]), "+f"(d[93]), "+f"(d[94]), "+f"(d[95]), "+f"(d[96]), "+f"(d[97]), "+f"(d[98]), "+f"(d[99]), "+f"(d[100]), "+f"(d[101]), "+f"(d[102]), "+f"(d[103]), "+f"(d[104]), "+f"(d[105]), "+f"(d[106]), "+f"(d[107]), "+f"(d[108]), "+f"(d[109]), "+f"(d[110]), "+f"(d[111]) : "r"(a0), "r"(a1), "r"(a2), "r"(a3), "l"(db), "r"(sd));
}
__device__ __forceinline__ void wg_rs64k(float (&d)[32], uint32_t a0, uint32_t a1, uint32_t a2, uint32_t a3, uint64_t db, int sd) {
  asm volatile("{\n.reg .pred p;\nsetp.ne.b32 p, %37, 0;\n"
  "wgmma.mma_async.sync.aligned.m64n64k16.f32.bf16.bf16 {%0, %1, %2, %3, %4, %5, %6, %7, %8, %9, %10, %11, %12, %13, %14, %15, %16, %17, %18, %19, %20, %21, %22, %23, %24, %25, %26, %27, %28, %29, %30, %31}, {%32, %33, %34, %35}, %36, p, 1, 1, 0;\n}\n"
  : "+f"(d[0]), "+f"(d[1]), "+f"(d[2]), "+f"(d[3]), "+f"(d[4]), "+f"(d[5]), "+f"(d[6]), "+f"(d[7]), "+f"(d[8]), "+f"(d[9]), "+f"(d[10]), "+f"(d[11]), "+f"(d[12]), "+f"(d[13]), "+f"(d[14]), "+f"(d[15]), "+f"(d[16]), "+f"(d[17]), "+f"(d[18]), "+f"(d[19]), "+f"(d[20]), "+f"(d[21]), "+f"(d[22]), "+f"(d[23]), "+f"(d[24]), "+f"(d[25]), "+f"(d[26]), "+f"(d[27]), "+f"(d[28]), "+f"(d[29]), "+f"(d[30]), "+f"(d[31]) : "r"(a0), "r"(a1), "r"(a2), "r"(a3), "l"(db), "r"(sd));
}
__device__ __forceinline__ void wg_rs24(float (&d)[12], uint32_t a0, uint32_t a1, uint32_t a2, uint32_t a3, uint64_t db, int sd) {
  asm volatile("{\n.reg .pred p;\nsetp.ne.b32 p, %17, 0;\n"
  "wgmma.mma_async.sync.aligned.m64n24k16.f32.bf16.bf16 {%0, %1, %2, %3, %4, %5, %6, %7, %8, %9, %10, %11}, {%12, %13, %14, %15}, %16, p, 1, 1, 1;\n}\n"
  : "+f"(d[0]), "+f"(d[1]), "+f"(d[2]), "+f"(d[3]), "+f"(d[4]), "+f"(d[5]), "+f"(d[6]), "+f"(d[7]), "+f"(d[8]), "+f"(d[9]), "+f"(d[10]), "+f"(d[11]) : "r"(a0), "r"(a1), "r"(a2), "r"(a3), "l"(db), "r"(sd));
}
__device__ __forceinline__ void wg_rs128(float (&d)[64], uint32_t a0, uint32_t a1, uint32_t a2, uint32_t a3, uint64_t db, int sd) {
  asm volatile("{\n.reg .pred p;\nsetp.ne.b32 p, %69, 0;\n"
  "wgmma.mma_async.sync.aligned.m64n128k16.f32.bf16.bf16 {%0, %1, %2, %3, %4, %5, %6, %7, %8, %9, %10, %11, %12, %13, %14, %15, %16, %17, %18, %19, %20, %21, %22, %23, %24, %25, %26, %27, %28, %29, %30, %31, %32, %33, %34, %35, %36, %37, %38, %39, %40, %41, %42, %43, %44, %45, %46, %47, %48, %49, %50, %51, %52, %53, %54, %55, %56, %57, %58, %59, %60, %61, %62, %63}, {%64, %65, %66, %67}, %68, p, 1, 1, 1;\n}\n"
  : "+f"(d[0]), "+f"(d[1]), "+f"(d[2]), "+f"(d[3]), "+f"(d[4]), "+f"(d[5]), "+f"(d[6]), "+f"(d[7]), "+f"(d[8]), "+f"(d[9]), "+f"(d[10]), "+f"(d[11]), "+f"(d[12]), "+f"(d[13]), "+f"(d[14]), "+f"(d[15]), "+f"(d[16]), "+f"(d[17]), "+f"(d[18]), "+f"(d[19]), "+f"(d[20]), "+f"(d[21]), "+f"(d[22]), "+f"(d[23]), "+f"(d[24]), "+f"(d[25]), "+f"(d[26]), "+f"(d[27]), "+f"(d[28]), "+f"(d[29]), "+f"(d[30]), "+f"(d[31]), "+f"(d[32]), "+f"(d[33]), "+f"(d[34]), "+f"(d[35]), "+f"(d[36]), "+f"(d[37]), "+f"(d[38]), "+f"(d[39]), "+f"(d[40]), "+f"(d[41]), "+f"(d[42]), "+f"(d[43]), "+f"(d[44]), "+f"(d[45]), "+f"(d[46]), "+f"(d[47]), "+f"(d[48]), "+f"(d[49]), "+f"(d[50]), "+f"(d[51]), "+f"(d[52]), "+f"(d[53]), "+f"(d[54]), "+f"(d[55]), "+f"(d[56]), "+f"(d[57]), "+f"(d[58]), "+f"(d[59]), "+f"(d[60]), "+f"(d[61]), "+f"(d[62]), "+f"(d[63]) : "r"(a0), "r"(a1), "r"(a2), "r"(a3), "l"(db), "r"(sd));
}
__device__ __forceinline__ void wg_rs64(float (&d)[32], uint32_t a0, uint32_t a1, uint32_t a2, uint32_t a3, uint64_t db, int sd) {
  asm volatile("{\n.reg .pred p;\nsetp.ne.b32 p, %37, 0;\n"
  "wgmma.mma_async.sync.aligned.m64n64k16.f32.bf16.bf16 {%0, %1, %2, %3, %4, %5, %6, %7, %8, %9, %10, %11, %12, %13, %14, %15, %16, %17, %18, %19, %20, %21, %22, %23, %24, %25, %26, %27, %28, %29, %30, %31}, {%32, %33, %34, %35}, %36, p, 1, 1, 1;\n}\n"
  : "+f"(d[0]), "+f"(d[1]), "+f"(d[2]), "+f"(d[3]), "+f"(d[4]), "+f"(d[5]), "+f"(d[6]), "+f"(d[7]), "+f"(d[8]), "+f"(d[9]), "+f"(d[10]), "+f"(d[11]), "+f"(d[12]), "+f"(d[13]), "+f"(d[14]), "+f"(d[15]), "+f"(d[16]), "+f"(d[17]), "+f"(d[18]), "+f"(d[19]), "+f"(d[20]), "+f"(d[21]), "+f"(d[22]), "+f"(d[23]), "+f"(d[24]), "+f"(d[25]), "+f"(d[26]), "+f"(d[27]), "+f"(d[28]), "+f"(d[29]), "+f"(d[30]), "+f"(d[31]) : "r"(a0), "r"(a1), "r"(a2), "r"(a3), "l"(db), "r"(sd));
}

__device__ __forceinline__ uint32_t kv_addr(int i) {
  return 94208u + KVB * (uint32_t)((0x541032u >> (4 * i)) & 15u);
}
__device__ __forceinline__ uint32_t w1b_addr(int s) {
  return (s == 3 || s == 4) ? (uint32_t)(s - 3) * 35840u : 102400u + (uint32_t)(s >= 5 ? s - 5 : s) * 35840u;
}
__device__ __forceinline__ void stg128(void* p, uint32_t a, uint32_t b, uint32_t c, uint32_t d) {
  asm volatile("st.global.v4.u32 [%0], {%1,%2,%3,%4};" ::"l"(p), "r"(a), "r"(b), "r"(c), "r"(d) : "memory");
}
__device__ __forceinline__ void stg32(void* p, uint32_t a) { asm volatile("st.global.u32 [%0], %1;" ::"l"(p), "r"(a) : "memory"); }
__device__ __forceinline__ void ld_tile(uint32_t (&a)[20], const uint8_t* p) {
#pragma unroll
  for (int k = 0; k < 5; k++)
    asm volatile("ld.relaxed.gpu.global.v4.u32 {%0,%1,%2,%3}, [%4];" : "=r"(a[4 * k]), "=r"(a[4 * k + 1]), "=r"(a[4 * k + 2]), "=r"(a[4 * k + 3]) : "l"(p + k * 512) : "memory");
}
__device__ __forceinline__ uint32_t tag16(uint32_t v, uint32_t tag) { return (v & ~TAGM) | tag; }
__device__ __forceinline__ float tag32(float v, uint32_t ep) { return __uint_as_float((__float_as_uint(v) & ~3u) | ep); }
__device__ __forceinline__ void fix_tile(uint32_t (&a)[20], const uint8_t* p, uint32_t tag) {
  uint32_t n = 0;
  while (__any_sync(0xffffffffu, (((a[0] ^ tag) | (a[4] ^ tag) | (a[8] ^ tag) | (a[12] ^ tag) | (a[16] ^ tag)) & TAGM) != 0u) && ++n < SPIN_MAX) ld_tile(a, p);
}
__device__ __forceinline__ void probe_wait(uint32_t& ready, int i, const void* p, uint32_t tag) {
  uint32_t n = 0;
  while (!((ready >> i) & 1u) && ++n < SPIN_MAX) ready = __ballot_sync(0xffffffffu, ((ldcg32(p) ^ tag) & TAGM) == 0u);
}
__device__ __forceinline__ float gather16(const float* p, int stride, uint32_t ep) {
  uint32_t v[16], n = 0;
  while (true) {
    uint32_t bad = 0;
#pragma unroll
    for (int i = 0; i < 16; i++) v[i] = ldcg32(p + i * stride);
#pragma unroll
    for (int i = 0; i < 16; i++) bad |= v[i] ^ ep;
    if (!__any_sync(0xffffffffu, (bad & 3u) != 0u) || ++n >= SPIN_MAX) break;
  }
  float s = 0.f;
#pragma unroll
  for (int i = 0; i < 16; i++) s += __uint_as_float(v[i]);
  return s;
}
__device__ __forceinline__ void ld4(uint4 (&v)[4], const uint8_t* p) {
#pragma unroll
  for (int i = 0; i < 4; i++) v[i] = ldcg128(p + i * 512);
}
__device__ __forceinline__ void add4(float (&acc)[32], const uint4 (&v)[4]) {
#pragma unroll
  for (int i = 0; i < 4; i++) {
    acc[8 * i + 0] += bf_lo(v[i].x); acc[8 * i + 1] += bf_hi(v[i].x); acc[8 * i + 2] += bf_lo(v[i].y); acc[8 * i + 3] += bf_hi(v[i].y);
    acc[8 * i + 4] += bf_lo(v[i].z); acc[8 * i + 5] += bf_hi(v[i].z); acc[8 * i + 6] += bf_lo(v[i].w); acc[8 * i + 7] += bf_hi(v[i].w);
  }
}

__device__ __forceinline__ uint64_t desc2(uint32_t lo, uint32_t hi) { uint64_t d; asm("mov.b64 %0, {%1, %2};" : "=l"(d) : "r"(lo), "r"(hi)); return d; }
template <int H>
__device__ __forceinline__ void qk_issue(float (&s)[32], const uint32_t (&q)[24], uint32_t kd) {
  constexpr int J0 = (H == 0) ? 0 : (H == 1) ? 2 : (H == 2) ? 5 : 7;
  wg_rs64k(s, q[H * 6 + 0], q[H * 6 + 1], q[H * 6 + 2], q[H * 6 + 3], desc2(kd + (0x400000u + J0 * 64), 8u), 0);
  wg_rs64k(s, q[H * 6 + 4], q[H * 6 + 5], 0u, 0u, desc2(kd + (0x400000u + (J0 + 2) * 64), 8u), 1);
}
template <int H>
__device__ __forceinline__ void pv_issue(float (&o)[12], const uint32_t (&p)[16], uint32_t kd) {
#pragma unroll
  for (int i = 0; i < 4; i++)
    wg_rs24(o, p[4 * i], p[4 * i + 1], p[4 * i + 2], p[4 * i + 3], desc2(kd + (0x80000u + 640 + 3 * H * 64 + i * 16), 64u), 1);
}
__device__ __forceinline__ void sm_mask(float (&s)[32], int mode, int dthr) {
  if (mode) {
    asm volatile("" : "+r"(dthr));
#pragma unroll
    for (int t = 0; t < 8; t++) {
      s[4 * t + 0] = ((8 * t + 0 <= dthr) != (mode == 2)) ? s[4 * t + 0] : -INFINITY;
      s[4 * t + 1] = ((8 * t + 1 <= dthr) != (mode == 2)) ? s[4 * t + 1] : -INFINITY;
      s[4 * t + 2] = ((8 * t - 8 <= dthr) != (mode == 2)) ? s[4 * t + 2] : -INFINITY;
      s[4 * t + 3] = ((8 * t - 7 <= dthr) != (mode == 2)) ? s[4 * t + 3] : -INFINITY;
    }
  }
}
__device__ __forceinline__ void sm_max(float (&s)[32], float (&m)[2], float (&d)[2]) {
  float a0 = fmaxf(s[0], s[1]), a1 = fmaxf(s[2], s[3]), b0 = fmaxf(s[4], s[5]), b1 = fmaxf(s[6], s[7]);
#pragma unroll
  for (int t = 2; t < 8; t += 2) {
    a0 = fmaxf(a0, fmaxf(s[4 * t], s[4 * t + 1]));
    a1 = fmaxf(a1, fmaxf(s[4 * t + 2], s[4 * t + 3]));
    b0 = fmaxf(b0, fmaxf(s[4 * t + 4], s[4 * t + 5]));
    b1 = fmaxf(b1, fmaxf(s[4 * t + 6], s[4 * t + 7]));
  }
  a0 = fmaxf(a0, b0);
  a1 = fmaxf(a1, b1);
  a0 = fmaxf(a0, __shfl_xor_sync(0xffffffffu, a0, 1));
  a1 = fmaxf(a1, __shfl_xor_sync(0xffffffffu, a1, 1));
  a0 = fmaxf(a0, __shfl_xor_sync(0xffffffffu, a0, 2));
  a1 = fmaxf(a1, __shfl_xor_sync(0xffffffffu, a1, 2));
  const float n0 = fmaxf(m[0], a0), n1 = fmaxf(m[1], a1);
  d[0] = m[0] - n0;
  d[1] = m[1] - n1;
  m[0] = n0;
  m[1] = n1;
#pragma unroll
  for (int t = 0; t < 8; t++) { s[4 * t] -= n0; s[4 * t + 1] -= n0; s[4 * t + 2] -= n1; s[4 * t + 3] -= n1; }
}
template <int T0, int T1>
__device__ __forceinline__ void sm_exp(const float (&s)[32], uint32_t (&p)[16]) {
#pragma unroll
  for (int t = T0; t < T1; t++) {
    p[2 * t] = pack2(ex2(s[4 * t]), ex2(s[4 * t + 1]));
    p[2 * t + 1] = pack2(ex2(s[4 * t + 2]), ex2(s[4 * t + 3]));
  }
}
__device__ __forceinline__ void sm_step(const float (&s)[32], uint32_t (&p)[16], float (&o)[12], float (&d)[2], float (&sn)[32], float (&mn)[2], int mode, int dthr) {
  WG_WAIT(2);
  reg_fence(o);
  const float al0 = ex2(d[0]), al1 = ex2(d[1]);
  sm_exp<0, EXP1>(s, p);
#pragma unroll
  for (int t = 0; t < 3; t++) { o[4 * t] *= al0; o[4 * t + 1] *= al0; o[4 * t + 2] *= al1; o[4 * t + 3] *= al1; }
#pragma unroll
  for (int i = 0; i < 2 * EXP1; i++) asm volatile("" : "+r"(p[i]));
  WG_WAIT(1);
  reg_fence(sn);
  sm_mask(sn, mode, dthr);
  sm_max(sn, mn, d);
  sm_exp<EXP1, 8>(s, p);
}
#define ATT_ISSUE(HQ, sq, kq, HP, op, pp, kv) do { WG_FENCE(); qk_issue<HQ>(sq, q, kq); WG_COMMIT(); pv_issue<HP>(op, pp, kv); WG_COMMIT(); } while (0)

__device__ __forceinline__ void store_partial64(const float* a, uint8_t* dst, uint32_t tag) {
#pragma unroll
  for (int i = 0; i < 4; i++) {
    uint4 v;
    v.x = tag16(pack2(a[8 * i + 0], a[8 * i + 1]), tag);
    v.y = pack2(a[8 * i + 2], a[8 * i + 3]);
    v.z = pack2(a[8 * i + 4], a[8 * i + 5]);
    v.w = pack2(a[8 * i + 6], a[8 * i + 7]);
    *reinterpret_cast<uint4*>(dst + i * 512) = v;
  }
}

__global__ void __cluster_dims__(2, 1, 1) __launch_bounds__(384, 1) fused_block_kernel(const __grid_constant__ Params P) {
  extern __shared__ __align__(1024) uint8_t smem[];
  const uint32_t sb = s2u(smem);
  const int tid = threadIdx.x, lane = tid & 31, warp = __shfl_sync(0xffffffffu, tid >> 5, 0);
  const uint32_t rank = blockIdx.x & 1;
  const int rb = blockIdx.x & 15, c = blockIdx.x >> 4;
  const int tile = rb * 8 + c;
  const uint32_t bars = sb + OFF_MISC;
#define BAR(i) (bars + 8u * (uint32_t)(i))
  const int odd = c & 1;
  const int mainch = (c >> 1) * 5 + (odd ? 3 : 0), leftch = (c >> 1) * 10 + (odd ? 5 : 4);
  if (warp >= 8) asm volatile("setmaxnreg.dec.sync.aligned.u32 56;");
  if (lane == 0) {
    if (warp == 8) {
      asm volatile("prefetch.tensormap [%0];" ::"l"(&P.mWqM) : "memory");
      asm volatile("prefetch.tensormap [%0];" ::"l"(&P.mWqL) : "memory");
    } else {
      const int i0 = (warp < 8 ? warp + 3 : warp - 9) * 6;
#pragma unroll
      for (int u = 0; u < 6; u++) {
        const int i = i0 + u;
        if (i < 64) mbar_init(BAR(i), i < B_KVOWN ? 1 : i < B_Q23 ? 4 : i < B_QEMPTY ? 8 : 16);
      }
    }
    asm volatile("fence.mbarrier_init.release.cluster;" ::: "memory");
    if (warp == 9) {
      mbar_expect(BAR(B_QFULL), QST);
      tma2d(sb, &P.mX, 0, rb * 128, BAR(B_QFULL));
    }
  }
  __syncwarp();
  if (warp == 8) STAMPW(11);
  asm volatile("barrier.cluster.arrive.relaxed.aligned;" ::: "memory");
  if (warp == 8) {
    asm volatile("barrier.cluster.wait.acquire.aligned;\nbar.arrive 1, 384;" ::: "memory");
    STAMPW(8);
    if (lane == 0) {
#pragma unroll 1
      for (int kt = 0; kt < 4; kt++) {
        const uint32_t a = sb + kt * QST, fb = BAR(B_QFULL + kt);
        if (kt) mbar_expect(fb, QST);
        tma4d_mc(a + 16384 + rank * 12288, &P.mWqM, 0, kt * 64 + rank * 32, mainch, 0, fb);
        tma4d_mc(a + 40960 + rank * 3072, &P.mWqL, 0, kt * 64 + rank * 32, leftch, 0, fb);
        if (kt) tma2d(a, &P.mX, kt * 64, rb * 128, fb);
        if (kt == 0) STAMPW(10);
      }
    }
    __syncwarp();
    STAMPW(9);
  } else {
    asm volatile("bar.sync 1, 384;" ::: "memory");
  }
  const int sc = (27 * c + 3) >> 2;

  if (warp >= 8) {
    const uint32_t epoch = ldcg32(&g_epoch[tile]) + 1u;
    const uint32_t ep = epoch & 3u, tag = (epoch & 1u) | ((epoch & 2u) << 15);
    if (warp == 8) {
      if (lane == 0) {
#pragma unroll 1
        for (int kt = 4; kt < 10; kt++) {
          const int st = kt & 3;
          mbar_wait(BAR(B_QEMPTY + st), ((kt >> 2) - 1) & 1);
          const uint32_t a = sb + st * QST, fb = BAR(B_QFULL + st);
          mbar_expect(fb, QST);
          tma4d_mc(a + 16384 + rank * 12288, &P.mWqM, 0, kt * 64 + rank * 32, mainch, 0, fb);
          tma4d_mc(a + 40960 + rank * 3072, &P.mWqL, 0, kt * 64 + rank * 32, leftch, 0, fb);
          tma2d(a, &P.mX, kt * 64, rb * 128, fb);
        }
        const CUtensorMap* mW1 = rank ? &P.mW1b : &P.mW1a;
        asm volatile("prefetch.tensormap [%0];" ::"l"(&P.mWo) : "memory");
        asm volatile("prefetch.tensormap [%0];" ::"l"(mW1) : "memory");
        asm volatile("prefetch.tensormap [%0];" ::"l"(&P.mW2) : "memory");
        mbar_wait(BAR(B_QEMPTY + 0), 0);
        mbar_wait(BAR(B_QEMPTY + 1), 0);
        if (rb) mbar_wait(BAR(B_KVFULL + 3), 0);
        mbar_expect(BAR(B_WOB), 89600);
#pragma unroll 1
        for (int i = 0; i < 4 - (int)rank; i++) {
          const int pos = rank * 4 + i;
          tma3d_mc(sb + OFF_WOB + pos * 12800, &P.mWo, 0, ((c + pos) & 7) * 80, c * 5, BAR(B_WOB));
        }
#pragma unroll 1
        for (int s = 0; s < 8; s++) {
          if (s == 0) {
            mbar_wait(BAR(B_ATTP), 0);
            mbar_expect(BAR(B_WOB7), 12800);
            if (rank) tma3d_mc(sb + OFF_WOB + 7 * 12800, &P.mWo, 0, ((c + 7) & 7) * 80, c * 5, BAR(B_WOB7));
          } else if (s == 3) mbar_wait(BAR(B_WODP), 0);
          else if (s >= 5) mbar_wait(BAR(B_BEMPTY + s - 5), 0);
          const uint32_t fb = BAR(B_BFULL + s);
          mbar_expect(fb, 35840);
          tma3d_mc(sb + w1b_addr(s) + rank * 20480, mW1, 0, ((c + s) & 7) * 80, sc + rank * 4, fb);
        }
#pragma unroll 1
        for (int s = 0; s < 5; s++) {
          mbar_wait(s < 4 ? BAR(B_BEMPTY + 4 + s) : BAR(B_W2E), 0);
          const uint32_t dst = sb + (s & 3) * W2SLOT + rank * 14336, fb = BAR(B_W2FULL + s);
          const int bx0 = s == 0 ? 8 : ((c + 2 * s - 1) & 7), bx1 = s == 0 ? 9 : ((c + 2 * s) & 7);
          mbar_expect(fb, W2SLOT);
          tma2d_mc(dst, &P.mW2, bx0 * 64, sc * 32 + rank * 112, fb);
          tma2d_mc(dst + 28672, &P.mW2, bx1 * 64, sc * 32 + rank * 112, fb);
        }
      }
      __syncwarp();
    } else {
      if (warp == 11) {
        mbar_wait(BAR(B_QFULL + 3), 0);
        if (lane == 0) {
          l2_prefetch_bulk(reinterpret_cast<const uint8_t*>(P.wo) + tile * 6400, 6400);
          l2_prefetch_bulk(reinterpret_cast<const uint8_t*>(P.w1) + tile * 17280, 17280);
          l2_prefetch_bulk(reinterpret_cast<const uint8_t*>(P.w2) + tile * 17280, 17280);
        }
        mbar_wait(BAR(B_PRE), 0);
#pragma unroll 1
        for (int q = lane; q < 60; q += 32) {
          float4 a = make_float4(0.f, 0.f, 0.f, 0.f);
#pragma unroll
          for (int i = 0; i < 8; i++) {
            const float4 v = *reinterpret_cast<const float4*>(smem + OFF_PRE + i * 960 + q * 16);
            a.x += v.x; a.y += v.y; a.z += v.z; a.w += v.w;
          }
          *reinterpret_cast<float4*>(&g_csq[tile * 240 + q * 4]) = make_float4(tag32(a.x, ep), tag32(a.y, ep), tag32(a.z, ep), tag32(a.w, ep));
        }
        __syncwarp();
        STAMPW(0);
        mbar_wait(BAR(B_Q23), 0);
      } else {
        mbar_wait(BAR(B_KVOWN + warp - 9), 0);
        if (lane == 0) {
          asm volatile("cp.async.bulk.global.shared::cta.bulk_group [%0], [%1], %2;\ncp.async.bulk.commit_group;"
                       ::"l"(g_kv + (size_t)((rb * 2 + warp - 9) * 8 + c) * KVB), "r"(sb + kv_addr(warp - 5)), "r"(KVB) : "memory");
        }
      }
#pragma unroll 1
      for (int bi = warp == 9 ? 2 : warp == 10 ? 3 : 1; bi >= 0; bi -= (warp == 9 ? 2 : 4)) {
        const int blk = 2 * rb - 4 + bi;
        if (blk < 0) continue;
        const uint8_t* src = g_kv + (size_t)(blk * 8 + c) * KVB;
        const uint32_t dst = sb + kv_addr(bi);
        uint32_t n = 0, ph = 0;
        while (!__all_sync(0xffffffffu, ((ldcg32(src + lane * 704 + 692) ^ tag) & TAGM) == 0u) && ++n < SPIN_MAX) {}
        if (warp == 9 && bi == 2) STAMPW(3);
        while (true) {
          if (lane == 0) {
            fence_async_glob();
            mbar_expect(BAR(B_KVLAND + bi), KVB);
            bulk_load(dst, src, KVB, BAR(B_KVLAND + bi));
          }
          mbar_wait(BAR(B_KVLAND + bi), ph);
          ph ^= 1u;
          uint32_t bad = 0;
#pragma unroll 11
          for (int i = 0; i < 44; i++) {
            uint32_t v;
            asm volatile("ld.shared.u32 %0, [%1];" : "=r"(v) : "r"(dst + (i * 32 + lane) * 16 + 4) : "memory");
            bad |= v ^ tag;
          }
          if (!__any_sync(0xffffffffu, (bad & TAGM) != 0u) || ++n >= SPIN_MAX) break;
        }
        if (lane == 0) {
          asm volatile("cp.async.bulk.wait_group.read 0;" ::: "memory");
          mbar_arrive(BAR(B_KVFULL + bi));
        }
        if (warp == 9 && bi == 2) STAMPW(5);
      }
      __syncwarp();
      asm volatile("barrier.cluster.wait.acquire.aligned;" ::: "memory");
      if (warp == 10) {
        const int col = sc * 32 + lane * 8;
        const uint8_t* wb = reinterpret_cast<const uint8_t*>(P.w1) + (size_t)rb * 40 * 3456 + (size_t)col * 2;
        float acc[8];
#pragma unroll
        for (int i = 0; i < 8; i++) acc[i] = 0.f;
        if (lane < 28 && col < 1728) {
#pragma unroll 1
          for (int i = 0; i < 40; i += 8) {
            uint4 v[8];
#pragma unroll
            for (int u = 0; u < 8; u++) v[u] = __ldg(reinterpret_cast<const uint4*>(wb + (size_t)(i + u) * 3456));
#pragma unroll
            for (int u = 0; u < 8; u++) {
              acc[0] += bf_lo(v[u].x); acc[1] += bf_hi(v[u].x); acc[2] += bf_lo(v[u].y); acc[3] += bf_hi(v[u].y);
              acc[4] += bf_lo(v[u].z); acc[5] += bf_hi(v[u].z); acc[6] += bf_lo(v[u].w); acc[7] += bf_hi(v[u].w);
            }
          }
        }
        if (lane < 28) {
          float4* dst = reinterpret_cast<float4*>(&g_cs1[tile * 224 + lane * 8]);
          dst[0] = make_float4(tag32(acc[0], ep), tag32(acc[1], ep), tag32(acc[2], ep), tag32(acc[3], ep));
          dst[1] = make_float4(tag32(acc[4], ep), tag32(acc[5], ep), tag32(acc[6], ep), tag32(acc[7], ep));
        }
        STAMPW(4);
      } else if (warp == 11) {
        mbar_wait(BAR(B_ATTP), 0);
#pragma unroll 1
        for (int u = lane; u < 224; u += 32) *reinterpret_cast<float*>(smem + OFF_XS + u * 4) = gather16(g_cs1 + c * 224 + u, 1792, ep);
        __syncwarp();
        if (lane == 0) mbar_arrive(BAR(B_CS1));
        STAMPW(1);
      }
    }
    mbar_wait(BAR(B_W2D), 0);
    if (warp == 9 || warp == 10) {
      const uint8_t* src = g_part + (size_t)((rb * 2 + warp - 9) * 8 + c) * 65536;
      const uint8_t* pw = src + ((c - 1 - (lane >> 2)) & 7) * 8192 + (lane & 3) * 2048 + 2032;
      uint32_t ready = 0;
#pragma unroll 1
      for (int u = 0; u < 6; u++) {
        if (u == 3) mbar_wait(BAR(B_W2D + 1), 0);
        uint32_t n = 0;
        while (((~ready >> (4 * u)) & 15u) && ++n < SPIN_MAX) ready = __ballot_sync(0xffffffffu, ((ldcg32(pw) ^ tag) & TAGM) == 0u);
        if (lane == 0) {
          const uint32_t fb = BAR(B_PL + 2 * u + warp - 9);
          fence_async_glob();
          mbar_expect(fb, 8192);
          bulk_load(sb + W2SLOT + u * 16384 + (u >= 3 ? 8192 : 0) + (warp - 9) * 8192, src + ((c - 1 - u) & 7) * 8192, 8192, fb);
        }
      }
    } else {
#pragma unroll 1
      for (int j = warp == 8 ? 0 : 4, je = j + 4; j < je; j++) {
        uint4 v8[8], hv;
        uint32_t n = 0, bad;
        const uint8_t* p8 = g_p89 + (size_t)tile * 32768 + j * 512 + lane * 16;
        const uint8_t* ph = g_h + (size_t)tile * 20480 + (32 + j) * 512 + lane * 16;
        asm volatile("" : "+l"(p8), "+l"(ph));
        do {
#pragma unroll
          for (int u = 0; u < 8; u++) v8[u] = ldcg128(p8 + u * 4096);
          hv = ldcg128(ph);
          bad = hv.x ^ tag;
#pragma unroll
          for (int u = 0; u < 8; u++) bad |= v8[u].x ^ tag;
        } while (__any_sync(0xffffffffu, (bad & TAGM) != 0u) && ++n < SPIN_MAX);
        float f[8] = {bf_lo(hv.x), bf_hi(hv.x), bf_lo(hv.y), bf_hi(hv.y), bf_lo(hv.z), bf_hi(hv.z), bf_lo(hv.w), bf_hi(hv.w)};
#pragma unroll
        for (int u = 0; u < 8; u++) {
          f[0] += bf_lo(v8[u].x); f[1] += bf_hi(v8[u].x); f[2] += bf_lo(v8[u].y); f[3] += bf_hi(v8[u].y);
          f[4] += bf_lo(v8[u].z); f[5] += bf_hi(v8[u].z); f[6] += bf_lo(v8[u].w); f[7] += bf_hi(v8[u].w);
        }
        uint8_t* op = reinterpret_cast<uint8_t*>(P.out) + (size_t)(tile * 16 + (lane >> 2)) * 1280 + 1024 + j * 32 + (lane & 3) * 4;
        *reinterpret_cast<uint32_t*>(op) = pack2(f[0], f[1]);
        *reinterpret_cast<uint32_t*>(op + 8 * 1280) = pack2(f[2], f[3]);
        *reinterpret_cast<uint32_t*>(op + 16) = pack2(f[4], f[5]);
        *reinterpret_cast<uint32_t*>(op + 8 * 1280 + 16) = pack2(f[6], f[7]);
      }
      if (warp == 11) STAMPW(2);
      if (warp == 11 && lane == 0) st_flag(&g_epoch[tile], epoch);
    }
  } else {
    const int r = warp >> 2, w = warp & 3, gq = lane >> 2, tq = lane & 3;
    asm volatile("setmaxnreg.inc.sync.aligned.u32 224;");
    STAMP(4);
    uint4 xv[5], wv[5];
    uint32_t ep;
    const int b = rb * 2 + r;
    uint32_t q[24], tag;
    STAMP(0);
    {
      float accM[96], accL[24];
      uint2 s0u, s1u;
#define QKV_ISSUE(kt) do { \
        const uint32_t a = sb + ((kt) & 3) * QST; \
        const uint64_t da = mkdesc(a + r * 8192, desc_hi(16, 1024, 1)); \
        const uint64_t dm = mkdesc(a + 16384, desc_hi(2048, 512, 2)); \
        const uint64_t dl = mkdesc(a + 40960, desc_hi(1024, 256, 3)); \
        mbar_wait(BAR(B_QFULL + ((kt) & 3)), ((kt) >> 2) & 1); \
        WG_FENCE(); \
        _Pragma("unroll") for (int k = 0; k < 4; k++) { \
          wg_ss192(accM, da + k * 2, dm + (k >> 1) * 768 + (k & 1) * 64, (kt) | k); \
          wg_ss48(accL, da + k * 2, dl + (k >> 1) * 192 + (k & 1) * 32, (kt) | k); \
        } \
        WG_COMMIT(); } while (0)
      QKV_ISSUE(0);
      STAMP(1);
      {
          const uint8_t* xb = reinterpret_cast<const uint8_t*>(P.x) + (size_t)(rb * 128 + c * 16 + warp * 2 + (lane >> 4)) * 1280 + (lane & 15) * 16;
          const int cl = lane < 30 ? lane : 29;
          const uint8_t* wb = reinterpret_cast<const uint8_t*>(P.wqkv) + (size_t)(rb * 40 + warp * 5) * 3840 + (cl / 10) * 1280 + c * 160 + (cl % 10) * 16;
#pragma unroll
          for (int i = 0; i < 5; i++) wv[i] = ldnc128(wb + i * 3840);
#pragma unroll
          for (int i = 0; i < 5; i++) xv[i] = ldnc128(xb + i * 256);
          ep = ldcg32(&g_epoch[tile]);
      }
#pragma unroll 1
      for (int kt = 1; kt < 10; kt++) {
        QKV_ISSUE(kt);
        if (kt == STATKT) {
          STAMP(19);
#pragma unroll
          for (int i = 0; i < 5; i++) asm volatile("" : "+r"(wv[i].x), "+r"(wv[i].y), "+r"(wv[i].z), "+r"(wv[i].w));
          float a[8];
#pragma unroll
          for (int i = 0; i < 8; i++) a[i] = 0.f;
#pragma unroll
          for (int u = 0; u < 5; u++) {
            a[0] += bf_lo(wv[u].x); a[1] += bf_hi(wv[u].x); a[2] += bf_lo(wv[u].y); a[3] += bf_hi(wv[u].y);
            a[4] += bf_lo(wv[u].z); a[5] += bf_hi(wv[u].z); a[6] += bf_lo(wv[u].w); a[7] += bf_hi(wv[u].w);
          }
          if (lane < 30) {
            float4* dst = reinterpret_cast<float4*>(smem + OFF_PRE + warp * 960 + lane * 32);
            dst[0] = make_float4(a[0], a[1], a[2], a[3]);
            dst[1] = make_float4(a[4], a[5], a[6], a[7]);
          }
          __syncwarp();
          if (lane == 0) mbar_arrive(BAR(B_PRE));
          STAMP(5);
        } else if (kt == STATKT + 1) {
          asm volatile("" : "+r"(ep));
#pragma unroll
          for (int i = 0; i < 5; i++) asm volatile("" : "+r"(xv[i].x), "+r"(xv[i].y), "+r"(xv[i].z), "+r"(xv[i].w));
          ep = (ep + 1u) & 3u;
          float s = 0.f;
#pragma unroll
          for (int i = 0; i < 5; i++)
            s += ((bf_lo(xv[i].x) + bf_hi(xv[i].x)) + (bf_lo(xv[i].y) + bf_hi(xv[i].y))) + ((bf_lo(xv[i].z) + bf_hi(xv[i].z)) + (bf_lo(xv[i].w) + bf_hi(xv[i].w)));
#pragma unroll
          for (int o = 8; o; o >>= 1) s += __shfl_xor_sync(0xffffffffu, s, o);
          const float mean = s * (1.f / 640.f);
          float m2 = 0.f;
#pragma unroll
          for (int i = 0; i < 5; i++) {
            const uint32_t u[4] = {xv[i].x, xv[i].y, xv[i].z, xv[i].w};
#pragma unroll
            for (int j = 0; j < 4; j++) {
              const float d0 = bf_lo(u[j]) - mean, d1 = bf_hi(u[j]) - mean;
              m2 += d0 * d0 + d1 * d1;
            }
          }
#pragma unroll
          for (int o = 8; o; o >>= 1) m2 += __shfl_xor_sync(0xffffffffu, m2, o);
          if ((lane & 15) == 0)
            g_xstat[rb * 128 + c * 16 + warp * 2 + (lane >> 4)] = make_float2(mean, tag32(rsqrtf(m2 * (1.f / 640.f) + 1e-5f), ep));
        } else if (kt == STATKT + 2) {
          asm volatile("barrier.cluster.wait.acquire.aligned;" ::: "memory");
        } else
        if (kt == 9) {
          const float cs = gather16(g_csq + c * 240 + (tid < 240 ? tid : 239), 1920, ep);
          if (tid < 240) *reinterpret_cast<float*>(smem + OFF_CS + tid * 4) = cs;
          uint32_t n = 0;
          do {
            s0u = ldcg64(&g_xstat[b * 64 + w * 16 + gq]);
            s1u = ldcg64(&g_xstat[b * 64 + w * 16 + gq + 8]);
          } while (__any_sync(0xffffffffu, (((s0u.y ^ ep) | (s1u.y ^ ep)) & 3u) != 0u) && ++n < SPIN_MAX);
          if (lane == 0) mbar_arrive(BAR(B_STAT));
        }
        WG_WAIT(1);
        if (lane == 0) {
          mbar_arrive_pair(BAR(B_QEMPTY + ((kt - 1) & 3)));
          if (kt == 8) mbar_arrive(BAR(B_Q23));
        }
      }
      WG_WAIT(0);
      reg_fence(accM); reg_fence(accL);
      if (lane == 0) mbar_arrive_pair(BAR(B_QEMPTY + 1));
      STAMP(2);
      tag = (ep & 1u) | ((ep & 2u) << 15);
      mbar_wait(BAR(B_STAT), 0);
      mbar_wait(BAR(B_Q23), 0);
      const float2 s0 = make_float2(__uint_as_float(s0u.x), __uint_as_float(s0u.y)), s1 = make_float2(__uint_as_float(s1u.x), __uint_as_float(s1u.y));
      const uint32_t km = tq == 1 ? ~TAGM : 0xffffffffu, kt1 = tq == 1 ? tag : 0u;
      const uint32_t csM = sb + OFF_CS + (odd ? 64 : 0) + tq * 8, csL = sb + OFF_CS + (odd ? 0 : 256) + tq * 8;
      const uint32_t kvo = sb + kv_addr(4 + r) + (uint32_t)(w * 16 + ((lane >> 3) & 1) * 8 + (lane & 7)) * 16u + (uint32_t)(lane >> 4) * 1024u;
      const float qs = 0.22360679774997896f * 1.4426950408889634f;
      const bool lo = tq < 2;
      uint32_t qj[20];
#pragma unroll
      for (int mm = 0; mm < 3; mm++) {
        const int mat = (mm + 1) % 3;
        const float r0 = mat == 0 ? s0.y * qs : s0.y, r1 = mat == 0 ? s1.y * qs : s1.y;
        const float n0 = -s0.x * r0, n1 = -s1.x * r1;
        uint32_t pk[20];
#pragma unroll
        for (int t = 0; t < 10; t++) {
          const float* a = t < 8 ? &accM[(mat * 8 + t) * 4] : &accL[(mat * 2 + t - 8) * 4];
          const float2 cs = lds64f(t < 8 ? csM + mat * 320 + t * 32 : csL + mat * 320 + (t - 8) * 32);
          pk[2 * t] = pack2(fmaf(a[0], r0, cs.x * n0), fmaf(a[1], r0, cs.y * n0));
          pk[2 * t + 1] = pack2(fmaf(a[2], r1, cs.x * n1), fmaf(a[3], r1, cs.y * n1));
        }
        if (mat == 1) {
#pragma unroll
          for (int i = 0; i < 20; i++) pk[i] = (pk[i] & km) | kt1;
#pragma unroll
          for (int t = 0; t < 8; t += 2) stsm4(kvo + (odd ? 2048 : 0) + t * 1024, pk[2 * t], pk[2 * t + 1], pk[2 * t + 2], pk[2 * t + 3]);
          stsm4(kvo + (odd ? 0 : 8192), pk[16], pk[17], pk[18], pk[19]);
        } else {
#pragma unroll
          for (int i = 0; i < 20; i++) qj[i] = odd ? pk[(i + 16) % 20] : pk[i];
        }
        if (mat == 2) {
          const uint32_t one = (tq & 1) ? 0u : 0x3f80u;
          uint32_t vv[24];
#pragma unroll
          for (int hp = 0; hp < 2; hp++) {
            const int j = hp * 10;
#pragma unroll
            for (int i = 0; i < 4; i++) { vv[hp * 12 + i] = qj[j + i]; vv[hp * 12 + 8 + i] = qj[j + 6 + i]; }
            vv[hp * 12 + 4] = lo ? qj[j + 4] : one; vv[hp * 12 + 5] = lo ? qj[j + 5] : one;
            vv[hp * 12 + 6] = lo ? one : qj[j + 4]; vv[hp * 12 + 7] = lo ? one : qj[j + 5];
          }
#pragma unroll
          for (int i = 0; i < 24; i++) vv[i] = (vv[i] & km) | kt1;
#pragma unroll
          for (int t = 0; t < 6; t++) stsm4(kvo + 10240 + t * 2048, vv[4 * t], vv[4 * t + 1], vv[4 * t + 2], vv[4 * t + 3]);
          fence_async_smem();
          __syncwarp();
          if (lane == 0) mbar_arrive(BAR(B_KVOWN + r));
        }
      }
#pragma unroll
      for (int hp = 0; hp < 2; hp++) {
        const int j = hp * 10;
        q[hp * 12 + 0] = qj[j + 0]; q[hp * 12 + 1] = qj[j + 1]; q[hp * 12 + 2] = qj[j + 2]; q[hp * 12 + 3] = qj[j + 3];
        q[hp * 12 + 4] = lo ? qj[j + 4] : 0u; q[hp * 12 + 5] = lo ? qj[j + 5] : 0u;
        q[hp * 12 + 6] = lo ? 0u : qj[j + 4]; q[hp * 12 + 7] = lo ? 0u : qj[j + 5];
        q[hp * 12 + 8] = qj[j + 6]; q[hp * 12 + 9] = qj[j + 7]; q[hp * 12 + 10] = qj[j + 8]; q[hp * 12 + 11] = qj[j + 9];
      }
    }
    STAMP(3);
    uint32_t x0[20], xr[20];
    const int row_lo = b * 64 + w * 16 + gq;
    {
      float o0[12], o1[12], o2[12], o3[12], m[4][2];
#pragma unroll
      for (int i = 0; i < 12; i++) { o0[i] = 0.f; o1[i] = 0.f; o2[i] = 0.f; o3[i] = 0.f; }
#pragma unroll
      for (int i = 0; i < 4; i++) m[i][0] = m[i][1] = -INFINITY;
      float s0[32], s1[32];
      uint32_t p0[16], p1[16];
      const int dthr = w * 16 + gq - 2 * tq;
      const uint32_t seq = r ? 0x13245u : 0x01324u;
      const int nit = rb >= 2 ? 5 : 2 * rb + 1 + r;
      mbar_wait(BAR(B_KVOWN + r), 0);
      uint32_t kb = ((sb + kv_addr(4 + r)) & 0x3FFFF) >> 4, kp = kb;
      WG_FENCE();
      qk_issue<0>(s0, q, kb);
      WG_COMMIT();
#pragma unroll
      for (int i = 0; i < 16; i++) p1[i] = 0u;
      float d[2];
      WG_WAIT(0);
      reg_fence(s0);
      sm_mask(s0, 1, dthr);
      sm_max(s0, m[0], d);
#pragma unroll 1
      for (int it = 0; it < nit; it++) {
        const int mode = it == 0 ? 1 : it == 4 ? 2 : 0;
        ATT_ISSUE(1, s1, kb, 3, o3, p1, kp);
        sm_step(s0, p0, o0, d, s1, m[1], mode, dthr);
        ATT_ISSUE(2, s0, kb, 0, o0, p0, kb);
        sm_step(s1, p1, o1, d, s0, m[2], mode, dthr);
        ATT_ISSUE(3, s1, kb, 1, o1, p1, kb);
        sm_step(s0, p0, o2, d, s1, m[3], mode, dthr);
        kp = kb;
        if (it + 1 < nit) {
          const int bi = (seq >> (4 * it + 4)) & 15;
          mbar_wait(bi == 4 ? BAR(B_KVOWN) : BAR(B_KVFULL + bi), 0);
          kb = ((sb + kv_addr(bi)) & 0x3FFFF) >> 4;
        }
        ATT_ISSUE(0, s0, kb, 2, o2, p0, kp);
        sm_step(s1, p1, o3, d, s0, m[0], it == 3 ? 2 : 0, dthr);
        WG_WAIT(0);
      }
      WG_FENCE();
      pv_issue<3>(o3, p1, kp);
      WG_COMMIT();
      const uint8_t* xp = reinterpret_cast<const uint8_t*>(P.x) + (size_t)row_lo * 1280 + c * 160 + tq * 4;
#pragma unroll
      for (int t = 0; t < 10; t++) {
        xr[2 * t] = ldnc32(xp + t * 16);
        xr[2 * t + 1] = ldnc32(xp + 8 * 1280 + t * 16);
      }
      WG_WAIT(0);
      reg_fence(o0); reg_fence(o1); reg_fence(o2); reg_fence(o3); reg_fence(s0); reg_fence(s1);
      if (lane == 0) mbar_arrive_pair(BAR(B_ATTP));
      float inv[4][2];
      inv[0][0] = rcp(__shfl_sync(0xffffffffu, o0[8], (lane & 28) + 2));
      inv[0][1] = rcp(__shfl_sync(0xffffffffu, o0[10], (lane & 28) + 2));
      inv[1][0] = rcp(__shfl_sync(0xffffffffu, o1[0], lane & 28));
      inv[1][1] = rcp(__shfl_sync(0xffffffffu, o1[2], lane & 28));
      inv[2][0] = rcp(__shfl_sync(0xffffffffu, o2[8], (lane & 28) + 2));
      inv[2][1] = rcp(__shfl_sync(0xffffffffu, o2[10], (lane & 28) + 2));
      inv[3][0] = rcp(__shfl_sync(0xffffffffu, o3[0], lane & 28));
      inv[3][1] = rcp(__shfl_sync(0xffffffffu, o3[2], lane & 28));
      const bool lo = tq < 2;
#define OPK(dst, o, t, h) do { x0[dst] = pack2(o[4 * (t)] * inv[h][0], o[4 * (t) + 1] * inv[h][0]); x0[dst + 1] = pack2(o[4 * (t) + 2] * inv[h][1], o[4 * (t) + 3] * inv[h][1]); } while (0)
#define OPK2(dst, oa, ha, ob, hb) do { \
        const float i0 = lo ? inv[ha][0] : inv[hb][0], i1 = lo ? inv[ha][1] : inv[hb][1]; \
        x0[dst] = pack2((lo ? oa[8] : ob[0]) * i0, (lo ? oa[9] : ob[1]) * i0); \
        x0[dst + 1] = pack2((lo ? oa[10] : ob[2]) * i1, (lo ? oa[11] : ob[3]) * i1); } while (0)
      OPK(0, o0, 0, 0); OPK(2, o0, 1, 0); OPK2(4, o0, 0, o1, 1); OPK(6, o1, 1, 1); OPK(8, o1, 2, 1);
      OPK(10, o2, 0, 2); OPK(12, o2, 1, 2); OPK2(14, o2, 2, o3, 3); OPK(16, o3, 1, 3); OPK(18, o3, 2, 3);
    }
    const int bw = b * 4 + w;
    const size_t tile_off = (size_t)bw * 20480 + lane * 16;
    const size_t probe_off = (size_t)bw * 20480 + ((c + lane) & 7) * 2560 + 2544;
    {
#pragma unroll
      for (int k = 0; k < 5; k++) {
        x0[4 * k] = tag16(x0[4 * k], tag);
        stg128(g_o + tile_off + c * 2560 + k * 512, x0[4 * k], x0[4 * k + 1], x0[4 * k + 2], x0[4 * k + 3]);
      }
      STAMP(6);
      const uint32_t pv = ldcg32(g_o + probe_off);
      float acc[40];
#pragma unroll
      for (int t = 0; t < 10; t++) {
        acc[4 * t] = bf_lo(xr[2 * t]); acc[4 * t + 1] = bf_hi(xr[2 * t]); acc[4 * t + 2] = bf_lo(xr[2 * t + 1]); acc[4 * t + 3] = bf_hi(xr[2 * t + 1]);
      }
      constexpr uint64_t HI = desc_hi(2560, 256, 3);
      const uint64_t db = mkdesc(sb + OFF_WOB, HI);
      mbar_wait(BAR(B_WOB), 0);
      WG_FENCE();
#pragma unroll
      for (int k = 0; k < 5; k++) wg_rs80(acc, x0[4 * k], x0[4 * k + 1], x0[4 * k + 2], x0[4 * k + 3], db + k * 32, 1);
      WG_COMMIT();
      uint32_t xa[7][20], ready = __ballot_sync(0xffffffffu, ((pv ^ tag) & TAGM) == 0u);
#pragma unroll
      for (int i = 1; i < 8; i++) {
        probe_wait(ready, i, g_o + probe_off, tag);
        if (i == 7) WG_WAIT(0);
        ld_tile(xa[i - 1], g_o + tile_off + ((c + i) & 7) * 2560);
      }
      STAMP(7);
#pragma unroll
      for (int i = 1; i < 8; i++) {
        if (i == 7) mbar_wait(BAR(B_WOB7), 0);
        fix_tile(xa[i - 1], g_o + tile_off + ((c + i) & 7) * 2560, tag);
        WG_FENCE();
#pragma unroll
        for (int k = 0; k < 5; k++) wg_rs80(acc, xa[i - 1][4 * k], xa[i - 1][4 * k + 1], xa[i - 1][4 * k + 2], xa[i - 1][4 * k + 3], db + i * 800 + k * 32, 1);
        WG_COMMIT();
      }
      WG_WAIT(0);
      reg_fence(acc);
      if (lane == 0) mbar_arrive_pair(BAR(B_WODP));
      STAMP(8);
      float sum0 = 0.f, sum1 = 0.f;
#pragma unroll
      for (int t = 0; t < 10; t++) {
        x0[2 * t] = pack2(acc[4 * t], acc[4 * t + 1]);
        x0[2 * t + 1] = pack2(acc[4 * t + 2], acc[4 * t + 3]);
      }
#pragma unroll
      for (int k = 0; k < 5; k++) {
        x0[4 * k] = tag16(x0[4 * k], tag);
        stg128(g_h + tile_off + c * 2560 + k * 512, x0[4 * k], x0[4 * k + 1], x0[4 * k + 2], x0[4 * k + 3]);
      }
#pragma unroll
      for (int t = 0; t < 10; t++) {
        sum0 += bf_lo(x0[2 * t]) + bf_hi(x0[2 * t]);
        sum1 += bf_lo(x0[2 * t + 1]) + bf_hi(x0[2 * t + 1]);
      }
      sum0 += __shfl_xor_sync(0xffffffffu, sum0, 1);
      sum1 += __shfl_xor_sync(0xffffffffu, sum1, 1);
      sum0 += __shfl_xor_sync(0xffffffffu, sum0, 2);
      sum1 += __shfl_xor_sync(0xffffffffu, sum1, 2);
      const float mu0 = sum0 * (1.f / 80.f), mu1 = sum1 * (1.f / 80.f);
      float v0 = 0.f, v1 = 0.f;
#pragma unroll
      for (int t = 0; t < 10; t++) {
        const float d0 = bf_lo(x0[2 * t]) - mu0, d1 = bf_hi(x0[2 * t]) - mu0, d2 = bf_lo(x0[2 * t + 1]) - mu1, d3 = bf_hi(x0[2 * t + 1]) - mu1;
        v0 += d0 * d0 + d1 * d1;
        v1 += d2 * d2 + d3 * d3;
      }
      v0 += __shfl_xor_sync(0xffffffffu, v0, 1);
      v1 += __shfl_xor_sync(0xffffffffu, v1, 1);
      v0 += __shfl_xor_sync(0xffffffffu, v0, 2);
      v1 += __shfl_xor_sync(0xffffffffu, v1, 2);
      if (tq < 2) g_hstat[(bw * 8 + c) * 16 + gq + tq * 8] = make_float2(tq ? mu1 : mu0, tag32(tq ? v1 : v0, ep));
    }
    uint32_t ha[56];
    {
      float acc[112];
      constexpr uint64_t HI = desc_hi(5120, 512, 2);
#define W1_ISSUE(xx, i) do { \
        const uint64_t db = mkdesc(sb + w1b_addr(i), HI); \
        mbar_wait(BAR(B_BFULL + (i)), 0); \
        WG_FENCE(); \
        _Pragma("unroll") for (int k = 0; k < 5; k++) wg_rs224(acc, xx[4 * k], xx[4 * k + 1], xx[4 * k + 2], xx[4 * k + 3], db + k * 64, (i) | k); \
        WG_COMMIT(); } while (0)
#define W1_STEP(xx, xp, i) do { \
        fix_tile(xx, ht + ((c + (i)) & 7) * 2560, tag); \
        W1_ISSUE(xx, i); \
        WG_WAIT(1); \
        if ((i) != 4 && lane == 0) mbar_arrive_pair(BAR(B_BEMPTY - 1 + (i))); \
        if ((i) < 5) ld_tile(xp, ht + ((c + (i) + 3) & 7) * 2560); } while (0)
      W1_ISSUE(x0, 0);
      STAMP(9);
      const uint8_t* ht = g_h + tile_off;
      uint32_t x1[20], x2[20], x3[20], ready = 0;
      probe_wait(ready, 1, g_h + probe_off, tag);
      ld_tile(x1, ht + ((c + 1) & 7) * 2560);
      probe_wait(ready, 2, g_h + probe_off, tag);
      ld_tile(x2, ht + ((c + 2) & 7) * 2560);
      probe_wait(ready, 3, g_h + probe_off, tag);
      ld_tile(x3, ht + ((c + 3) & 7) * 2560);
      STAMP(10);
#pragma unroll 1
      for (int i = 1; ; i += 4) {
        W1_STEP(x1, x0, i);
        W1_STEP(x2, x1, i + 1);
        W1_STEP(x3, x2, i + 2);
        if (i == 5) break;
        W1_STEP(x0, x3, i + 3);
      }
      uint2 hs[4];
      {
        const float2* hp = &g_hstat[(bw * 8 + tq * 2) * 16 + gq];
        uint32_t n = 0;
        do {
          hs[0] = ldcg64(hp); hs[1] = ldcg64(hp + 16); hs[2] = ldcg64(hp + 8); hs[3] = ldcg64(hp + 24);
        } while (__any_sync(0xffffffffu, (((hs[0].y ^ ep) | (hs[1].y ^ ep) | (hs[2].y ^ ep) | (hs[3].y ^ ep)) & 3u) != 0u) && ++n < SPIN_MAX);
      }
      float mean0, mean1, rs0, rs1;
      {
        const float a0 = __uint_as_float(hs[0].x), a1 = __uint_as_float(hs[1].x), b0 = __uint_as_float(hs[2].x), b1 = __uint_as_float(hs[3].x);
        float t0 = a0 + a1, t1 = b0 + b1;
        t0 += __shfl_xor_sync(0xffffffffu, t0, 1);
        t1 += __shfl_xor_sync(0xffffffffu, t1, 1);
        t0 += __shfl_xor_sync(0xffffffffu, t0, 2);
        t1 += __shfl_xor_sync(0xffffffffu, t1, 2);
        mean0 = t0 * 0.125f;
        mean1 = t1 * 0.125f;
        float u0 = __uint_as_float(hs[0].y) + __uint_as_float(hs[1].y) + 80.f * ((a0 - mean0) * (a0 - mean0) + (a1 - mean0) * (a1 - mean0));
        float u1 = __uint_as_float(hs[2].y) + __uint_as_float(hs[3].y) + 80.f * ((b0 - mean1) * (b0 - mean1) + (b1 - mean1) * (b1 - mean1));
        u0 += __shfl_xor_sync(0xffffffffu, u0, 1);
        u1 += __shfl_xor_sync(0xffffffffu, u1, 1);
        u0 += __shfl_xor_sync(0xffffffffu, u0, 2);
        u1 += __shfl_xor_sync(0xffffffffu, u1, 2);
        rs0 = 0.5f * rsqrtf(u0 * (1.f / 640.f) + 1e-5f);
        rs1 = 0.5f * rsqrtf(u1 * (1.f / 640.f) + 1e-5f);
      }
      mbar_wait(BAR(B_CS1), 0);
      WG_WAIT(0);
      reg_fence(acc);
      if (lane == 0) mbar_arrive_pair(BAR(B_BEMPTY + 7));
      STAMP(11);
      const float n0 = -mean0 * rs0, n1 = -mean1 * rs1;
#pragma unroll
      for (int t = 0; t < 28; t++) {
        const float2 cs = lds64f(sb + OFF_XS + t * 32 + tq * 8);
        const float h0 = fmaf(acc[4 * t], rs0, cs.x * n0), h1 = fmaf(acc[4 * t + 1], rs0, cs.y * n0);
        const float h2 = fmaf(acc[4 * t + 2], rs1, cs.x * n1), h3 = fmaf(acc[4 * t + 3], rs1, cs.y * n1);
        ha[2 * t] = pack2(fmaf(h0, tanh_fast(h0), h0), fmaf(h1, tanh_fast(h1), h1));
        ha[2 * t + 1] = pack2(fmaf(h2, tanh_fast(h2), h2), fmaf(h3, tanh_fast(h3), h3));
      }
      if ((c & 3) == 3) {
#pragma unroll
        for (int t = 48; t < 56; t++) ha[t] = 0u;
      }
    }
    STAMP(12);
    {
      float accA[64], accB[64];
      constexpr uint64_t HI = desc_hi(28672, 1024, 1);
      const uint32_t lane_off = w * 2048 + lane * 16;
#define W2_ISSUE(acc, s) do { \
        mbar_wait(BAR(B_W2FULL + (s)), 0); \
        const uint64_t db = mkdesc(sb + ((s) & 3) * W2SLOT, HI); \
        WG_FENCE(); \
        _Pragma("unroll") for (int k = 0; k < 14; k++) wg_rs128(acc, ha[4 * k], ha[4 * k + 1], ha[4 * k + 2], ha[4 * k + 3], db + k * 128, k); \
        WG_COMMIT(); } while (0)
      uint8_t* const gp = g_part + (size_t)(b * 64 + c) * 8192 + lane_off;
#define W2_STORE(acc, s) do { \
        store_partial64(&acc[0], gp + ((c + 2 * (s) - 1) & 7) * 65536, tag); \
        store_partial64(&acc[32], gp + ((c + 2 * (s)) & 7) * 65536, tag); } while (0)
      W2_ISSUE(accA, 0);
      W2_ISSUE(accB, 1);
      WG_WAIT(1);
      reg_fence(accA);
      if (lane == 0) mbar_arrive_pair(BAR(B_W2E));
      {
        uint8_t* dst = g_p89 + (size_t)(bw * 8 + c) * 4096 + lane * 16;
        store_partial64(&accA[0], dst, tag);
        store_partial64(&accA[32], dst + 2048, tag);
      }
      STAMP(13);
      W2_ISSUE(accA, 2);
      WG_WAIT(1);
      reg_fence(accB);
      if (lane == 0) mbar_arrive(BAR(B_W2D));
      W2_STORE(accB, 1);
      W2_ISSUE(accB, 3);
      WG_WAIT(1);
      reg_fence(accA);
      if (lane == 0) mbar_arrive(BAR(B_W2D + 1));
      W2_STORE(accA, 2);
      float accR[32], accO[32];
      {
        mbar_wait(BAR(B_W2FULL + 4), 0);
        const uint64_t db = mkdesc(sb, HI);
        WG_FENCE();
#pragma unroll
        for (int k = 0; k < 14; k++) wg_rs64(accR, ha[4 * k], ha[4 * k + 1], ha[4 * k + 2], ha[4 * k + 3], db + k * 128, k);
        WG_COMMIT();
#pragma unroll
        for (int k = 0; k < 14; k++) wg_rs64(accO, ha[4 * k], ha[4 * k + 1], ha[4 * k + 2], ha[4 * k + 3], db + 1792 + k * 128, k);
        WG_COMMIT();
      }
      WG_WAIT(2);
      reg_fence(accB);
      W2_STORE(accB, 3);
      uint4 v[4];
      ld4(v, g_h + tile_off + c * 2048);
      WG_WAIT(1);
      reg_fence(accR);
      store_partial64(&accR[0], gp + ((c + 7) & 7) * 65536, tag);
      STAMP(14);
      WG_WAIT(0);
      reg_fence(accO);
      add4(accO, v);
      STAMP(15);
      const uint8_t* pp = g_part + (size_t)(b * 8 + c) * 65536 + lane_off;
#pragma unroll 1
      for (int u = 0; u < 7; u++) {
        if (u < 6) {
          const uint32_t z = sb + W2SLOT + u * 16384 + (u >= 3 ? 8192 : 0) + r * 8192 + lane_off;
          mbar_wait(BAR(B_PL + 2 * u + r), 0);
#pragma unroll
          for (int i = 0; i < 4; i++)
            asm volatile("ld.shared.v4.u32 {%0,%1,%2,%3}, [%4];" : "=r"(v[i].x), "=r"(v[i].y), "=r"(v[i].z), "=r"(v[i].w) : "r"(z + i * 512) : "memory");
        } else {
          STAMP(16);
          v[0].x = ~tag;
        }
        uint32_t n = 0;
        while (__any_sync(0xffffffffu, (((v[0].x ^ tag) | (v[1].x ^ tag) | (v[2].x ^ tag) | (v[3].x ^ tag)) & TAGM) != 0u) && ++n < SPIN_MAX)
          ld4(v, pp + ((c - 1 - u) & 7) * 8192);
        add4(accO, v);
      }
      uint8_t* op = reinterpret_cast<uint8_t*>(P.out) + (size_t)row_lo * 1280 + c * 128 + tq * 4;
#pragma unroll
      for (int t = 0; t < 8; t++) {
        *reinterpret_cast<uint32_t*>(op + t * 16) = pack2(accO[4 * t], accO[4 * t + 1]);
        *reinterpret_cast<uint32_t*>(op + 8 * 1280 + t * 16) = pack2(accO[4 * t + 2], accO[4 * t + 3]);
      }
      STAMP(17);
    }
  }
}

typedef CUresult (*EncodeFn)(CUtensorMap*, CUtensorMapDataType, cuuint32_t, void*, const cuuint64_t*, const cuuint64_t*, const cuuint32_t*,
                             const cuuint32_t*, CUtensorMapInterleave, CUtensorMapSwizzle, CUtensorMapL2promotion, CUtensorMapFloatOOBfill);

static void make_map(EncodeFn enc, CUtensorMap* m, const void* p, int nd, const cuuint64_t* dims, const cuuint64_t* strides, const cuuint32_t* box,
                     CUtensorMapSwizzle sw) {
  const cuuint32_t es[5] = {1, 1, 1, 1, 1};
  enc(m, CU_TENSOR_MAP_DATA_TYPE_BFLOAT16, (cuuint32_t)nd, const_cast<void*>(p), dims, strides, box, es, CU_TENSOR_MAP_INTERLEAVE_NONE, sw,
      CU_TENSOR_MAP_L2_PROMOTION_L2_128B, CU_TENSOR_MAP_FLOAT_OOB_FILL_NONE);
}

extern "C" void kernel_launch(void* const* d_in, const int* in_sizes, int n_in, void* d_out, int out_size) {
  (void)in_sizes; (void)n_in; (void)out_size;
  static EncodeFn enc = nullptr;
  if (!enc) {
    void* f = nullptr;
    cudaDriverEntryPointQueryResult qr;
    cudaGetDriverEntryPoint("cuTensorMapEncodeTiled", &f, cudaEnableDefault, &qr);
    enc = (EncodeFn)f;
    cudaFuncSetAttribute(fused_block_kernel, cudaFuncAttributeMaxDynamicSharedMemorySize, (int)SMEM_BYTES);
  }
  Params P;
  P.x = (const __nv_bfloat16*)d_in[0];
  P.wqkv = (const __nv_bfloat16*)d_in[1];
  P.wo = (const __nv_bfloat16*)d_in[2];
  P.w1 = (const __nv_bfloat16*)d_in[4];
  P.w2 = (const __nv_bfloat16*)d_in[5];
  P.out = (__nv_bfloat16*)d_out;
  { const cuuint64_t d[2] = {640, 2048}, s[1] = {1280}; const cuuint32_t b[2] = {64, 128}; make_map(enc, &P.mX, P.x, 2, d, s, b, CU_TENSOR_MAP_SWIZZLE_128B); }
  { const cuuint64_t d[4] = {32, 640, 20, 3}, s[3] = {3840, 64, 1280}; const cuuint32_t b[4] = {32, 32, 2, 3}; make_map(enc, &P.mWqM, P.wqkv, 4, d, s, b, CU_TENSOR_MAP_SWIZZLE_64B); }
  { const cuuint64_t d[4] = {16, 640, 40, 3}, s[3] = {3840, 32, 1280}; const cuuint32_t b[4] = {16, 32, 1, 3}; make_map(enc, &P.mWqL, P.wqkv, 4, d, s, b, CU_TENSOR_MAP_SWIZZLE_32B); }
  { const cuuint64_t d[3] = {16, 640, 40}, s[2] = {1280, 32}; const cuuint32_t b[3] = {16, 80, 5}; make_map(enc, &P.mWo, P.wo, 3, d, s, b, CU_TENSOR_MAP_SWIZZLE_32B); }
  { const cuuint64_t d[3] = {32, 640, 54}, s[2] = {3456, 64}; const cuuint32_t b[3] = {32, 80, 4}; make_map(enc, &P.mW1a, P.w1, 3, d, s, b, CU_TENSOR_MAP_SWIZZLE_64B); }
  { const cuuint64_t d[3] = {32, 640, 54}, s[2] = {3456, 64}; const cuuint32_t b[3] = {32, 80, 3}; make_map(enc, &P.mW1b, P.w1, 3, d, s, b, CU_TENSOR_MAP_SWIZZLE_64B); }
  { const cuuint64_t d[2] = {640, 1728}, s[1] = {1280}; const cuuint32_t b[2] = {64, 112}; make_map(enc, &P.mW2, P.w2, 2, d, s, b, CU_TENSOR_MAP_SWIZZLE_128B); }
  fused_block_kernel<<<SMIDMAP ? 132 : 128, 384, SMEM_BYTES, cudaStreamPerThread>>>(P);
}
```

```cpp
#include <cuda_runtime.h>
#include <cuda.h>
#include <cuda_bf16.h>
#include <stdint.h>

#define PROF 0
#define STATKT 3
#define LASTW 1
#define FORCE_SAFE 0u
#define SMIDMAP 0

__device__ __align__(1024) uint8_t g_kv[32 * 8 * 22528];
__device__ __align__(1024) uint8_t g_o[32 * 4 * 8 * 2560];
__device__ __align__(1024) uint8_t g_h[32 * 4 * 8 * 2560];
__device__ __align__(1024) float2 g_hstat[32 * 4 * 8 * 16];
__device__ __align__(1024) uint8_t g_part[32 * 8 * 8 * 8192];
__device__ __align__(1024) uint8_t g_p89[32 * 4 * 8 * 4096];
__device__ __align__(128) float2 g_xstat[2048];
__device__ __align__(128) float g_csq[16 * 8 * 240];
__device__ __align__(128) float g_cs1[16 * 8 * 224];
__device__ __align__(128) uint32_t g_epoch[128];
#define STAMP(slot)
#define STAMPW(slot)

struct Params {
  CUtensorMap mX, mWqM, mWqL, mWo, mW1a, mW1b, mW2;
  const __nv_bfloat16 *x, *wqkv, *wo, *w1, *w2;
  __nv_bfloat16* out;
};

constexpr uint32_t QST = 47104;
constexpr uint32_t KVB = 22528;
constexpr uint32_t OFF_WOB = 0;
constexpr uint32_t OFF_PRE = 188416;
constexpr uint32_t W2SLOT = 57344;
constexpr uint32_t OFF_MISC = 229376;
constexpr uint32_t OFF_CS = OFF_MISC + 512;
constexpr uint32_t OFF_XS = OFF_CS + 960;
constexpr uint32_t SMEM_BYTES = 232448;

enum {
  B_QFULL = 0, B_KVFULL = 4, B_KVLAND = 8, B_WOB = 12, B_WOB7 = 13, B_BFULL = 14, B_W2FULL = 22, B_PL = 27, B_CS1 = 39,
  B_KVOWN = 40,
  B_Q23 = 42, B_PRE = 43, B_STAT = 44, B_W2D = 45,
  B_QEMPTY = 47, B_ATTP = 51, B_WODP = 52, B_BEMPTY = 53, B_W2E = 61,
  NBAR = 62
};
constexpr uint32_t TAGM = 0x00010001u;
constexpr uint32_t SPIN_MAX = 1u << 18;

__device__ __forceinline__ uint32_t s2u(const void* p) { return (uint32_t)__cvta_generic_to_shared(p); }
__device__ __forceinline__ void mbar_init(uint32_t b, int c) { asm volatile("mbarrier.init.shared::cta.b64 [%0], %1;" ::"r"(b), "r"(c)); }
__device__ __forceinline__ void mbar_expect(uint32_t b, int bytes) { asm volatile("mbarrier.arrive.expect_tx.shared::cta.b64 _, [%0], %1;" ::"r"(b), "r"(bytes) : "memory"); }
__device__ __forceinline__ void mbar_arrive(uint32_t b) { asm volatile("mbarrier.arrive.shared::cta.b64 _, [%0];" ::"r"(b) : "memory"); }
__device__ __forceinline__ void mbar_arrive_pair(uint32_t b) {
  asm volatile("{\n.reg .b32 r;\nmapa.shared::cluster.u32 r, %0, 0;\nmbarrier.arrive.shared::cluster.b64 _, [r];\n"
               "mapa.shared::cluster.u32 r, %0, 1;\nmbarrier.arrive.shared::cluster.b64 _, [r];\n}" ::"r"(b) : "memory");
}
__device__ __forceinline__ void mbar_wait(uint32_t b, uint32_t ph) {
  asm volatile("{\n.reg .pred p;\n.reg .u32 n;\nmov.u32 n, 0;\nW%=:\nmbarrier.try_wait.parity.shared::cta.b64 p, [%0], %1;\n"
               "add.u32 n, n, 1;\nsetp.lt.and.u32 p, n, 0x100000, !p;\n@p bra W%=;\n}" ::"r"(b), "r"(ph) : "memory");
}
__device__ __forceinline__ void tma2d(uint32_t dst, const CUtensorMap* m, int c0, int c1, uint32_t bar) {
  asm volatile("cp.async.bulk.tensor.2d.shared::cluster.global.mbarrier::complete_tx::bytes [%0], [%1, {%3, %4}], [%2];" ::"r"(dst), "l"(m), "r"(bar), "r"(c0), "r"(c1) : "memory");
}
__device__ __forceinline__ void tma2d_mc(uint32_t dst, const CUtensorMap* m, int c0, int c1, uint32_t bar) {
  asm volatile("cp.async.bulk.tensor.2d.shared::cluster.global.mbarrier::complete_tx::bytes.multicast::cluster [%0], [%1, {%3, %4}], [%2], %5;" ::"r"(dst), "l"(m), "r"(bar), "r"(c0), "r"(c1), "h"((uint16_t)3) : "memory");
}
__device__ __forceinline__ void tma3d_mc(uint32_t dst, const CUtensorMap* m, int c0, int c1, int c2, uint32_t bar) {
  asm volatile("cp.async.bulk.tensor.3d.shared::cluster.global.mbarrier::complete_tx::bytes.multicast::cluster [%0], [%1, {%3, %4, %5}], [%2], %6;" ::"r"(dst), "l"(m), "r"(bar), "r"(c0), "r"(c1), "r"(c2), "h"((uint16_t)3) : "memory");
}
__device__ __forceinline__ void tma4d_mc(uint32_t dst, const CUtensorMap* m, int c0, int c1, int c2, int c3, uint32_t bar) {
  asm volatile("cp.async.bulk.tensor.4d.shared::cluster.global.mbarrier::complete_tx::bytes.multicast::cluster [%0], [%1, {%3, %4, %5, %6}], [%2], %7;" ::"r"(dst), "l"(m), "r"(bar), "r"(c0), "r"(c1), "r"(c2), "r"(c3), "h"((uint16_t)3) : "memory");
}
__device__ __forceinline__ void bulk_load(uint32_t dst, const void* src, int bytes, uint32_t bar) {
  asm volatile("cp.async.bulk.shared::cluster.global.mbarrier::complete_tx::bytes [%0], [%1], %2, [%3];" ::"r"(dst), "l"(src), "r"(bytes), "r"(bar) : "memory");
}
__device__ __forceinline__ void tma4d_pf(const CUtensorMap* m, int c0, int c1, int c2, int c3) {
  asm volatile("cp.async.bulk.prefetch.tensor.4d.L2.global [%0, {%1, %2, %3, %4}];" ::"l"(m), "r"(c0), "r"(c1), "r"(c2), "r"(c3) : "memory");
}
__device__ __forceinline__ void l2_prefetch_bulk(const void* p, int bytes) { asm volatile("cp.async.bulk.prefetch.L2.global [%0], %1;" ::"l"(p), "r"(bytes) : "memory"); }
__device__ __forceinline__ void l2_prefetch(const void* p) { asm volatile("prefetch.global.L2 [%0];" ::"l"(p)); }
__device__ __forceinline__ uint32_t ld_flag(const uint32_t* p) { uint32_t v; asm volatile("ld.acquire.gpu.global.u32 %0, [%1];" : "=r"(v) : "l"(p) : "memory"); return v; }
__device__ __forceinline__ void st_flag(uint32_t* p, uint32_t v) { asm volatile("st.relaxed.gpu.global.u32 [%0], %1;" ::"l"(p), "r"(v) : "memory"); }
__device__ __forceinline__ void fence_gpu() { asm volatile("fence.acq_rel.gpu;" ::: "memory"); }
__device__ __forceinline__ void fence_async_smem() { asm volatile("fence.proxy.async.shared::cta;" ::: "memory"); }
__device__ __forceinline__ void fence_async_glob() { asm volatile("fence.proxy.async.global;" ::: "memory"); }
__device__ __forceinline__ uint4 ldcg128(const void* p) { uint4 v; asm volatile("ld.relaxed.gpu.global.v4.u32 {%0,%1,%2,%3}, [%4];" : "=r"(v.x), "=r"(v.y), "=r"(v.z), "=r"(v.w) : "l"(p) : "memory"); return v; }
__device__ __forceinline__ uint4 ldnc128(const void* p) { uint4 v; asm volatile("ld.global.nc.v4.u32 {%0,%1,%2,%3}, [%4];" : "=r"(v.x), "=r"(v.y), "=r"(v.z), "=r"(v.w) : "l"(p)); return v; }
__device__ __forceinline__ uint32_t ldnc32(const void* p) { uint32_t v; asm volatile("ld.global.nc.u32 %0, [%1];" : "=r"(v) : "l"(p)); return v; }
__device__ __forceinline__ uint2 ldcg64(const void* p) { uint2 v; asm volatile("ld.relaxed.gpu.global.v2.u32 {%0,%1}, [%2];" : "=r"(v.x), "=r"(v.y) : "l"(p) : "memory"); return v; }
__device__ __forceinline__ uint32_t ldcg32(const void* p) { uint32_t v; asm volatile("ld.relaxed.gpu.global.u32 %0, [%1];" : "=r"(v) : "l"(p) : "memory"); return v; }
__device__ __forceinline__ uint32_t pack2(float lo, float hi) { uint32_t r; asm("cvt.rn.bf16x2.f32 %0, %1, %2;" : "=r"(r) : "f"(hi), "f"(lo)); return r; }
__device__ __forceinline__ float bf_lo(uint32_t v) { return __uint_as_float(v << 16); }
__device__ __forceinline__ float bf_hi(uint32_t v) { return __uint_as_float(v & 0xffff0000u); }
__device__ __forceinline__ float ex2(float x) { float y; asm("ex2.approx.ftz.f32 %0, %1;" : "=f"(y) : "f"(x)); return y; }
__device__ __forceinline__ float rcp(float x) { float y; asm("rcp.approx.ftz.f32 %0, %1;" : "=f"(y) : "f"(x)); return y; }
__device__ __forceinline__ float tanh_fast(float x) { float y; asm("tanh.approx.f32 %0, %1;" : "=f"(y) : "f"(x)); return y; }
__device__ __forceinline__ void stsm4(uint32_t a, uint32_t r0, uint32_t r1, uint32_t r2, uint32_t r3) {
  asm volatile("stmatrix.sync.aligned.m8n8.x4.shared.b16 [%0], {%1,%2,%3,%4};" ::"r"(a), "r"(r0), "r"(r1), "r"(r2), "r"(r3) : "memory");
}
__device__ __forceinline__ float2 lds64f(uint32_t a) { float2 v; asm volatile("ld.shared.v2.f32 {%0,%1}, [%2];" : "=f"(v.x), "=f"(v.y) : "r"(a)); return v; }
__device__ __forceinline__ constexpr uint64_t desc_hi(uint32_t lbo, uint32_t sbo, uint32_t sw) {
  return ((uint64_t)(lbo >> 4) << 16) | ((uint64_t)(sbo >> 4) << 32) | ((uint64_t)sw << 62);
}
__device__ __forceinline__ uint64_t mkdesc(uint32_t addr, uint64_t hi) { return hi | (uint64_t)((addr & 0x3FFFF) >> 4); }
#define WG_FENCE() asm volatile("wgmma.fence.sync.aligned;" ::: "memory")
#define WG_COMMIT() asm volatile("wgmma.commit_group.sync.aligned;" ::: "memory")
#define WG_WAIT_(n) asm volatile("wgmma.wait_group.sync.aligned " #n ";" ::: "memory")
#define WG_WAIT(n) WG_WAIT_(n)
template <int N> __device__ __forceinline__ void reg_fence(float (&a)[N]) {
#pragma unroll
  for (int i = 0; i < N; i++) asm volatile("" : "+f"(a[i])::"memory");
}

__device__ __forceinline__ void wg_ss192(float (&d)[96], uint64_t da, uint64_t db, int sd) {
  asm volatile("{\n.reg .pred p;\nsetp.ne.b32 p, %98, 0;\n"
  "wgmma.mma_async.sync.aligned.m64n192k16.f32.bf16.bf16 {%0, %1, %2, %3, %4, %5, %6, %7, %8, %9, %10, %11, %12, %13, %14, %15, %16, %17, %18, %19, %20, %21, %22, %23, %24, %25, %26, %27, %28, %29, %30, %31, %32, %33, %34, %35, %36, %37, %38, %39, %40, %41, %42, %43, %44, %45, %46, %47, %48, %49, %50, %51, %52, %53, %54, %55, %56, %57, %58, %59, %60, %61, %62, %63, %64, %65, %66, %67, %68, %69, %70, %71, %72, %73, %74, %75, %76, %77, %78, %79, %80, %81, %82, %83, %84, %85, %86, %87, %88, %89, %90, %91, %92, %93, %94, %95}, %96, %97, p, 1, 1, 0, 1;\n}\n"
  : "+f"(d[0]), "+f"(d[1]), "+f"(d[2]), "+f"(d[3]), "+f"(d[4]), "+f"(d[5]), "+f"(d[6]), "+f"(d[7]), "+f"(d[8]), "+f"(d[9]), "+f"(d[10]), "+f"(d[11]), "+f"(d[12]), "+f"(d[13]), "+f"(d[14]), "+f"(d[15]), "+f"(d[16]), "+f"(d[17]), "+f"(d[18]), "+f"(d[19]), "+f"(d[20]), "+f"(d[21]), "+f"(d[22]), "+f"(d[23]), "+f"(d[24]), "+f"(d[25]), "+f"(d[26]), "+f"(d[27]), "+f"(d[28]), "+f"(d[29]), "+f"(d[30]), "+f"(d[31]), "+f"(d[32]), "+f"(d[33]), "+f"(d[34]), "+f"(d[35]), "+f"(d[36]), "+f"(d[37]), "+f"(d[38]), "+f"(d[39]), "+f"(d[40]), "+f"(d[41]), "+f"(d[42]), "+f"(d[43]), "+f"(d[44]), "+f"(d[45]), "+f"(d[46]), "+f"(d[47]), "+f"(d[48]), "+f"(d[49]), "+f"(d[50]), "+f"(d[51]), "+f"(d[52]), "+f"(d[53]), "+f"(d[54]), "+f"(d[55]), "+f"(d[56]), "+f"(d[57]), "+f"(d[58]), "+f"(d[59]), "+f"(d[60]), "+f"(d[61]), "+f"(d[62]), "+f"(d[63]), "+f"(d[64]), "+f"(d[65]), "+f"(d[66]), "+f"(d[67]), "+f"(d[68]), "+f"(d[69]), "+f"(d[70]), "+f"(d[71]), "+f"(d[72]), "+f"(d[73]), "+f"(d[74]), "+f"(d[75]), "+f"(d[76]), "+f"(d[77]), "+f"(d[78]), "+f"(d[79]), "+f"(d[80]), "+f"(d[81]), "+f"(d[82]), "+f"(d[83]), "+f"(d[84]), "+f"(d[85]), "+f"(d[86]), "+f"(d[87]), "+f"(d[88]), "+f"(d[89]), "+f"(d[90]), "+f"(d[91]), "+f"(d[92]), "+f"(d[93]), "+f"(d[94]), "+f"(d[95]) : "l"(da), "l"(db), "r"(sd));
}
__device__ __forceinline__ void wg_ss48(float (&d)[24], uint64_t da, uint64_t db, int sd) {
  asm volatile("{\n.reg .pred p;\nsetp.ne.b32 p, %26, 0;\n"
  "wgmma.mma_async.sync.aligned.m64n48k16.f32.bf16.bf16 {%0, %1, %2, %3, %4, %5, %6, %7, %8, %9, %10, %11, %12, %13, %14, %15, %16, %17, %18, %19, %20, %21, %22, %23}, %24, %25, p, 1, 1, 0, 1;\n}\n"
  : "+f"(d[0]), "+f"(d[1]), "+f"(d[2]), "+f"(d[3]), "+f"(d[4]), "+f"(d[5]), "+f"(d[6]), "+f"(d[7]), "+f"(d[8]), "+f"(d[9]), "+f"(d[10]), "+f"(d[11]), "+f"(d[12]), "+f"(d[13]), "+f"(d[14]), "+f"(d[15]), "+f"(d[16]), "+f"(d[17]), "+f"(d[18]), "+f"(d[19]), "+f"(d[20]), "+f"(d[21]), "+f"(d[22]), "+f"(d[23]) : "l"(da), "l"(db), "r"(sd));
}
__device__ __forceinline__ void wg_rs80(float (&d)[40], uint32_t a0, uint32_t a1, uint32_t a2, uint32_t a3, uint64_t db, int sd) {
  asm volatile("{\n.reg .pred p;\nsetp.ne.b32 p, %45, 0;\n"
  "wgmma.mma_async.sync.aligned.m64n80k16.f32.bf16.bf16 {%0, %1, %2, %3, %4, %5, %6, %7, %8, %9, %10, %11, %12, %13, %14, %15, %16, %17, %18, %19, %20, %21, %22, %23, %24, %25, %26, %27, %28, %29, %30, %31, %32, %33, %34, %35, %36, %37, %38, %39}, {%40, %41, %42, %43}, %44, p, 1, 1, 1;\n}\n"
  : "+f"(d[0]), "+f"(d[1]), "+f"(d[2]), "+f"(d[3]), "+f"(d[4]), "+f"(d[5]), "+f"(d[6]), "+f"(d[7]), "+f"(d[8]), "+f"(d[9]), "+f"(d[10]), "+f"(d[11]), "+f"(d[12]), "+f"(d[13]), "+f"(d[14]), "+f"(d[15]), "+f"(d[16]), "+f"(d[17]), "+f"(d[18]), "+f"(d[19]), "+f"(d[20]), "+f"(d[21]), "+f"(d[22]), "+f"(d[23]), "+f"(d[24]), "+f"(d[25]), "+f"(d[26]), "+f"(d[27]), "+f"(d[28]), "+f"(d[29]), "+f"(d[30]), "+f"(d[31]), "+f"(d[32]), "+f"(d[33]), "+f"(d[34]), "+f"(d[35]), "+f"(d[36]), "+f"(d[37]), "+f"(d[38]), "+f"(d[39]) : "r"(a0), "r"(a1), "r"(a2), "r"(a3), "l"(db), "r"(sd));
}
__device__ __forceinline__ void wg_rs224(float (&d)[112], uint32_t a0, uint32_t a1, uint32_t a2, uint32_t a3, uint64_t db, int sd) {
  asm volatile("{\n.reg .pred p;\nsetp.ne.b32 p, %117, 0;\n"
  "wgmma.mma_async.sync.aligned.m64n224k16.f32.bf16.bf16 {%0, %1, %2, %3, %4, %5, %6, %7, %8, %9, %10, %11, %12, %13, %14, %15, %16, %17, %18, %19, %20, %21, %22, %23, %24, %25, %26, %27, %28, %29, %30, %31, %32, %33, %34, %35, %36, %37, %38, %39, %40, %41, %42, %43, %44, %45, %46, %47, %48, %49, %50, %51, %52, %53, %54, %55, %56, %57, %58, %59, %60, %61, %62, %63, %64, %65, %66, %67, %68, %69, %70, %71, %72, %73, %74, %75, %76, %77, %78, %79, %80, %81, %82, %83, %84, %85, %86, %87, %88, %89, %90, %91, %92, %93, %94, %95, %96, %97, %98, %99, %100, %101, %102, %103, %104, %105, %106, %107, %108, %109, %110, %111}, {%112, %113, %114, %115}, %116, p, 1, 1, 1;\n}\n"
  : "+f"(d[0]), "+f"(d[1]), "+f"(d[2]), "+f"(d[3]), "+f"(d[4]), "+f"(d[5]), "+f"(d[6]), "+f"(d[7]), "+f"(d[8]), "+f"(d[9]), "+f"(d[10]), "+f"(d[11]), "+f"(d[12]), "+f"(d[13]), "+f"(d[14]), "+f"(d[15]), "+f"(d[16]), "+f"(d[17]), "+f"(d[18]), "+f"(d[19]), "+f"(d[20]), "+f"(d[21]), "+f"(d[22]), "+f"(d[23]), "+f"(d[24]), "+f"(d[25]), "+f"(d[26]), "+f"(d[27]), "+f"(d[28]), "+f"(d[29]), "+f"(d[30]), "+f"(d[31]), "+f"(d[32]), "+f"(d[33]), "+f"(d[34]), "+f"(d[35]), "+f"(d[36]), "+f"(d[37]), "+f"(d[38]), "+f"(d[39]), "+f"(d[40]), "+f"(d[41]), "+f"(d[42]), "+f"(d[43]), "+f"(d[44]), "+f"(d[45]), "+f"(d[46]), "+f"(d[47]), "+f"(d[48]), "+f"(d[49]), "+f"(d[50]), "+f"(d[51]), "+f"(d[52]), "+f"(d[53]), "+f"(d[54]), "+f"(d[55]), "+f"(d[56]), "+f"(d[57]), "+f"(d[58]), "+f"(d[59]), "+f"(d[60]), "+f"(d[61]), "+f"(d[62]), "+f"(d[63]), "+f"(d[64]), "+f"(d[65]), "+f"(d[66]), "+f"(d[67]), "+f"(d[68]), "+f"(d[69]), "+f"(d[70]), "+f"(d[71]), "+f"(d[72]), "+f"(d[73]), "+f"(d[74]), "+f"(d[75]), "+f"(d[76]), "+f"(d[77]), "+f"(d[78]), "+f"(d[79]), "+f"(d[80]), "+f"(d[81]), "+f"(d[82]), "+f"(d[83]), "+f"(d[84]), "+f"(d[85]), "+f"(d[86]), "+f"(d[87]), "+f"(d[88]), "+f"(d[89]), "+f"(d[90]), "+f"(d[91]), "+f"(d[92]), "+f"(d[93]), "+f"(d[94]), "+f"(d[95]), "+f"(d[96]), "+f"(d[97]), "+f"(d[98]), "+f"(d[99]), "+f"(d[100]), "+f"(d[101]), "+f"(d[102]), "+f"(d[103]), "+f"(d[104]), "+f"(d[105]), "+f"(d[106]), "+f"(d[107]), "+f"(d[108]), "+f"(d[109]), "+f"(d[110]), "+f"(d[111]) : "r"(a0), "r"(a1), "r"(a2), "r"(a3), "l"(db), "r"(sd));
}
__device__ __forceinline__ void wg_rs64k(float (&d)[32], uint32_t a0, uint32_t a1, uint32_t a2, uint32_t a3, uint64_t db, int sd) {
  asm volatile("{\n.reg .pred p;\nsetp.ne.b32 p, %37, 0;\n"
  "wgmma.mma_async.sync.aligned.m64n64k16.f32.bf16.bf16 {%0, %1, %2, %3, %4, %5, %6, %7, %8, %9, %10, %11, %12, %13, %14, %15, %16, %17, %18, %19, %20, %21, %22, %23, %24, %25, %26, %27, %28, %29, %30, %31}, {%32, %33, %34, %35}, %36, p, 1, 1, 0;\n}\n"
  : "+f"(d[0]), "+f"(d[1]), "+f"(d[2]), "+f"(d[3]), "+f"(d[4]), "+f"(d[5]), "+f"(d[6]), "+f"(d[7]), "+f"(d[8]), "+f"(d[9]), "+f"(d[10]), "+f"(d[11]), "+f"(d[12]), "+f"(d[13]), "+f"(d[14]), "+f"(d[15]), "+f"(d[16]), "+f"(d[17]), "+f"(d[18]), "+f"(d[19]), "+f"(d[20]), "+f"(d[21]), "+f"(d[22]), "+f"(d[23]), "+f"(d[24]), "+f"(d[25]), "+f"(d[26]), "+f"(d[27]), "+f"(d[28]), "+f"(d[29]), "+f"(d[30]), "+f"(d[31]) : "r"(a0), "r"(a1), "r"(a2), "r"(a3), "l"(db), "r"(sd));
}
__device__ __forceinline__ void wg_rs24(float (&d)[12], uint32_t a0, uint32_t a1, uint32_t a2, uint32_t a3, uint64_t db, int sd) {
  asm volatile("{\n.reg .pred p;\nsetp.ne.b32 p, %17, 0;\n"
  "wgmma.mma_async.sync.aligned.m64n24k16.f32.bf16.bf16 {%0, %1, %2, %3, %4, %5, %6, %7, %8, %9, %10, %11}, {%12, %13, %14, %15}, %16, p, 1, 1, 1;\n}\n"
  : "+f"(d[0]), "+f"(d[1]), "+f"(d[2]), "+f"(d[3]), "+f"(d[4]), "+f"(d[5]), "+f"(d[6]), "+f"(d[7]), "+f"(d[8]), "+f"(d[9]), "+f"(d[10]), "+f"(d[11]) : "r"(a0), "r"(a1), "r"(a2), "r"(a3), "l"(db), "r"(sd));
}
__device__ __forceinline__ void wg_rs128(float (&d)[64], uint32_t a0, uint32_t a1, uint32_t a2, uint32_t a3, uint64_t db, int sd) {
  asm volatile("{\n.reg .pred p;\nsetp.ne.b32 p, %69, 0;\n"
  "wgmma.mma_async.sync.aligned.m64n128k16.f32.bf16.bf16 {%0, %1, %2, %3, %4, %5, %6, %7, %8, %9, %10, %11, %12, %13, %14, %15, %16, %17, %18, %19, %20, %21, %22, %23, %24, %25, %26, %27, %28, %29, %30, %31, %32, %33, %34, %35, %36, %37, %38, %39, %40, %41, %42, %43, %44, %45, %46, %47, %48, %49, %50, %51, %52, %53, %54, %55, %56, %57, %58, %59, %60, %61, %62, %63}, {%64, %65, %66, %67}, %68, p, 1, 1, 1;\n}\n"
  : "+f"(d[0]), "+f"(d[1]), "+f"(d[2]), "+f"(d[3]), "+f"(d[4]), "+f"(d[5]), "+f"(d[6]), "+f"(d[7]), "+f"(d[8]), "+f"(d[9]), "+f"(d[10]), "+f"(d[11]), "+f"(d[12]), "+f"(d[13]), "+f"(d[14]), "+f"(d[15]), "+f"(d[16]), "+f"(d[17]), "+f"(d[18]), "+f"(d[19]), "+f"(d[20]), "+f"(d[21]), "+f"(d[22]), "+f"(d[23]), "+f"(d[24]), "+f"(d[25]), "+f"(d[26]), "+f"(d[27]), "+f"(d[28]), "+f"(d[29]), "+f"(d[30]), "+f"(d[31]), "+f"(d[32]), "+f"(d[33]), "+f"(d[34]), "+f"(d[35]), "+f"(d[36]), "+f"(d[37]), "+f"(d[38]), "+f"(d[39]), "+f"(d[40]), "+f"(d[41]), "+f"(d[42]), "+f"(d[43]), "+f"(d[44]), "+f"(d[45]), "+f"(d[46]), "+f"(d[47]), "+f"(d[48]), "+f"(d[49]), "+f"(d[50]), "+f"(d[51]), "+f"(d[52]), "+f"(d[53]), "+f"(d[54]), "+f"(d[55]), "+f"(d[56]), "+f"(d[57]), "+f"(d[58]), "+f"(d[59]), "+f"(d[60]), "+f"(d[61]), "+f"(d[62]), "+f"(d[63]) : "r"(a0), "r"(a1), "r"(a2), "r"(a3), "l"(db), "r"(sd));
}
__device__ __forceinline__ void wg_rs64(float (&d)[32], uint32_t a0, uint32_t a1, uint32_t a2, uint32_t a3, uint64_t db, int sd) {
  asm volatile("{\n.reg .pred p;\nsetp.ne.b32 p, %37, 0;\n"
  "wgmma.mma_async.sync.aligned.m64n64k16.f32.bf16.bf16 {%0, %1, %2, %3, %4, %5, %6, %7, %8, %9, %10, %11, %12, %13, %14, %15, %16, %17, %18, %19, %20, %21, %22, %23, %24, %25, %26, %27, %28, %29, %30, %31}, {%32, %33, %34, %35}, %36, p, 1, 1, 1;\n}\n"
  : "+f"(d[0]), "+f"(d[1]), "+f"(d[2]), "+f"(d[3]), "+f"(d[4]), "+f"(d[5]), "+f"(d[6]), "+f"(d[7]), "+f"(d[8]), "+f"(d[9]), "+f"(d[10]), "+f"(d[11]), "+f"(d[12]), "+f"(d[13]), "+f"(d[14]), "+f"(d[15]), "+f"(d[16]), "+f"(d[17]), "+f"(d[18]), "+f"(d[19]), "+f"(d[20]), "+f"(d[21]), "+f"(d[22]), "+f"(d[23]), "+f"(d[24]), "+f"(d[25]), "+f"(d[26]), "+f"(d[27]), "+f"(d[28]), "+f"(d[29]), "+f"(d[30]), "+f"(d[31]) : "r"(a0), "r"(a1), "r"(a2), "r"(a3), "l"(db), "r"(sd));
}

__device__ __forceinline__ uint32_t kv_addr(int i) {
  return 94208u + KVB * (uint32_t)((0x541032u >> (4 * i)) & 15u);
}
__device__ __forceinline__ uint32_t w1b_addr(int s) {
  return (s == 3 || s == 4) ? (uint32_t)(s - 3) * 35840u : 102400u + (uint32_t)(s >= 5 ? s - 5 : s) * 35840u;
}
__device__ __forceinline__ void stg128(void* p, uint32_t a, uint32_t b, uint32_t c, uint32_t d) {
  asm volatile("st.global.v4.u32 [%0], {%1,%2,%3,%4};" ::"l"(p), "r"(a), "r"(b), "r"(c), "r"(d) : "memory");
}
__device__ __forceinline__ void stg32(void* p, uint32_t a) { asm volatile("st.global.u32 [%0], %1;" ::"l"(p), "r"(a) : "memory"); }
__device__ __forceinline__ void ld_tile(uint32_t (&a)[20], const uint8_t* p) {
#pragma unroll
  for (int k = 0; k < 5; k++)
    asm volatile("ld.relaxed.gpu.global.v4.u32 {%0,%1,%2,%3}, [%4];" : "=r"(a[4 * k]), "=r"(a[4 * k + 1]), "=r"(a[4 * k + 2]), "=r"(a[4 * k + 3]) : "l"(p + k * 512) : "memory");
}
__device__ __forceinline__ uint32_t tag16(uint32_t v, uint32_t tag) { return (v & ~TAGM) | tag; }
__device__ __forceinline__ float tag32(float v, uint32_t ep) { return __uint_as_float((__float_as_uint(v) & ~3u) | ep); }
__device__ __forceinline__ void fix_tile(uint32_t (&a)[20], const uint8_t* p, uint32_t tag) {
  uint32_t n = 0;
  while (__any_sync(0xffffffffu, (((a[0] ^ tag) | (a[4] ^ tag) | (a[8] ^ tag) | (a[12] ^ tag) | (a[16] ^ tag)) & TAGM) != 0u) && ++n < SPIN_MAX) ld_tile(a, p);
}
__device__ __forceinline__ void probe_wait(uint32_t& ready, int i, const void* p, uint32_t tag) {
  uint32_t n = 0;
  while (!((ready >> i) & 1u) && ++n < SPIN_MAX) ready = __ballot_sync(0xffffffffu, ((ldcg32(p) ^ tag) & TAGM) == 0u);
}
__device__ __forceinline__ float gather16(const float* p, int stride, uint32_t ep) {
  uint32_t v[16], n = 0;
  while (true) {
    uint32_t bad = 0;
#pragma unroll
    for (int i = 0; i < 16; i++) v[i] = ldcg32(p + i * stride);
#pragma unroll
    for (int i = 0; i < 16; i++) bad |= v[i] ^ ep;
    if (!__any_sync(0xffffffffu, (bad & 3u) != 0u) || ++n >= SPIN_MAX) break;
  }
  float s = 0.f;
#pragma unroll
  for (int i = 0; i < 16; i++) s += __uint_as_float(v[i]);
  return s;
}
__device__ __forceinline__ void ld4(uint4 (&v)[4], const uint8_t* p) {
#pragma unroll
  for (int i = 0; i < 4; i++) v[i] = ldcg128(p + i * 512);
}
__device__ __forceinline__ void add4(float (&acc)[32], const uint4 (&v)[4]) {
#pragma unroll
  for (int i = 0; i < 4; i++) {
    acc[8 * i + 0] += bf_lo(v[i].x); acc[8 * i + 1] += bf_hi(v[i].x); acc[8 * i + 2] += bf_lo(v[i].y); acc[8 * i + 3] += bf_hi(v[i].y);
    acc[8 * i + 4] += bf_lo(v[i].z); acc[8 * i + 5] += bf_hi(v[i].z); acc[8 * i + 6] += bf_lo(v[i].w); acc[8 * i + 7] += bf_hi(v[i].w);
  }
}

__device__ __forceinline__ uint64_t desc2(uint32_t lo, uint32_t hi) { uint64_t d; asm("mov.b64 %0, {%1, %2};" : "=l"(d) : "r"(lo), "r"(hi)); return d; }
template <int H>
__device__ __forceinline__ void qk_issue(float (&s)[32], const uint32_t (&q)[24], uint32_t m0, uint32_t m1, uint32_t kd) {
  constexpr int J0 = (H == 0) ? 0 : (H == 1) ? 2 : (H == 2) ? 5 : 7;
  wg_rs64k(s, q[H * 6 + 0], q[H * 6 + 1], q[H * 6 + 2], q[H * 6 + 3], desc2(kd + (0x400000u + J0 * 64), 8u), 0);
  wg_rs64k(s, q[H * 6 + 4], q[H * 6 + 5], m0, m1, desc2(kd + (((10 - J0) * 64u << 16) + (J0 + 2) * 64), 8u), 1);
}
template <int H>
__device__ __forceinline__ void pv_issue(float (&o)[12], const uint32_t (&p)[16], uint32_t kd) {
#pragma unroll
  for (int i = 0; i < 4; i++)
    wg_rs24(o, p[4 * i], p[4 * i + 1], p[4 * i + 2], p[4 * i + 3], desc2(kd + (0x80000u + 640 + 3 * H * 64 + i * 16), 64u), 1);
}
__device__ __forceinline__ void sm_exp(const float (&s)[32], uint32_t (&p)[16], const uint32_t (&nk)[9], uint32_t flip) {
#pragma unroll
  for (int t = 0; t < 8; t++) {
    p[2 * t] = pack2(ex2(s[4 * t]), ex2(s[4 * t + 1])) & (~nk[t + 1] ^ flip);
    p[2 * t + 1] = pack2(ex2(s[4 * t + 2]), ex2(s[4 * t + 3])) & (~nk[t] ^ flip);
  }
#pragma unroll
  for (int i = 0; i < 16; i++) asm volatile("" : "+r"(p[i])::"memory");
}
__device__ __forceinline__ void mma16816(float* d, uint32_t a0, uint32_t a1, uint32_t a2, uint32_t a3, uint32_t b0, uint32_t b1) {
  asm volatile("mma.sync.aligned.m16n8k16.row.col.f32.bf16.bf16.f32 {%0,%1,%2,%3}, {%4,%5,%6,%7}, {%8,%9}, {%0,%1,%2,%3};"
               : "+f"(d[0]), "+f"(d[1]), "+f"(d[2]), "+f"(d[3]) : "r"(a0), "r"(a1), "r"(a2), "r"(a3), "r"(b0), "r"(b1));
}
template <int H>
__device__ __forceinline__ void safe_head(float (&o)[12], const uint32_t (&q)[24], uint32_t sb, uint32_t seq, int nit, int dthr, int lane) {
  constexpr int J0 = (H == 0) ? 0 : (H == 1) ? 2 : (H == 2) ? 5 : 7;
  float m0 = -INFINITY, m1 = -INFINITY;
#pragma unroll
  for (int i = 0; i < 12; i++) o[i] = 0.f;
#pragma unroll 1
  for (int st = 0; st < 4 * nit; st++) {
    const uint32_t a = sb + kv_addr((seq >> (st & 28)) & 15) + (st & 3) * 256 + (lane & 15) * 16, a2 = a + (lane >> 4) * 1024;
    uint32_t b[6];
    asm volatile("ldmatrix.sync.aligned.m8n8.x4.shared.b16 {%0,%1,%2,%3}, [%4];" : "=r"(b[0]), "=r"(b[1]), "=r"(b[2]), "=r"(b[3]) : "r"(a2 + J0 * 1024) : "memory");
    asm volatile("ldmatrix.sync.aligned.m8n8.x2.shared.b16 {%0,%1}, [%2];" : "=r"(b[4]), "=r"(b[5]) : "r"(a + (J0 + 2) * 1024) : "memory");
    float s[8];
#pragma unroll
    for (int i = 0; i < 8; i++) s[i] = 0.f;
#pragma unroll
    for (int t = 0; t < 2; t++) {
      mma16816(&s[4 * t], q[6 * H], q[6 * H + 1], q[6 * H + 2], q[6 * H + 3], b[t], b[2 + t]);
      mma16816(&s[4 * t], q[6 * H + 4], q[6 * H + 5], 0u, 0u, b[4 + t], 0u);
    }
    if (st < 4 || st >= 16) {
      const int z = dthr - (st & 3) * 16;
#pragma unroll
      for (int i = 0; i < 8; i++)
        if (((i >> 2) * 8 + (i & 1) - (i & 2) * 4 <= z) != (st < 4)) s[i] = -INFINITY;
    }
    float n0 = fmaxf(fmaxf(s[0], s[1]), fmaxf(s[4], s[5])), n1 = fmaxf(fmaxf(s[2], s[3]), fmaxf(s[6], s[7]));
    n0 = fmaxf(n0, __shfl_xor_sync(0xffffffffu, n0, 1));
    n1 = fmaxf(n1, __shfl_xor_sync(0xffffffffu, n1, 1));
    n0 = fmaxf(m0, fmaxf(n0, __shfl_xor_sync(0xffffffffu, n0, 2)));
    n1 = fmaxf(m1, fmaxf(n1, __shfl_xor_sync(0xffffffffu, n1, 2)));
    const float al0 = ex2(m0 - n0), al1 = ex2(m1 - n1);
    m0 = n0;
    m1 = n1;
    const uint32_t p0 = pack2(ex2(s[0] - n0), ex2(s[1] - n0)), p1 = pack2(ex2(s[2] - n1), ex2(s[3] - n1));
    const uint32_t p2 = pack2(ex2(s[4] - n0), ex2(s[5] - n0)), p3 = pack2(ex2(s[6] - n1), ex2(s[7] - n1));
    asm volatile("ldmatrix.sync.aligned.m8n8.x4.trans.shared.b16 {%0,%1,%2,%3}, [%4];" : "=r"(b[0]), "=r"(b[1]), "=r"(b[2]), "=r"(b[3]) : "r"(a2 + (10 + 3 * H) * 1024) : "memory");
    asm volatile("ldmatrix.sync.aligned.m8n8.x2.trans.shared.b16 {%0,%1}, [%2];" : "=r"(b[4]), "=r"(b[5]) : "r"(a + (12 + 3 * H) * 1024) : "memory");
#pragma unroll
    for (int t = 0; t < 3; t++) {
      o[4 * t] *= al0; o[4 * t + 1] *= al0; o[4 * t + 2] *= al1; o[4 * t + 3] *= al1;
      mma16816(&o[4 * t], p0, p1, p2, p3, b[2 * t], b[2 * t + 1]);
    }
  }
}
#define ATT_STEP(HQ, sq, kq, HP, op, pp, kv, sc, pc, W) do { \
  WG_FENCE(); qk_issue<HQ>(sq, q, qm[2 * HQ], qm[2 * HQ + 1], kq); WG_COMMIT(); WG_WAIT(1); pv_issue<HP>(op, pp, kv); WG_COMMIT(); \
  sm_exp(sc, pc, nk, flip); WG_WAIT(W); reg_fence(sq); } while (0)
__device__ __forceinline__ uint32_t bmul2(uint32_t a, uint32_t b) { uint32_t d; asm("mul.rn.bf16x2 %0, %1, %2;" : "=r"(d) : "r"(a), "r"(b)); return d; }
__device__ __forceinline__ uint32_t badd2(uint32_t a, uint32_t b) { uint32_t d; asm("add.rn.bf16x2 %0, %1, %2;" : "=r"(d) : "r"(a), "r"(b)); return d; }
__device__ __forceinline__ uint32_t bfma2(uint32_t a, uint32_t b, uint32_t c) { uint32_t d; asm("fma.rn.bf16x2 %0, %1, %2, %3;" : "=r"(d) : "r"(a), "r"(b), "r"(c)); return d; }

__device__ __forceinline__ void store_partial64(const float* a, uint8_t* dst, uint32_t tag) {
#pragma unroll
  for (int i = 0; i < 4; i++) {
    uint4 v;
    v.x = tag16(pack2(a[8 * i + 0], a[8 * i + 1]), tag);
    v.y = pack2(a[8 * i + 2], a[8 * i + 3]);
    v.z = pack2(a[8 * i + 4], a[8 * i + 5]);
    v.w = pack2(a[8 * i + 6], a[8 * i + 7]);
    *reinterpret_cast<uint4*>(dst + i * 512) = v;
  }
}

__global__ void __cluster_dims__(2, 1, 1) __launch_bounds__(384, 1) fused_block_kernel(const __grid_constant__ Params P) {
  extern __shared__ __align__(1024) uint8_t smem[];
  const uint32_t sb = s2u(smem);
  const int tid = threadIdx.x, lane = tid & 31, warp = __shfl_sync(0xffffffffu, tid >> 5, 0);
  const uint32_t rank = blockIdx.x & 1;
  const int rb = blockIdx.x & 15, c = blockIdx.x >> 4;
  const int tile = rb * 8 + c;
  const uint32_t bars = sb + OFF_MISC;
#define BAR(i) (bars + 8u * (uint32_t)(i))
  const int odd = c & 1;
  const int mainch = (c >> 1) * 5 + (odd ? 3 : 0), leftch = (c >> 1) * 10 + (odd ? 5 : 4);
  if (warp >= 8) asm volatile("setmaxnreg.dec.sync.aligned.u32 56;");
  if (lane == 0) {
    if (warp == 8) {
      asm volatile("prefetch.tensormap [%0];" ::"l"(&P.mWqM) : "memory");
      asm volatile("prefetch.tensormap [%0];" ::"l"(&P.mWqL) : "memory");
    } else {
      const int i0 = (warp < 8 ? warp + 3 : warp - 9) * 6;
#pragma unroll
      for (int u = 0; u < 6; u++) {
        const int i = i0 + u;
        if (i < 64) mbar_init(BAR(i), i < B_KVOWN ? 1 : i < B_Q23 ? 4 : i < B_QEMPTY ? 8 : 16);
      }
    }
    asm volatile("fence.mbarrier_init.release.cluster;" ::: "memory");
    if (warp == 9) {
      mbar_expect(BAR(B_QFULL), QST);
      tma2d(sb, &P.mX, 0, rb * 128, BAR(B_QFULL));
    }
  }
  __syncwarp();
  if (warp == 8) STAMPW(11);
  asm volatile("barrier.cluster.arrive.relaxed.aligned;" ::: "memory");
  if (warp == 8) {
    asm volatile("barrier.cluster.wait.acquire.aligned;\nbar.arrive 1, 384;" ::: "memory");
    STAMPW(8);
    if (lane == 0) {
#pragma unroll 1
      for (int kt = 0; kt < 4; kt++) {
        const uint32_t a = sb + kt * QST, fb = BAR(B_QFULL + kt);
        if (kt) mbar_expect(fb, QST);
        tma4d_mc(a + 16384 + rank * 12288, &P.mWqM, 0, kt * 64 + rank * 32, mainch, 0, fb);
        tma4d_mc(a + 40960 + rank * 3072, &P.mWqL, 0, kt * 64 + rank * 32, leftch, 0, fb);
        if (kt) tma2d(a, &P.mX, kt * 64, rb * 128, fb);
        if (kt == 0) STAMPW(10);
      }
    }
    __syncwarp();
    STAMPW(9);
  } else {
    asm volatile("bar.sync 1, 384;" ::: "memory");
  }
  const int sc = (27 * c + 3) >> 2;

  if (warp >= 8) {
    const uint32_t epoch = ldcg32(&g_epoch[tile]) + 1u;
    const uint32_t ep = epoch & 3u, tag = (epoch & 1u) | ((epoch & 2u) << 15);
    if (warp == 8) {
      if (lane == 0) {
#pragma unroll 1
        for (int kt = 4; kt < 10; kt++) {
          const int st = kt & 3;
          mbar_wait(BAR(B_QEMPTY + st), ((kt >> 2) - 1) & 1);
          const uint32_t a = sb + st * QST, fb = BAR(B_QFULL + st);
          mbar_expect(fb, QST);
          tma4d_mc(a + 16384 + rank * 12288, &P.mWqM, 0, kt * 64 + rank * 32, mainch, 0, fb);
          tma4d_mc(a + 40960 + rank * 3072, &P.mWqL, 0, kt * 64 + rank * 32, leftch, 0, fb);
          tma2d(a, &P.mX, kt * 64, rb * 128, fb);
        }
        const CUtensorMap* mW1 = rank ? &P.mW1b : &P.mW1a;
        asm volatile("prefetch.tensormap [%0];" ::"l"(&P.mWo) : "memory");
        asm volatile("prefetch.tensormap [%0];" ::"l"(mW1) : "memory");
        asm volatile("prefetch.tensormap [%0];" ::"l"(&P.mW2) : "memory");
        mbar_wait(BAR(B_QEMPTY + 0), 0);
        mbar_wait(BAR(B_QEMPTY + 1), 0);
        if (rb) mbar_wait(BAR(B_KVFULL + 3), 0);
        mbar_expect(BAR(B_WOB), 89600);
#pragma unroll 1
        for (int i = 0; i < 4 - (int)rank; i++) {
          const int pos = rank * 4 + i;
          tma3d_mc(sb + OFF_WOB + pos * 12800, &P.mWo, 0, ((c + pos) & 7) * 80, c * 5, BAR(B_WOB));
        }
#pragma unroll 1
        for (int s = 0; s < 8; s++) {
          if (s == 0) {
            mbar_wait(BAR(B_ATTP), 0);
            mbar_expect(BAR(B_WOB7), 12800);
            if (rank) tma3d_mc(sb + OFF_WOB + 7 * 12800, &P.mWo, 0, ((c + 7) & 7) * 80, c * 5, BAR(B_WOB7));
          } else if (s == 3) mbar_wait(BAR(B_WODP), 0);
          else if (s >= 5) mbar_wait(BAR(B_BEMPTY + s - 5), 0);
          const uint32_t fb = BAR(B_BFULL + s);
          mbar_expect(fb, 35840);
          tma3d_mc(sb + w1b_addr(s) + rank * 20480, mW1, 0, ((c + s) & 7) * 80, sc + rank * 4, fb);
        }
#pragma unroll 1
        for (int s = 0; s < 5; s++) {
          mbar_wait(s < 4 ? BAR(B_BEMPTY + 4 + s) : BAR(B_W2E), 0);
          const uint32_t dst = sb + (s & 3) * W2SLOT + rank * 14336, fb = BAR(B_W2FULL + s);
          const int bx0 = s == 0 ? 8 : ((c + 2 * s - 1) & 7), bx1 = s == 0 ? 9 : ((c + 2 * s) & 7);
          mbar_expect(fb, W2SLOT);
          tma2d_mc(dst, &P.mW2, bx0 * 64, sc * 32 + rank * 112, fb);
          tma2d_mc(dst + 28672, &P.mW2, bx1 * 64, sc * 32 + rank * 112, fb);
        }
      }
      __syncwarp();
    } else {
      if (warp == 11) {
        mbar_wait(BAR(B_QFULL + 3), 0);
        if (lane == 0) {
          l2_prefetch_bulk(reinterpret_cast<const uint8_t*>(P.wo) + tile * 6400, 6400);
          l2_prefetch_bulk(reinterpret_cast<const uint8_t*>(P.w1) + tile * 17280, 17280);
          l2_prefetch_bulk(reinterpret_cast<const uint8_t*>(P.w2) + tile * 17280, 17280);
        }
        mbar_wait(BAR(B_PRE), 0);
#pragma unroll 1
        for (int q = lane; q < 60; q += 32) {
          float4 a = make_float4(0.f, 0.f, 0.f, 0.f);
#pragma unroll
          for (int i = 0; i < 8; i++) {
            const float4 v = *reinterpret_cast<const float4*>(smem + OFF_PRE + i * 960 + q * 16);
            a.x += v.x; a.y += v.y; a.z += v.z; a.w += v.w;
          }
          *reinterpret_cast<float4*>(&g_csq[tile * 240 + q * 4]) = make_float4(tag32(a.x, ep), tag32(a.y, ep), tag32(a.z, ep), tag32(a.w, ep));
        }
        __syncwarp();
        STAMPW(0);
        mbar_wait(BAR(B_Q23), 0);
      } else {
        mbar_wait(BAR(B_KVOWN + warp - 9), 0);
        if (lane == 0) {
          asm volatile("cp.async.bulk.global.shared::cta.bulk_group [%0], [%1], %2;\ncp.async.bulk.commit_group;"
                       ::"l"(g_kv + (size_t)((rb * 2 + warp - 9) * 8 + c) * KVB), "r"(sb + kv_addr(warp - 5)), "r"(KVB) : "memory");
        }
      }
#pragma unroll 1
      for (int bi = warp == 9 ? 2 : warp == 10 ? 3 : 1; bi >= 0; bi -= (warp == 9 ? 2 : 4)) {
        const int blk = 2 * rb - 4 + bi;
        if (blk < 0) continue;
        const uint8_t* src = g_kv + (size_t)(blk * 8 + c) * KVB;
        const uint32_t dst = sb + kv_addr(bi);
        uint32_t n = 0, ph = 0;
        while (!__all_sync(0xffffffffu, ((ldcg32(src + lane * 704 + 692) ^ tag) & TAGM) == 0u) && ++n < SPIN_MAX) {}
        if (warp == 9 && bi == 2) STAMPW(3);
        while (true) {
          if (lane == 0) {
            fence_async_glob();
            mbar_expect(BAR(B_KVLAND + bi), KVB);
            bulk_load(dst, src, KVB, BAR(B_KVLAND + bi));
          }
          mbar_wait(BAR(B_KVLAND + bi), ph);
          ph ^= 1u;
          uint32_t bad = 0;
#pragma unroll 11
          for (int i = 0; i < 44; i++) {
            uint32_t v;
            asm volatile("ld.shared.u32 %0, [%1];" : "=r"(v) : "r"(dst + (i * 32 + lane) * 16 + 4) : "memory");
            bad |= v ^ tag;
          }
          if (!__any_sync(0xffffffffu, (bad & TAGM) != 0u) || ++n >= SPIN_MAX) break;
        }
        if (lane == 0) {
          asm volatile("cp.async.bulk.wait_group.read 0;" ::: "memory");
          mbar_arrive(BAR(B_KVFULL + bi));
        }
        if (warp == 9 && bi == 2) STAMPW(5);
      }
      __syncwarp();
      asm volatile("barrier.cluster.wait.acquire.aligned;" ::: "memory");
      if (warp == 10) {
        const int col = sc * 32 + lane * 8;
        const uint8_t* wb = reinterpret_cast<const uint8_t*>(P.w1) + (size_t)rb * 40 * 3456 + (size_t)col * 2;
        float acc[8];
#pragma unroll
        for (int i = 0; i < 8; i++) acc[i] = 0.f;
        if (lane < 28 && col < 1728) {
#pragma unroll 1
          for (int i = 0; i < 40; i += 8) {
            uint4 v[8];
#pragma unroll
            for (int u = 0; u < 8; u++) v[u] = __ldg(reinterpret_cast<const uint4*>(wb + (size_t)(i + u) * 3456));
#pragma unroll
            for (int u = 0; u < 8; u++) {
              acc[0] += bf_lo(v[u].x); acc[1] += bf_hi(v[u].x); acc[2] += bf_lo(v[u].y); acc[3] += bf_hi(v[u].y);
              acc[4] += bf_lo(v[u].z); acc[5] += bf_hi(v[u].z); acc[6] += bf_lo(v[u].w); acc[7] += bf_hi(v[u].w);
            }
          }
        }
        if (lane < 28) {
          float4* dst = reinterpret_cast<float4*>(&g_cs1[tile * 224 + lane * 8]);
          dst[0] = make_float4(tag32(acc[0], ep), tag32(acc[1], ep), tag32(acc[2], ep), tag32(acc[3], ep));
          dst[1] = make_float4(tag32(acc[4], ep), tag32(acc[5], ep), tag32(acc[6], ep), tag32(acc[7], ep));
        }
        STAMPW(4);
      } else if (warp == 11) {
        mbar_wait(BAR(B_ATTP), 0);
#pragma unroll 1
        for (int u = lane; u < 224; u += 32) *reinterpret_cast<float*>(smem + OFF_XS + u * 4) = gather16(g_cs1 + c * 224 + u, 1792, ep);
        __syncwarp();
        if (lane == 0) mbar_arrive(BAR(B_CS1));
        STAMPW(1);
      }
    }
    mbar_wait(BAR(B_W2D), 0);
    if (warp == 9 || warp == 10) {
      const uint8_t* src = g_part + (size_t)((rb * 2 + warp - 9) * 8 + c) * 65536;
      const uint8_t* pw = src + ((c - 1 - (lane >> 2)) & 7) * 8192 + (lane & 3) * 2048 + 2032;
      uint32_t ready = 0;
#pragma unroll 1
      for (int u = 0; u < 6; u++) {
        if (u == 3) mbar_wait(BAR(B_W2D + 1), 0);
        uint32_t n = 0;
        while (((~ready >> (4 * u)) & 15u) && ++n < SPIN_MAX) ready = __ballot_sync(0xffffffffu, ((ldcg32(pw) ^ tag) & TAGM) == 0u);
        if (lane == 0) {
          const uint32_t fb = BAR(B_PL + 2 * u + warp - 9);
          fence_async_glob();
          mbar_expect(fb, 8192);
          bulk_load(sb + W2SLOT + u * 16384 + (u >= 3 ? 8192 : 0) + (warp - 9) * 8192, src + ((c - 1 - u) & 7) * 8192, 8192, fb);
        }
      }
    } else {
#pragma unroll 1
      for (int j = warp == 8 ? 0 : 4, je = j + 4; j < je; j++) {
        uint4 v8[8], hv;
        uint32_t n = 0, bad;
        const uint8_t* p8 = g_p89 + (size_t)tile * 32768 + j * 512 + lane * 16;
        const uint8_t* ph = g_h + (size_t)tile * 20480 + (32 + j) * 512 + lane * 16;
        asm volatile("" : "+l"(p8), "+l"(ph));
        do {
#pragma unroll
          for (int u = 0; u < 8; u++) v8[u] = ldcg128(p8 + u * 4096);
          hv = ldcg128(ph);
          bad = hv.x ^ tag;
#pragma unroll
          for (int u = 0; u < 8; u++) bad |= v8[u].x ^ tag;
        } while (__any_sync(0xffffffffu, (bad & TAGM) != 0u) && ++n < SPIN_MAX);
        float f[8] = {bf_lo(hv.x), bf_hi(hv.x), bf_lo(hv.y), bf_hi(hv.y), bf_lo(hv.z), bf_hi(hv.z), bf_lo(hv.w), bf_hi(hv.w)};
#pragma unroll
        for (int u = 0; u < 8; u++) {
          f[0] += bf_lo(v8[u].x); f[1] += bf_hi(v8[u].x); f[2] += bf_lo(v8[u].y); f[3] += bf_hi(v8[u].y);
          f[4] += bf_lo(v8[u].z); f[5] += bf_hi(v8[u].z); f[6] += bf_lo(v8[u].w); f[7] += bf_hi(v8[u].w);
        }
        uint8_t* op = reinterpret_cast<uint8_t*>(P.out) + (size_t)(tile * 16 + (lane >> 2)) * 1280 + 1024 + j * 32 + (lane & 3) * 4;
        *reinterpret_cast<uint32_t*>(op) = pack2(f[0], f[1]);
        *reinterpret_cast<uint32_t*>(op + 8 * 1280) = pack2(f[2], f[3]);
        *reinterpret_cast<uint32_t*>(op + 16) = pack2(f[4], f[5]);
        *reinterpret_cast<uint32_t*>(op + 8 * 1280 + 16) = pack2(f[6], f[7]);
      }
      if (warp == 11) STAMPW(2);
      if (warp == 11 && lane == 0) st_flag(&g_epoch[tile], epoch);
    }
  } else {
    const int r = warp >> 2, w = warp & 3, gq = lane >> 2, tq = lane & 3;
    asm volatile("setmaxnreg.inc.sync.aligned.u32 224;");
    STAMP(4);
    uint4 xv[5], wv[5];
    uint32_t ep;
    const int b = rb * 2 + r;
    uint32_t q[24], qm[8], tag;
    STAMP(0);
    {
      float accM[96], accL[24];
      uint2 s0u, s1u;
#define QKV_ISSUE(kt) do { \
        const uint32_t a = sb + ((kt) & 3) * QST; \
        const uint64_t da = mkdesc(a + r * 8192, desc_hi(16, 1024, 1)); \
        const uint64_t dm = mkdesc(a + 16384, desc_hi(2048, 512, 2)); \
        const uint64_t dl = mkdesc(a + 40960, desc_hi(1024, 256, 3)); \
        mbar_wait(BAR(B_QFULL + ((kt) & 3)), ((kt) >> 2) & 1); \
        WG_FENCE(); \
        _Pragma("unroll") for (int k = 0; k < 4; k++) { \
          wg_ss192(accM, da + k * 2, dm + (k >> 1) * 768 + (k & 1) * 64, (kt) | k); \
          wg_ss48(accL, da + k * 2, dl + (k >> 1) * 192 + (k & 1) * 32, (kt) | k); \
        } \
        WG_COMMIT(); } while (0)
      QKV_ISSUE(0);
      STAMP(1);
      {
          const uint8_t* xb = reinterpret_cast<const uint8_t*>(P.x) + (size_t)(rb * 128 + c * 16 + warp * 2 + (lane >> 4)) * 1280 + (lane & 15) * 16;
          const int cl = lane < 30 ? lane : 29;
          const uint8_t* wb = reinterpret_cast<const uint8_t*>(P.wqkv) + (size_t)(rb * 40 + warp * 5) * 3840 + (cl / 10) * 1280 + c * 160 + (cl % 10) * 16;
#pragma unroll
          for (int i = 0; i < 5; i++) wv[i] = ldnc128(wb + i * 3840);
#pragma unroll
          for (int i = 0; i < 5; i++) xv[i] = ldnc128(xb + i * 256);
          ep = ldcg32(&g_epoch[tile]);
      }
#pragma unroll 1
      for (int kt = 1; kt < 10; kt++) {
        QKV_ISSUE(kt);
        if (kt == STATKT) {
          STAMP(19);
#pragma unroll
          for (int i = 0; i < 5; i++) asm volatile("" : "+r"(wv[i].x), "+r"(wv[i].y), "+r"(wv[i].z), "+r"(wv[i].w));
          float a[8];
#pragma unroll
          for (int i = 0; i < 8; i++) a[i] = 0.f;
#pragma unroll
          for (int u = 0; u < 5; u++) {
            a[0] += bf_lo(wv[u].x); a[1] += bf_hi(wv[u].x); a[2] += bf_lo(wv[u].y); a[3] += bf_hi(wv[u].y);
            a[4] += bf_lo(wv[u].z); a[5] += bf_hi(wv[u].z); a[6] += bf_lo(wv[u].w); a[7] += bf_hi(wv[u].w);
          }
          if (lane < 30) {
            float4* dst = reinterpret_cast<float4*>(smem + OFF_PRE + warp * 960 + lane * 32);
            dst[0] = make_float4(a[0], a[1], a[2], a[3]);
            dst[1] = make_float4(a[4], a[5], a[6], a[7]);
          }
          __syncwarp();
          if (lane == 0) mbar_arrive(BAR(B_PRE));
          STAMP(5);
        } else if (kt == STATKT + 1) {
          asm volatile("" : "+r"(ep));
#pragma unroll
          for (int i = 0; i < 5; i++) asm volatile("" : "+r"(xv[i].x), "+r"(xv[i].y), "+r"(xv[i].z), "+r"(xv[i].w));
          ep = (ep + 1u) & 3u;
          float s = 0.f;
#pragma unroll
          for (int i = 0; i < 5; i++)
            s += ((bf_lo(xv[i].x) + bf_hi(xv[i].x)) + (bf_lo(xv[i].y) + bf_hi(xv[i].y))) + ((bf_lo(xv[i].z) + bf_hi(xv[i].z)) + (bf_lo(xv[i].w) + bf_hi(xv[i].w)));
#pragma unroll
          for (int o = 8; o; o >>= 1) s += __shfl_xor_sync(0xffffffffu, s, o);
          const float mean = s * (1.f / 640.f);
          float m2 = 0.f;
#pragma unroll
          for (int i = 0; i < 5; i++) {
            const uint32_t u[4] = {xv[i].x, xv[i].y, xv[i].z, xv[i].w};
#pragma unroll
            for (int j = 0; j < 4; j++) {
              const float d0 = bf_lo(u[j]) - mean, d1 = bf_hi(u[j]) - mean;
              m2 += d0 * d0 + d1 * d1;
            }
          }
#pragma unroll
          for (int o = 8; o; o >>= 1) m2 += __shfl_xor_sync(0xffffffffu, m2, o);
          if ((lane & 15) == 0)
            g_xstat[rb * 128 + c * 16 + warp * 2 + (lane >> 4)] = make_float2(mean, tag32(rsqrtf(m2 * (1.f / 640.f) + 1e-5f), ep));
        } else if (kt == STATKT + 2) {
          asm volatile("barrier.cluster.wait.acquire.aligned;" ::: "memory");
        } else
        if (kt == 9) {
          const float cs = gather16(g_csq + c * 240 + (tid < 240 ? tid : 239), 1920, ep);
          if (tid < 240) *reinterpret_cast<float*>(smem + OFF_CS + tid * 4) = cs;
          uint32_t n = 0;
          do {
            s0u = ldcg64(&g_xstat[b * 64 + w * 16 + gq]);
            s1u = ldcg64(&g_xstat[b * 64 + w * 16 + gq + 8]);
          } while (__any_sync(0xffffffffu, (((s0u.y ^ ep) | (s1u.y ^ ep)) & 3u) != 0u) && ++n < SPIN_MAX);
          if (lane == 0) mbar_arrive(BAR(B_STAT));
        }
        WG_WAIT(1);
        if (lane == 0) {
          mbar_arrive_pair(BAR(B_QEMPTY + ((kt - 1) & 3)));
          if (kt == 8) mbar_arrive(BAR(B_Q23));
        }
      }
      WG_WAIT(0);
      reg_fence(accM); reg_fence(accL);
      if (lane == 0) mbar_arrive_pair(BAR(B_QEMPTY + 1));
      STAMP(2);
      tag = (ep & 1u) | ((ep & 2u) << 15);
      mbar_wait(BAR(B_STAT), 0);
      mbar_wait(BAR(B_Q23), 0);
      const float2 s0 = make_float2(__uint_as_float(s0u.x), __uint_as_float(s0u.y)), s1 = make_float2(__uint_as_float(s1u.x), __uint_as_float(s1u.y));
      const uint32_t km = tq == 1 ? ~TAGM : 0xffffffffu, kt1 = tq == 1 ? tag : 0u;
      const uint32_t csM = sb + OFF_CS + (odd ? 64 : 0) + tq * 8, csL = sb + OFF_CS + (odd ? 0 : 256) + tq * 8;
      const uint32_t kvo = sb + kv_addr(4 + r) + (uint32_t)(w * 16 + ((lane >> 3) & 1) * 8 + (lane & 7)) * 16u + (uint32_t)(lane >> 4) * 1024u;
      const float qs = 0.22360679774997896f * 1.4426950408889634f;
      const bool lo = tq < 2;
      uint32_t qj[20], kj[20];
#pragma unroll
      for (int mm = 0; mm < 3; mm++) {
        const int mat = (mm + 1) % 3;
        const float r0 = mat == 0 ? s0.y * qs : s0.y, r1 = mat == 0 ? s1.y * qs : s1.y;
        const float n0 = -s0.x * r0, n1 = -s1.x * r1;
        uint32_t pk[20];
#pragma unroll
        for (int t = 0; t < 10; t++) {
          const float* a = t < 8 ? &accM[(mat * 8 + t) * 4] : &accL[(mat * 2 + t - 8) * 4];
          const float2 cs = lds64f(t < 8 ? csM + mat * 320 + t * 32 : csL + mat * 320 + (t - 8) * 32);
          pk[2 * t] = pack2(fmaf(a[0], r0, cs.x * n0), fmaf(a[1], r0, cs.y * n0));
          pk[2 * t + 1] = pack2(fmaf(a[2], r1, cs.x * n1), fmaf(a[3], r1, cs.y * n1));
        }
#pragma unroll
        for (int i = 0; i < 20; i++) qj[i] = odd ? pk[(i + 16) % 20] : pk[i];
        if (mat == 1) {
#pragma unroll
          for (int i = 0; i < 20; i++) kj[i] = (qj[i] & km) | kt1;
#pragma unroll
          for (int t = 0; t < 10; t += 2) stsm4(kvo + t * 1024, kj[2 * t], kj[2 * t + 1], kj[2 * t + 2], kj[2 * t + 3]);
        }
        if (mat == 2) {
          const uint32_t one = (tq & 1) ? 0u : 0x3f80u;
          uint32_t vv[24];
#pragma unroll
          for (int hp = 0; hp < 2; hp++) {
            const int j = hp * 10;
#pragma unroll
            for (int i = 0; i < 4; i++) { vv[hp * 12 + i] = qj[j + i]; vv[hp * 12 + 8 + i] = qj[j + 6 + i]; }
            vv[hp * 12 + 4] = lo ? qj[j + 4] : one; vv[hp * 12 + 5] = lo ? qj[j + 5] : one;
            vv[hp * 12 + 6] = lo ? one : qj[j + 4]; vv[hp * 12 + 7] = lo ? one : qj[j + 5];
          }
#pragma unroll
          for (int i = 0; i < 24; i++) vv[i] = (vv[i] & km) | kt1;
#pragma unroll
          for (int t = 0; t < 6; t++) stsm4(kvo + 10240 + t * 2048, vv[4 * t], vv[4 * t + 1], vv[4 * t + 2], vv[4 * t + 3]);
          fence_async_smem();
          __syncwarp();
          if (lane == 0) mbar_arrive(BAR(B_KVOWN + r));
        }
      }
#pragma unroll
      for (int hp = 0; hp < 2; hp++) {
        const int j = hp * 10;
        q[hp * 12 + 0] = qj[j + 0]; q[hp * 12 + 1] = qj[j + 1]; q[hp * 12 + 2] = qj[j + 2]; q[hp * 12 + 3] = qj[j + 3];
        q[hp * 12 + 4] = lo ? qj[j + 4] : 0u; q[hp * 12 + 5] = lo ? qj[j + 5] : 0u;
        q[hp * 12 + 6] = lo ? 0u : qj[j + 4]; q[hp * 12 + 7] = lo ? 0u : qj[j + 5];
        q[hp * 12 + 8] = qj[j + 6]; q[hp * 12 + 9] = qj[j + 7]; q[hp * 12 + 10] = qj[j + 8]; q[hp * 12 + 11] = qj[j + 9];
      }
#pragma unroll
      for (int h = 0; h < 4; h++) {
        const int j = (h >> 1) * 10 + (h & 1) * 4;
        const uint32_t d0 = bfma2(q[6 * h + 4], kj[j + 4], bfma2(q[6 * h + 2], kj[j + 2], bmul2(q[6 * h], kj[j])));
        const uint32_t d1 = bfma2(q[6 * h + 5], kj[j + 5], bfma2(q[6 * h + 3], kj[j + 3], bmul2(q[6 * h + 1], kj[j + 1])));
        uint32_t u = badd2(__byte_perm(d0, d1, 0x5410), __byte_perm(d0, d1, 0x7632));
        u = badd2(u, __shfl_xor_sync(0xffffffffu, u, 1));
        u = badd2(u, __shfl_xor_sync(0xffffffffu, u, 2));
        u = tq == 2 ? u ^ 0x80008000u : 0u;
        qm[2 * h] = u & 0xffffu;
        qm[2 * h + 1] = u >> 16;
      }
    }
    STAMP(3);
    uint32_t x0[20], xr[20];
    const int row_lo = b * 64 + w * 16 + gq;
    {
      float o0[12], o1[12], o2[12], o3[12];
#pragma unroll
      for (int i = 0; i < 12; i++) { o0[i] = 0.f; o1[i] = 0.f; o2[i] = 0.f; o3[i] = 0.f; }
      float s0[32], s1[32];
      uint32_t p0[16], p1[16];
      const int dthr = w * 16 + gq - 2 * tq;
      const uint32_t seq = r ? 0x13245u : 0x01324u;
      const int nit = rb >= 2 ? 5 : 2 * rb + 1 + r;
      mbar_wait(BAR(B_KVOWN + r), 0);
      uint32_t kb = ((sb + kv_addr(4 + r)) & 0x3FFFF) >> 4, kp = kb;
      WG_FENCE();
      qk_issue<0>(s0, q, qm[0], qm[1], kb);
      WG_COMMIT();
#pragma unroll
      for (int i = 0; i < 16; i++) p1[i] = 0u;
      WG_WAIT(0);
      reg_fence(s0);
#pragma unroll 1
      for (int it = 0; it < nit; it++) {
        const int nb = (it & 3) ? 4096 : dthr * 16 + 144;
        const uint32_t flip = it == 4 ? 0xffffffffu : 0u;
        uint32_t nk[9];
#pragma unroll
        for (int t = 0; t < 9; t++) asm("shl.b32 %0, %1, %2;" : "=r"(nk[t]) : "r"(0xffffffffu), "r"(max(nb - 128 * t, 0)));
        ATT_STEP(1, s1, kb, 3, o3, p1, kp, s0, p0, 1);
        ATT_STEP(2, s0, kb, 0, o0, p0, kb, s1, p1, 1);
        ATT_STEP(3, s1, kb, 1, o1, p1, kb, s0, p0, 1);
        kp = kb;
        if (it + 1 < nit) {
          const int bi = (seq >> (4 * it + 4)) & 15;
          mbar_wait(bi == 4 ? BAR(B_KVOWN) : BAR(B_KVFULL + bi), 0);
          kb = ((sb + kv_addr(bi)) & 0x3FFFF) >> 4;
        }
        ATT_STEP(0, s0, kb, 2, o2, p0, kp, s1, p1, LASTW);
      }
      WG_FENCE();
      pv_issue<3>(o3, p1, kp);
      WG_COMMIT();
      WG_WAIT(0);
      reg_fence(o0); reg_fence(o1); reg_fence(o2); reg_fence(o3);
      {
        const uint32_t e0 = 63u << 23;
        const uint32_t ba = (__float_as_uint(o0[8]) - e0) | (__float_as_uint(o0[10]) - e0) | (__float_as_uint(o2[8]) - e0) | (__float_as_uint(o2[10]) - e0);
        const uint32_t bb = (__float_as_uint(o1[0]) - e0) | (__float_as_uint(o1[2]) - e0) | (__float_as_uint(o3[0]) - e0) | (__float_as_uint(o3[2]) - e0);
        if (__builtin_expect(__any_sync(0xffffffffu, ((tq == 2 ? ba : tq == 0 ? bb : 0u) >> 30) != FORCE_SAFE), 0)) {
          safe_head<0>(o0, q, sb, seq, nit, dthr, lane);
          safe_head<1>(o1, q, sb, seq, nit, dthr, lane);
          safe_head<2>(o2, q, sb, seq, nit, dthr, lane);
          safe_head<3>(o3, q, sb, seq, nit, dthr, lane);
          __syncwarp();
        }
      }
      if (lane == 0) mbar_arrive_pair(BAR(B_ATTP));
      const uint8_t* xp = reinterpret_cast<const uint8_t*>(P.x) + (size_t)row_lo * 1280 + c * 160 + tq * 4;
#pragma unroll
      for (int t = 0; t < 10; t++) {
        xr[2 * t] = ldnc32(xp + t * 16);
        xr[2 * t + 1] = ldnc32(xp + 8 * 1280 + t * 16);
      }
      float inv[4][2];
      inv[0][0] = rcp(__shfl_sync(0xffffffffu, o0[8], (lane & 28) + 2));
      inv[0][1] = rcp(__shfl_sync(0xffffffffu, o0[10], (lane & 28) + 2));
      inv[1][0] = rcp(__shfl_sync(0xffffffffu, o1[0], lane & 28));
      inv[1][1] = rcp(__shfl_sync(0xffffffffu, o1[2], lane & 28));
      inv[2][0] = rcp(__shfl_sync(0xffffffffu, o2[8], (lane & 28) + 2));
      inv[2][1] = rcp(__shfl_sync(0xffffffffu, o2[10], (lane & 28) + 2));
      inv[3][0] = rcp(__shfl_sync(0xffffffffu, o3[0], lane & 28));
      inv[3][1] = rcp(__shfl_sync(0xffffffffu, o3[2], lane & 28));
      const bool lo = tq < 2;
#define OPK(dst, o, t, h) do { x0[dst] = pack2(o[4 * (t)] * inv[h][0], o[4 * (t) + 1] * inv[h][0]); x0[dst + 1] = pack2(o[4 * (t) + 2] * inv[h][1], o[4 * (t) + 3] * inv[h][1]); } while (0)
#define OPK2(dst, oa, ha, ob, hb) do { \
        const float i0 = lo ? inv[ha][0] : inv[hb][0], i1 = lo ? inv[ha][1] : inv[hb][1]; \
        x0[dst] = pack2((lo ? oa[8] : ob[0]) * i0, (lo ? oa[9] : ob[1]) * i0); \
        x0[dst + 1] = pack2((lo ? oa[10] : ob[2]) * i1, (lo ? oa[11] : ob[3]) * i1); } while (0)
      OPK(0, o0, 0, 0); OPK(2, o0, 1, 0); OPK2(4, o0, 0, o1, 1); OPK(6, o1, 1, 1); OPK(8, o1, 2, 1);
      OPK(10, o2, 0, 2); OPK(12, o2, 1, 2); OPK2(14, o2, 2, o3, 3); OPK(16, o3, 1, 3); OPK(18, o3, 2, 3);
    }
    const int bw = b * 4 + w;
    const size_t tile_off = (size_t)bw * 20480 + lane * 16;
    const size_t probe_off = (size_t)bw * 20480 + ((c + lane) & 7) * 2560 + 2544;
    {
#pragma unroll
      for (int k = 0; k < 5; k++) {
        x0[4 * k] = tag16(x0[4 * k], tag);
        stg128(g_o + tile_off + c * 2560 + k * 512, x0[4 * k], x0[4 * k + 1], x0[4 * k + 2], x0[4 * k + 3]);
      }
      STAMP(6);
      const uint32_t pv = ldcg32(g_o + probe_off);
      float acc[40];
#pragma unroll
      for (int t = 0; t < 10; t++) {
        acc[4 * t] = bf_lo(xr[2 * t]); acc[4 * t + 1] = bf_hi(xr[2 * t]); acc[4 * t + 2] = bf_lo(xr[2 * t + 1]); acc[4 * t + 3] = bf_hi(xr[2 * t + 1]);
      }
      constexpr uint64_t HI = desc_hi(2560, 256, 3);
      const uint64_t db = mkdesc(sb + OFF_WOB, HI);
      mbar_wait(BAR(B_WOB), 0);
      WG_FENCE();
#pragma unroll
      for (int k = 0; k < 5; k++) wg_rs80(acc, x0[4 * k], x0[4 * k + 1], x0[4 * k + 2], x0[4 * k + 3], db + k * 32, 1);
      WG_COMMIT();
      uint32_t xa[7][20], ready = __ballot_sync(0xffffffffu, ((pv ^ tag) & TAGM) == 0u);
#pragma unroll
      for (int i = 1; i < 8; i++) {
        probe_wait(ready, i, g_o + probe_off, tag);
        if (i == 7) WG_WAIT(0);
        ld_tile(xa[i - 1], g_o + tile_off + ((c + i) & 7) * 2560);
      }
      STAMP(7);
#pragma unroll
      for (int i = 1; i < 8; i++) {
        if (i == 7) mbar_wait(BAR(B_WOB7), 0);
        fix_tile(xa[i - 1], g_o + tile_off + ((c + i) & 7) * 2560, tag);
        WG_FENCE();
#pragma unroll
        for (int k = 0; k < 5; k++) wg_rs80(acc, xa[i - 1][4 * k], xa[i - 1][4 * k + 1], xa[i - 1][4 * k + 2], xa[i - 1][4 * k + 3], db + i * 800 + k * 32, 1);
        WG_COMMIT();
      }
      WG_WAIT(0);
      reg_fence(acc);
      if (lane == 0) mbar_arrive_pair(BAR(B_WODP));
      STAMP(8);
      float sum0 = 0.f, sum1 = 0.f;
#pragma unroll
      for (int t = 0; t < 10; t++) {
        x0[2 * t] = pack2(acc[4 * t], acc[4 * t + 1]);
        x0[2 * t + 1] = pack2(acc[4 * t + 2], acc[4 * t + 3]);
      }
#pragma unroll
      for (int k = 0; k < 5; k++) {
        x0[4 * k] = tag16(x0[4 * k], tag);
        stg128(g_h + tile_off + c * 2560 + k * 512, x0[4 * k], x0[4 * k + 1], x0[4 * k + 2], x0[4 * k + 3]);
      }
#pragma unroll
      for (int t = 0; t < 10; t++) {
        sum0 += bf_lo(x0[2 * t]) + bf_hi(x0[2 * t]);
        sum1 += bf_lo(x0[2 * t + 1]) + bf_hi(x0[2 * t + 1]);
      }
      sum0 += __shfl_xor_sync(0xffffffffu, sum0, 1);
      sum1 += __shfl_xor_sync(0xffffffffu, sum1, 1);
      sum0 += __shfl_xor_sync(0xffffffffu, sum0, 2);
      sum1 += __shfl_xor_sync(0xffffffffu, sum1, 2);
      const float mu0 = sum0 * (1.f / 80.f), mu1 = sum1 * (1.f / 80.f);
      float v0 = 0.f, v1 = 0.f;
#pragma unroll
      for (int t = 0; t < 10; t++) {
        const float d0 = bf_lo(x0[2 * t]) - mu0, d1 = bf_hi(x0[2 * t]) - mu0, d2 = bf_lo(x0[2 * t + 1]) - mu1, d3 = bf_hi(x0[2 * t + 1]) - mu1;
        v0 += d0 * d0 + d1 * d1;
        v1 += d2 * d2 + d3 * d3;
      }
      v0 += __shfl_xor_sync(0xffffffffu, v0, 1);
      v1 += __shfl_xor_sync(0xffffffffu, v1, 1);
      v0 += __shfl_xor_sync(0xffffffffu, v0, 2);
      v1 += __shfl_xor_sync(0xffffffffu, v1, 2);
      if (tq < 2) g_hstat[(bw * 8 + c) * 16 + gq + tq * 8] = make_float2(tq ? mu1 : mu0, tag32(tq ? v1 : v0, ep));
    }
    uint32_t ha[56];
    {
      float acc[112];
      constexpr uint64_t HI = desc_hi(5120, 512, 2);
#define W1_ISSUE(xx, i) do { \
        const uint64_t db = mkdesc(sb + w1b_addr(i), HI); \
        mbar_wait(BAR(B_BFULL + (i)), 0); \
        WG_FENCE(); \
        _Pragma("unroll") for (int k = 0; k < 5; k++) wg_rs224(acc, xx[4 * k], xx[4 * k + 1], xx[4 * k + 2], xx[4 * k + 3], db + k * 64, (i) | k); \
        WG_COMMIT(); } while (0)
#define W1_STEP(xx, xp, i) do { \
        fix_tile(xx, ht + ((c + (i)) & 7) * 2560, tag); \
        W1_ISSUE(xx, i); \
        WG_WAIT(1); \
        if ((i) != 4 && lane == 0) mbar_arrive_pair(BAR(B_BEMPTY - 1 + (i))); \
        if ((i) < 5) ld_tile(xp, ht + ((c + (i) + 3) & 7) * 2560); } while (0)
      W1_ISSUE(x0, 0);
      STAMP(9);
      const uint8_t* ht = g_h + tile_off;
      uint32_t x1[20], x2[20], x3[20], ready = 0;
      probe_wait(ready, 1, g_h + probe_off, tag);
      ld_tile(x1, ht + ((c + 1) & 7) * 2560);
      probe_wait(ready, 2, g_h + probe_off, tag);
      ld_tile(x2, ht + ((c + 2) & 7) * 2560);
      probe_wait(ready, 3, g_h + probe_off, tag);
      ld_tile(x3, ht + ((c + 3) & 7) * 2560);
      STAMP(10);
#pragma unroll 1
      for (int i = 1; ; i += 4) {
        W1_STEP(x1, x0, i);
        W1_STEP(x2, x1, i + 1);
        W1_STEP(x3, x2, i + 2);
        if (i == 5) break;
        W1_STEP(x0, x3, i + 3);
      }
      uint2 hs[4];
      {
        const float2* hp = &g_hstat[(bw * 8 + tq * 2) * 16 + gq];
        uint32_t n = 0;
        do {
          hs[0] = ldcg64(hp); hs[1] = ldcg64(hp + 16); hs[2] = ldcg64(hp + 8); hs[3] = ldcg64(hp + 24);
        } while (__any_sync(0xffffffffu, (((hs[0].y ^ ep) | (hs[1].y ^ ep) | (hs[2].y ^ ep) | (hs[3].y ^ ep)) & 3u) != 0u) && ++n < SPIN_MAX);
      }
      float mean0, mean1, rs0, rs1;
      {
        const float a0 = __uint_as_float(hs[0].x), a1 = __uint_as_float(hs[1].x), b0 = __uint_as_float(hs[2].x), b1 = __uint_as_float(hs[3].x);
        float t0 = a0 + a1, t1 = b0 + b1;
        t0 += __shfl_xor_sync(0xffffffffu, t0, 1);
        t1 += __shfl_xor_sync(0xffffffffu, t1, 1);
        t0 += __shfl_xor_sync(0xffffffffu, t0, 2);
        t1 += __shfl_xor_sync(0xffffffffu, t1, 2);
        mean0 = t0 * 0.125f;
        mean1 = t1 * 0.125f;
        float u0 = __uint_as_float(hs[0].y) + __uint_as_float(hs[1].y) + 80.f * ((a0 - mean0) * (a0 - mean0) + (a1 - mean0) * (a1 - mean0));
        float u1 = __uint_as_float(hs[2].y) + __uint_as_float(hs[3].y) + 80.f * ((b0 - mean1) * (b0 - mean1) + (b1 - mean1) * (b1 - mean1));
        u0 += __shfl_xor_sync(0xffffffffu, u0, 1);
        u1 += __shfl_xor_sync(0xffffffffu, u1, 1);
        u0 += __shfl_xor_sync(0xffffffffu, u0, 2);
        u1 += __shfl_xor_sync(0xffffffffu, u1, 2);
        rs0 = 0.5f * rsqrtf(u0 * (1.f / 640.f) + 1e-5f);
        rs1 = 0.5f * rsqrtf(u1 * (1.f / 640.f) + 1e-5f);
      }
      mbar_wait(BAR(B_CS1), 0);
      WG_WAIT(0);
      reg_fence(acc);
      if (lane == 0) mbar_arrive_pair(BAR(B_BEMPTY + 7));
      STAMP(11);
      const float n0 = -mean0 * rs0, n1 = -mean1 * rs1;
#pragma unroll
      for (int t = 0; t < 28; t++) {
        const float2 cs = lds64f(sb + OFF_XS + t * 32 + tq * 8);
        const float h0 = fmaf(acc[4 * t], rs0, cs.x * n0), h1 = fmaf(acc[4 * t + 1], rs0, cs.y * n0);
        const float h2 = fmaf(acc[4 * t + 2], rs1, cs.x * n1), h3 = fmaf(acc[4 * t + 3], rs1, cs.y * n1);
        ha[2 * t] = pack2(fmaf(h0, tanh_fast(h0), h0), fmaf(h1, tanh_fast(h1), h1));
        ha[2 * t + 1] = pack2(fmaf(h2, tanh_fast(h2), h2), fmaf(h3, tanh_fast(h3), h3));
      }
      if ((c & 3) == 3) {
#pragma unroll
        for (int t = 48; t < 56; t++) ha[t] = 0u;
      }
    }
    STAMP(12);
    {
      float accA[64], accB[64];
      constexpr uint64_t HI = desc_hi(28672, 1024, 1);
      const uint32_t lane_off = w * 2048 + lane * 16;
#define W2_ISSUE(acc, s) do { \
        mbar_wait(BAR(B_W2FULL + (s)), 0); \
        const uint64_t db = mkdesc(sb + ((s) & 3) * W2SLOT, HI); \
        WG_FENCE(); \
        _Pragma("unroll") for (int k = 0; k < 14; k++) wg_rs128(acc, ha[4 * k], ha[4 * k + 1], ha[4 * k + 2], ha[4 * k + 3], db + k * 128, k); \
        WG_COMMIT(); } while (0)
      uint8_t* const gp = g_part + (size_t)(b * 64 + c) * 8192 + lane_off;
#define W2_STORE(acc, s) do { \
        store_partial64(&acc[0], gp + ((c + 2 * (s) - 1) & 7) * 65536, tag); \
        store_partial64(&acc[32], gp + ((c + 2 * (s)) & 7) * 65536, tag); } while (0)
      W2_ISSUE(accA, 0);
      W2_ISSUE(accB, 1);
      WG_WAIT(1);
      reg_fence(accA);
      if (lane == 0) mbar_arrive_pair(BAR(B_W2E));
      {
        uint8_t* dst = g_p89 + (size_t)(bw * 8 + c) * 4096 + lane * 16;
        store_partial64(&accA[0], dst, tag);
        store_partial64(&accA[32], dst + 2048, tag);
      }
      STAMP(13);
      W2_ISSUE(accA, 2);
      WG_WAIT(1);
      reg_fence(accB);
      if (lane == 0) mbar_arrive(BAR(B_W2D));
      W2_STORE(accB, 1);
      W2_ISSUE(accB, 3);
      WG_WAIT(1);
      reg_fence(accA);
      if (lane == 0) mbar_arrive(BAR(B_W2D + 1));
      W2_STORE(accA, 2);
      float accR[32], accO[32];
      {
        mbar_wait(BAR(B_W2FULL + 4), 0);
        const uint64_t db = mkdesc(sb, HI);
        WG_FENCE();
#pragma unroll
        for (int k = 0; k < 14; k++) wg_rs64(accR, ha[4 * k], ha[4 * k + 1], ha[4 * k + 2], ha[4 * k + 3], db + k * 128, k);
        WG_COMMIT();
#pragma unroll
        for (int k = 0; k < 14; k++) wg_rs64(accO, ha[4 * k], ha[4 * k + 1], ha[4 * k + 2], ha[4 * k + 3], db + 1792 + k * 128, k);
        WG_COMMIT();
      }
      WG_WAIT(2);
      reg_fence(accB);
      W2_STORE(accB, 3);
      uint4 v[4];
      ld4(v, g_h + tile_off + c * 2048);
      WG_WAIT(1);
      reg_fence(accR);
      store_partial64(&accR[0], gp + ((c + 7) & 7) * 65536, tag);
      STAMP(14);
      WG_WAIT(0);
      reg_fence(accO);
      add4(accO, v);
      STAMP(15);
      const uint8_t* pp = g_part + (size_t)(b * 8 + c) * 65536 + lane_off;
#pragma unroll 1
      for (int u = 0; u < 7; u++) {
        if (u < 6) {
          const uint32_t z = sb + W2SLOT + u * 16384 + (u >= 3 ? 8192 : 0) + r * 8192 + lane_off;
          mbar_wait(BAR(B_PL + 2 * u + r), 0);
#pragma unroll
          for (int i = 0; i < 4; i++)
            asm volatile("ld.shared.v4.u32 {%0,%1,%2,%3}, [%4];" : "=r"(v[i].x), "=r"(v[i].y), "=r"(v[i].z), "=r"(v[i].w) : "r"(z + i * 512) : "memory");
        } else {
          STAMP(16);
          v[0].x = ~tag;
        }
        uint32_t n = 0;
        while (__any_sync(0xffffffffu, (((v[0].x ^ tag) | (v[1].x ^ tag) | (v[2].x ^ tag) | (v[3].x ^ tag)) & TAGM) != 0u) && ++n < SPIN_MAX)
          ld4(v, pp + ((c - 1 - u) & 7) * 8192);
        add4(accO, v);
      }
      uint8_t* op = reinterpret_cast<uint8_t*>(P.out) + (size_t)row_lo * 1280 + c * 128 + tq * 4;
#pragma unroll
      for (int t = 0; t < 8; t++) {
        *reinterpret_cast<uint32_t*>(op + t * 16) = pack2(accO[4 * t], accO[4 * t + 1]);
        *reinterpret_cast<uint32_t*>(op + 8 * 1280 + t * 16) = pack2(accO[4 * t + 2], accO[4 * t + 3]);
      }
      STAMP(17);
    }
  }
}

typedef CUresult (*EncodeFn)(CUtensorMap*, CUtensorMapDataType, cuuint32_t, void*, const cuuint64_t*, const cuuint64_t*, const cuuint32_t*,
                             const cuuint32_t*, CUtensorMapInterleave, CUtensorMapSwizzle, CUtensorMapL2promotion, CUtensorMapFloatOOBfill);

static void make_map(EncodeFn enc, CUtensorMap* m, const void* p, int nd, const cuuint64_t* dims, const cuuint64_t* strides, const cuuint32_t* box,
                     CUtensorMapSwizzle sw) {
  const cuuint32_t es[5] = {1, 1, 1, 1, 1};
  enc(m, CU_TENSOR_MAP_DATA_TYPE_BFLOAT16, (cuuint32_t)nd, const_cast<void*>(p), dims, strides, box, es, CU_TENSOR_MAP_INTERLEAVE_NONE, sw,
      CU_TENSOR_MAP_L2_PROMOTION_L2_128B, CU_TENSOR_MAP_FLOAT_OOB_FILL_NONE);
}

extern "C" void kernel_launch(void* const* d_in, const int* in_sizes, int n_in, void* d_out, int out_size) {
  (void)in_sizes; (void)n_in; (void)out_size;
  static EncodeFn enc = nullptr;
  if (!enc) {
    void* f = nullptr;
    cudaDriverEntryPointQueryResult qr;
    cudaGetDriverEntryPoint("cuTensorMapEncodeTiled", &f, cudaEnableDefault, &qr);
    enc = (EncodeFn)f;
    cudaFuncSetAttribute(fused_block_kernel, cudaFuncAttributeMaxDynamicSharedMemorySize, (int)SMEM_BYTES);
  }
  Params P;
  P.x = (const __nv_bfloat16*)d_in[0];
  P.wqkv = (const __nv_bfloat16*)d_in[1];
  P.wo = (const __nv_bfloat16*)d_in[2];
  P.w1 = (const __nv_bfloat16*)d_in[4];
  P.w2 = (const __nv_bfloat16*)d_in[5];
  P.out = (__nv_bfloat16*)d_out;
  { const cuuint64_t d[2] = {640, 2048}, s[1] = {1280}; const cuuint32_t b[2] = {64, 128}; make_map(enc, &P.mX, P.x, 2, d, s, b, CU_TENSOR_MAP_SWIZZLE_128B); }
  { const cuuint64_t d[4] = {32, 640, 20, 3}, s[3] = {3840, 64, 1280}; const cuuint32_t b[4] = {32, 32, 2, 3}; make_map(enc, &P.mWqM, P.wqkv, 4, d, s, b, CU_TENSOR_MAP_SWIZZLE_64B); }
  { const cuuint64_t d[4] = {16, 640, 40, 3}, s[3] = {3840, 32, 1280}; const cuuint32_t b[4] = {16, 32, 1, 3}; make_map(enc, &P.mWqL, P.wqkv, 4, d, s, b, CU_TENSOR_MAP_SWIZZLE_32B); }
  { const cuuint64_t d[3] = {16, 640, 40}, s[2] = {1280, 32}; const cuuint32_t b[3] = {16, 80, 5}; make_map(enc, &P.mWo, P.wo, 3, d, s, b, CU_TENSOR_MAP_SWIZZLE_32B); }
  { const cuuint64_t d[3] = {32, 640, 54}, s[2] = {3456, 64}; const cuuint32_t b[3] = {32, 80, 4}; make_map(enc, &P.mW1a, P.w1, 3, d, s, b, CU_TENSOR_MAP_SWIZZLE_64B); }
  { const cuuint64_t d[3] = {32, 640, 54}, s[2] = {3456, 64}; const cuuint32_t b[3] = {32, 80, 3}; make_map(enc, &P.mW1b, P.w1, 3, d, s, b, CU_TENSOR_MAP_SWIZZLE_64B); }
  { const cuuint64_t d[2] = {640, 1728}, s[1] = {1280}; const cuuint32_t b[2] = {64, 112}; make_map(enc, &P.mW2, P.w2, 2, d, s, b, CU_TENSOR_MAP_SWIZZLE_128B); }
  fused_block_kernel<<<SMIDMAP ? 132 : 128, 384, SMEM_BYTES, cudaStreamPerThread>>>(P);
}
```

```cpp
#include <cuda_runtime.h>
#include <cuda.h>
#include <cuda_bf16.h>
#include <stdint.h>

#define PROF 0
#define STATKT 3
#define LASTW 1
#define KVP 8
#define LATEWODP 0
#define OSYNC 0
#define FORCE_SAFE 0u
#define SMIDMAP 0

__device__ __align__(1024) uint8_t g_kv[32 * 8 * 22528];
__device__ __align__(1024) uint8_t g_o[32 * 4 * 8 * 2560];
__device__ __align__(1024) uint8_t g_h[32 * 4 * 8 * 2560];
__device__ __align__(1024) float2 g_hstat[32 * 4 * 8 * 16];
__device__ __align__(128) uint32_t g_oflag[32 * 8];
__device__ __align__(128) float2 g_xstat[2048];
__device__ __align__(128) float g_csq[16 * 8 * 240];
__device__ __align__(128) float g_cs1[16 * 8 * 224];
__device__ __align__(128) uint32_t g_epoch[128];
#define STAMP(slot)
#define STAMPW(slot)

struct Params {
  CUtensorMap mX, mWqM, mWqL, mWo, mW1a, mW1b, mW2, mOutH, mOut;
  const __nv_bfloat16 *x, *wqkv, *wo, *w1, *w2;
  __nv_bfloat16* out;
};

constexpr uint32_t QST = 47104;
constexpr uint32_t KVB = 22528;
constexpr uint32_t OFF_WOB = 0;
constexpr uint32_t OFF_PRE = 188416;
constexpr uint32_t W2SLOT = 57344;
constexpr uint32_t OFF_OST = 174080;
constexpr uint32_t OFF_HST = 209920;
constexpr uint32_t OFF_CS = 229376;
constexpr uint32_t OFF_XS = 230912;
constexpr uint32_t OFF_MISC = 231936;
constexpr uint32_t SMEM_BYTES = 232448;

enum {
  B_QFULL = 0, B_KVFULL = 4, B_KVLAND = 8, B_WOB = 12, B_WOB7 = 13, B_BFULL = 14, B_W2FULL = 22, B_CS1 = 27, B_OUTOK = 28,
  B_KVOWN = 30, B_HST = 32,
  B_Q23 = 34, B_PRE = 35, B_STAT = 36, B_ATTL = 37,
  B_QEMPTY = 38, B_W2E = 42, B_WODP = 44, B_BEMPTY = 45, B_ATT4 = 53, B_ATT3 = 54,
  B_ATT2 = 55,
  NBAR = 56
};
constexpr uint32_t TAGM = 0x00010001u;
constexpr uint32_t SPIN_MAX = 1u << 18;

__device__ __forceinline__ uint32_t s2u(const void* p) { return (uint32_t)__cvta_generic_to_shared(p); }
__device__ __forceinline__ void mbar_init(uint32_t b, int c) { asm volatile("mbarrier.init.shared::cta.b64 [%0], %1;" ::"r"(b), "r"(c)); }
__device__ __forceinline__ void mbar_expect(uint32_t b, int bytes) { asm volatile("mbarrier.arrive.expect_tx.shared::cta.b64 _, [%0], %1;" ::"r"(b), "r"(bytes) : "memory"); }
__device__ __forceinline__ void mbar_arrive(uint32_t b) { asm volatile("mbarrier.arrive.shared::cta.b64 _, [%0];" ::"r"(b) : "memory"); }
__device__ __forceinline__ void mbar_arrive_pair(uint32_t b) {
  asm volatile("{\n.reg .b32 r;\nmapa.shared::cluster.u32 r, %0, 0;\nmbarrier.arrive.shared::cluster.b64 _, [r];\n"
               "mapa.shared::cluster.u32 r, %0, 1;\nmbarrier.arrive.shared::cluster.b64 _, [r];\n}" ::"r"(b) : "memory");
}
__device__ __forceinline__ void mbar_wait(uint32_t b, uint32_t ph) {
  asm volatile("{\n.reg .pred p;\n.reg .u32 n;\nmov.u32 n, 0;\nW%=:\nmbarrier.try_wait.parity.shared::cta.b64 p, [%0], %1;\n"
               "add.u32 n, n, 1;\nsetp.lt.and.u32 p, n, 0x100000, !p;\n@p bra W%=;\n}" ::"r"(b), "r"(ph) : "memory");
}
__device__ __forceinline__ void tma2d(uint32_t dst, const CUtensorMap* m, int c0, int c1, uint32_t bar) {
  asm volatile("cp.async.bulk.tensor.2d.shared::cluster.global.mbarrier::complete_tx::bytes [%0], [%1, {%3, %4}], [%2];" ::"r"(dst), "l"(m), "r"(bar), "r"(c0), "r"(c1) : "memory");
}
__device__ __forceinline__ void tma2d_mc(uint32_t dst, const CUtensorMap* m, int c0, int c1, uint32_t bar) {
  asm volatile("cp.async.bulk.tensor.2d.shared::cluster.global.mbarrier::complete_tx::bytes.multicast::cluster [%0], [%1, {%3, %4}], [%2], %5;" ::"r"(dst), "l"(m), "r"(bar), "r"(c0), "r"(c1), "h"((uint16_t)3) : "memory");
}
__device__ __forceinline__ void tma3d_mc(uint32_t dst, const CUtensorMap* m, int c0, int c1, int c2, uint32_t bar) {
  asm volatile("cp.async.bulk.tensor.3d.shared::cluster.global.mbarrier::complete_tx::bytes.multicast::cluster [%0], [%1, {%3, %4, %5}], [%2], %6;" ::"r"(dst), "l"(m), "r"(bar), "r"(c0), "r"(c1), "r"(c2), "h"((uint16_t)3) : "memory");
}
__device__ __forceinline__ void tma4d_mc(uint32_t dst, const CUtensorMap* m, int c0, int c1, int c2, int c3, uint32_t bar) {
  asm volatile("cp.async.bulk.tensor.4d.shared::cluster.global.mbarrier::complete_tx::bytes.multicast::cluster [%0], [%1, {%3, %4, %5, %6}], [%2], %7;" ::"r"(dst), "l"(m), "r"(bar), "r"(c0), "r"(c1), "r"(c2), "r"(c3), "h"((uint16_t)3) : "memory");
}
__device__ __forceinline__ void bulk_load(uint32_t dst, const void* src, int bytes, uint32_t bar) {
  asm volatile("cp.async.bulk.shared::cluster.global.mbarrier::complete_tx::bytes [%0], [%1], %2, [%3];" ::"r"(dst), "l"(src), "r"(bytes), "r"(bar) : "memory");
}
__device__ __forceinline__ void tma4d_pf(const CUtensorMap* m, int c0, int c1, int c2, int c3) {
  asm volatile("cp.async.bulk.prefetch.tensor.4d.L2.global [%0, {%1, %2, %3, %4}];" ::"l"(m), "r"(c0), "r"(c1), "r"(c2), "r"(c3) : "memory");
}
__device__ __forceinline__ void l2_prefetch_bulk(const void* p, int bytes) { asm volatile("cp.async.bulk.prefetch.L2.global [%0], %1;" ::"l"(p), "r"(bytes) : "memory"); }
__device__ __forceinline__ void l2_prefetch(const void* p) { asm volatile("prefetch.global.L2 [%0];" ::"l"(p)); }
__device__ __forceinline__ uint32_t ld_flag(const uint32_t* p) { uint32_t v; asm volatile("ld.acquire.gpu.global.u32 %0, [%1];" : "=r"(v) : "l"(p) : "memory"); return v; }
__device__ __forceinline__ void st_flag(uint32_t* p, uint32_t v) { asm volatile("st.relaxed.gpu.global.u32 [%0], %1;" ::"l"(p), "r"(v) : "memory"); }
__device__ __forceinline__ void fence_gpu() { asm volatile("fence.acq_rel.gpu;" ::: "memory"); }
__device__ __forceinline__ void fence_async_smem() { asm volatile("fence.proxy.async.shared::cta;" ::: "memory"); }
__device__ __forceinline__ void fence_async_glob() { asm volatile("fence.proxy.async.global;" ::: "memory"); }
__device__ __forceinline__ uint4 ldcg128(const void* p) { uint4 v; asm volatile("ld.relaxed.gpu.global.v4.u32 {%0,%1,%2,%3}, [%4];" : "=r"(v.x), "=r"(v.y), "=r"(v.z), "=r"(v.w) : "l"(p) : "memory"); return v; }
__device__ __forceinline__ uint4 ldnc128(const void* p) { uint4 v; asm volatile("ld.global.nc.v4.u32 {%0,%1,%2,%3}, [%4];" : "=r"(v.x), "=r"(v.y), "=r"(v.z), "=r"(v.w) : "l"(p)); return v; }
__device__ __forceinline__ uint32_t ldnc32(const void* p) { uint32_t v; asm volatile("ld.global.nc.u32 %0, [%1];" : "=r"(v) : "l"(p)); return v; }
__device__ __forceinline__ uint2 ldcg64(const void* p) { uint2 v; asm volatile("ld.relaxed.gpu.global.v2.u32 {%0,%1}, [%2];" : "=r"(v.x), "=r"(v.y) : "l"(p) : "memory"); return v; }
__device__ __forceinline__ uint32_t ldcg32(const void* p) { uint32_t v; asm volatile("ld.relaxed.gpu.global.u32 %0, [%1];" : "=r"(v) : "l"(p) : "memory"); return v; }
__device__ __forceinline__ uint32_t pack2(float lo, float hi) { uint32_t r; asm("cvt.rn.bf16x2.f32 %0, %1, %2;" : "=r"(r) : "f"(hi), "f"(lo)); return r; }
__device__ __forceinline__ float bf_lo(uint32_t v) { return __uint_as_float(v << 16); }
__device__ __forceinline__ float bf_hi(uint32_t v) { return __uint_as_float(v & 0xffff0000u); }
__device__ __forceinline__ float ex2(float x) { float y; asm("ex2.approx.ftz.f32 %0, %1;" : "=f"(y) : "f"(x)); return y; }
__device__ __forceinline__ float rcp(float x) { float y; asm("rcp.approx.ftz.f32 %0, %1;" : "=f"(y) : "f"(x)); return y; }
__device__ __forceinline__ float tanh_fast(float x) { float y; asm("tanh.approx.f32 %0, %1;" : "=f"(y) : "f"(x)); return y; }
__device__ __forceinline__ void stsm4(uint32_t a, uint32_t r0, uint32_t r1, uint32_t r2, uint32_t r3) {
  asm volatile("stmatrix.sync.aligned.m8n8.x4.shared.b16 [%0], {%1,%2,%3,%4};" ::"r"(a), "r"(r0), "r"(r1), "r"(r2), "r"(r3) : "memory");
}
__device__ __forceinline__ float2 lds64f(uint32_t a) { float2 v; asm volatile("ld.shared.v2.f32 {%0,%1}, [%2];" : "=f"(v.x), "=f"(v.y) : "r"(a)); return v; }
__device__ __forceinline__ constexpr uint64_t desc_hi(uint32_t lbo, uint32_t sbo, uint32_t sw) {
  return ((uint64_t)(lbo >> 4) << 16) | ((uint64_t)(sbo >> 4) << 32) | ((uint64_t)sw << 62);
}
__device__ __forceinline__ uint64_t mkdesc(uint32_t addr, uint64_t hi) { return hi | (uint64_t)((addr & 0x3FFFF) >> 4); }
#define WG_FENCE() asm volatile("wgmma.fence.sync.aligned;" ::: "memory")
#define WG_COMMIT() asm volatile("wgmma.commit_group.sync.aligned;" ::: "memory")
#define WG_WAIT_(n) asm volatile("wgmma.wait_group.sync.aligned " #n ";" ::: "memory")
#define WG_WAIT(n) WG_WAIT_(n)
template <int N> __device__ __forceinline__ void reg_fence(float (&a)[N]) {
#pragma unroll
  for (int i = 0; i < N; i++) asm volatile("" : "+f"(a[i])::"memory");
}

__device__ __forceinline__ void wg_ss192(float (&d)[96], uint64_t da, uint64_t db, int sd) {
  asm volatile("{\n.reg .pred p;\nsetp.ne.b32 p, %98, 0;\n"
  "wgmma.mma_async.sync.aligned.m64n192k16.f32.bf16.bf16 {%0, %1, %2, %3, %4, %5, %6, %7, %8, %9, %10, %11, %12, %13, %14, %15, %16, %17, %18, %19, %20, %21, %22, %23, %24, %25, %26, %27, %28, %29, %30, %31, %32, %33, %34, %35, %36, %37, %38, %39, %40, %41, %42, %43, %44, %45, %46, %47, %48, %49, %50, %51, %52, %53, %54, %55, %56, %57, %58, %59, %60, %61, %62, %63, %64, %65, %66, %67, %68, %69, %70, %71, %72, %73, %74, %75, %76, %77, %78, %79, %80, %81, %82, %83, %84, %85, %86, %87, %88, %89, %90, %91, %92, %93, %94, %95}, %96, %97, p, 1, 1, 0, 1;\n}\n"
  : "+f"(d[0]), "+f"(d[1]), "+f"(d[2]), "+f"(d[3]), "+f"(d[4]), "+f"(d[5]), "+f"(d[6]), "+f"(d[7]), "+f"(d[8]), "+f"(d[9]), "+f"(d[10]), "+f"(d[11]), "+f"(d[12]), "+f"(d[13]), "+f"(d[14]), "+f"(d[15]), "+f"(d[16]), "+f"(d[17]), "+f"(d[18]), "+f"(d[19]), "+f"(d[20]), "+f"(d[21]), "+f"(d[22]), "+f"(d[23]), "+f"(d[24]), "+f"(d[25]), "+f"(d[26]), "+f"(d[27]), "+f"(d[28]), "+f"(d[29]), "+f"(d[30]), "+f"(d[31]), "+f"(d[32]), "+f"(d[33]), "+f"(d[34]), "+f"(d[35]), "+f"(d[36]), "+f"(d[37]), "+f"(d[38]), "+f"(d[39]), "+f"(d[40]), "+f"(d[41]), "+f"(d[42]), "+f"(d[43]), "+f"(d[44]), "+f"(d[45]), "+f"(d[46]), "+f"(d[47]), "+f"(d[48]), "+f"(d[49]), "+f"(d[50]), "+f"(d[51]), "+f"(d[52]), "+f"(d[53]), "+f"(d[54]), "+f"(d[55]), "+f"(d[56]), "+f"(d[57]), "+f"(d[58]), "+f"(d[59]), "+f"(d[60]), "+f"(d[61]), "+f"(d[62]), "+f"(d[63]), "+f"(d[64]), "+f"(d[65]), "+f"(d[66]), "+f"(d[67]), "+f"(d[68]), "+f"(d[69]), "+f"(d[70]), "+f"(d[71]), "+f"(d[72]), "+f"(d[73]), "+f"(d[74]), "+f"(d[75]), "+f"(d[76]), "+f"(d[77]), "+f"(d[78]), "+f"(d[79]), "+f"(d[80]), "+f"(d[81]), "+f"(d[82]), "+f"(d[83]), "+f"(d[84]), "+f"(d[85]), "+f"(d[86]), "+f"(d[87]), "+f"(d[88]), "+f"(d[89]), "+f"(d[90]), "+f"(d[91]), "+f"(d[92]), "+f"(d[93]), "+f"(d[94]), "+f"(d[95]) : "l"(da), "l"(db), "r"(sd));
}
__device__ __forceinline__ void wg_ss48(float (&d)[24], uint64_t da, uint64_t db, int sd) {
  asm volatile("{\n.reg .pred p;\nsetp.ne.b32 p, %26, 0;\n"
  "wgmma.mma_async.sync.aligned.m64n48k16.f32.bf16.bf16 {%0, %1, %2, %3, %4, %5, %6, %7, %8, %9, %10, %11, %12, %13, %14, %15, %16, %17, %18, %19, %20, %21, %22, %23}, %24, %25, p, 1, 1, 0, 1;\n}\n"
  : "+f"(d[0]), "+f"(d[1]), "+f"(d[2]), "+f"(d[3]), "+f"(d[4]), "+f"(d[5]), "+f"(d[6]), "+f"(d[7]), "+f"(d[8]), "+f"(d[9]), "+f"(d[10]), "+f"(d[11]), "+f"(d[12]), "+f"(d[13]), "+f"(d[14]), "+f"(d[15]), "+f"(d[16]), "+f"(d[17]), "+f"(d[18]), "+f"(d[19]), "+f"(d[20]), "+f"(d[21]), "+f"(d[22]), "+f"(d[23]) : "l"(da), "l"(db), "r"(sd));
}
__device__ __forceinline__ void wg_rs80(float (&d)[40], uint32_t a0, uint32_t a1, uint32_t a2, uint32_t a3, uint64_t db, int sd) {
  asm volatile("{\n.reg .pred p;\nsetp.ne.b32 p, %45, 0;\n"
  "wgmma.mma_async.sync.aligned.m64n80k16.f32.bf16.bf16 {%0, %1, %2, %3, %4, %5, %6, %7, %8, %9, %10, %11, %12, %13, %14, %15, %16, %17, %18, %19, %20, %21, %22, %23, %24, %25, %26, %27, %28, %29, %30, %31, %32, %33, %34, %35, %36, %37, %38, %39}, {%40, %41, %42, %43}, %44, p, 1, 1, 1;\n}\n"
  : "+f"(d[0]), "+f"(d[1]), "+f"(d[2]), "+f"(d[3]), "+f"(d[4]), "+f"(d[5]), "+f"(d[6]), "+f"(d[7]), "+f"(d[8]), "+f"(d[9]), "+f"(d[10]), "+f"(d[11]), "+f"(d[12]), "+f"(d[13]), "+f"(d[14]), "+f"(d[15]), "+f"(d[16]), "+f"(d[17]), "+f"(d[18]), "+f"(d[19]), "+f"(d[20]), "+f"(d[21]), "+f"(d[22]), "+f"(d[23]), "+f"(d[24]), "+f"(d[25]), "+f"(d[26]), "+f"(d[27]), "+f"(d[28]), "+f"(d[29]), "+f"(d[30]), "+f"(d[31]), "+f"(d[32]), "+f"(d[33]), "+f"(d[34]), "+f"(d[35]), "+f"(d[36]), "+f"(d[37]), "+f"(d[38]), "+f"(d[39]) : "r"(a0), "r"(a1), "r"(a2), "r"(a3), "l"(db), "r"(sd));
}
__device__ __forceinline__ void wg_rs224(float (&d)[112], uint32_t a0, uint32_t a1, uint32_t a2, uint32_t a3, uint64_t db, int sd) {
  asm volatile("{\n.reg .pred p;\nsetp.ne.b32 p, %117, 0;\n"
  "wgmma.mma_async.sync.aligned.m64n224k16.f32.bf16.bf16 {%0, %1, %2, %3, %4, %5, %6, %7, %8, %9, %10, %11, %12, %13, %14, %15, %16, %17, %18, %19, %20, %21, %22, %23, %24, %25, %26, %27, %28, %29, %30, %31, %32, %33, %34, %35, %36, %37, %38, %39, %40, %41, %42, %43, %44, %45, %46, %47, %48, %49, %50, %51, %52, %53, %54, %55, %56, %57, %58, %59, %60, %61, %62, %63, %64, %65, %66, %67, %68, %69, %70, %71, %72, %73, %74, %75, %76, %77, %78, %79, %80, %81, %82, %83, %84, %85, %86, %87, %88, %89, %90, %91, %92, %93, %94, %95, %96, %97, %98, %99, %100, %101, %102, %103, %104, %105, %106, %107, %108, %109, %110, %111}, {%112, %113, %114, %115}, %116, p, 1, 1, 1;\n}\n"
  : "+f"(d[0]), "+f"(d[1]), "+f"(d[2]), "+f"(d[3]), "+f"(d[4]), "+f"(d[5]), "+f"(d[6]), "+f"(d[7]), "+f"(d[8]), "+f"(d[9]), "+f"(d[10]), "+f"(d[11]), "+f"(d[12]), "+f"(d[13]), "+f"(d[14]), "+f"(d[15]), "+f"(d[16]), "+f"(d[17]), "+f"(d[18]), "+f"(d[19]), "+f"(d[20]), "+f"(d[21]), "+f"(d[22]), "+f"(d[23]), "+f"(d[24]), "+f"(d[25]), "+f"(d[26]), "+f"(d[27]), "+f"(d[28]), "+f"(d[29]), "+f"(d[30]), "+f"(d[31]), "+f"(d[32]), "+f"(d[33]), "+f"(d[34]), "+f"(d[35]), "+f"(d[36]), "+f"(d[37]), "+f"(d[38]), "+f"(d[39]), "+f"(d[40]), "+f"(d[41]), "+f"(d[42]), "+f"(d[43]), "+f"(d[44]), "+f"(d[45]), "+f"(d[46]), "+f"(d[47]), "+f"(d[48]), "+f"(d[49]), "+f"(d[50]), "+f"(d[51]), "+f"(d[52]), "+f"(d[53]), "+f"(d[54]), "+f"(d[55]), "+f"(d[56]), "+f"(d[57]), "+f"(d[58]), "+f"(d[59]), "+f"(d[60]), "+f"(d[61]), "+f"(d[62]), "+f"(d[63]), "+f"(d[64]), "+f"(d[65]), "+f"(d[66]), "+f"(d[67]), "+f"(d[68]), "+f"(d[69]), "+f"(d[70]), "+f"(d[71]), "+f"(d[72]), "+f"(d[73]), "+f"(d[74]), "+f"(d[75]), "+f"(d[76]), "+f"(d[77]), "+f"(d[78]), "+f"(d[79]), "+f"(d[80]), "+f"(d[81]), "+f"(d[82]), "+f"(d[83]), "+f"(d[84]), "+f"(d[85]), "+f"(d[86]), "+f"(d[87]), "+f"(d[88]), "+f"(d[89]), "+f"(d[90]), "+f"(d[91]), "+f"(d[92]), "+f"(d[93]), "+f"(d[94]), "+f"(d[95]), "+f"(d[96]), "+f"(d[97]), "+f"(d[98]), "+f"(d[99]), "+f"(d[100]), "+f"(d[101]), "+f"(d[102]), "+f"(d[103]), "+f"(d[104]), "+f"(d[105]), "+f"(d[106]), "+f"(d[107]), "+f"(d[108]), "+f"(d[109]), "+f"(d[110]), "+f"(d[111]) : "r"(a0), "r"(a1), "r"(a2), "r"(a3), "l"(db), "r"(sd));
}
__device__ __forceinline__ void wg_rs64k(float (&d)[32], uint32_t a0, uint32_t a1, uint32_t a2, uint32_t a3, uint64_t db, int sd) {
  asm volatile("{\n.reg .pred p;\nsetp.ne.b32 p, %37, 0;\n"
  "wgmma.mma_async.sync.aligned.m64n64k16.f32.bf16.bf16 {%0, %1, %2, %3, %4, %5, %6, %7, %8, %9, %10, %11, %12, %13, %14, %15, %16, %17, %18, %19, %20, %21, %22, %23, %24, %25, %26, %27, %28, %29, %30, %31}, {%32, %33, %34, %35}, %36, p, 1, 1, 0;\n}\n"
  : "+f"(d[0]), "+f"(d[1]), "+f"(d[2]), "+f"(d[3]), "+f"(d[4]), "+f"(d[5]), "+f"(d[6]), "+f"(d[7]), "+f"(d[8]), "+f"(d[9]), "+f"(d[10]), "+f"(d[11]), "+f"(d[12]), "+f"(d[13]), "+f"(d[14]), "+f"(d[15]), "+f"(d[16]), "+f"(d[17]), "+f"(d[18]), "+f"(d[19]), "+f"(d[20]), "+f"(d[21]), "+f"(d[22]), "+f"(d[23]), "+f"(d[24]), "+f"(d[25]), "+f"(d[26]), "+f"(d[27]), "+f"(d[28]), "+f"(d[29]), "+f"(d[30]), "+f"(d[31]) : "r"(a0), "r"(a1), "r"(a2), "r"(a3), "l"(db), "r"(sd));
}
__device__ __forceinline__ void wg_rs24(float (&d)[12], uint32_t a0, uint32_t a1, uint32_t a2, uint32_t a3, uint64_t db, int sd) {
  asm volatile("{\n.reg .pred p;\nsetp.ne.b32 p, %17, 0;\n"
  "wgmma.mma_async.sync.aligned.m64n24k16.f32.bf16.bf16 {%0, %1, %2, %3, %4, %5, %6, %7, %8, %9, %10, %11}, {%12, %13, %14, %15}, %16, p, 1, 1, 1;\n}\n"
  : "+f"(d[0]), "+f"(d[1]), "+f"(d[2]), "+f"(d[3]), "+f"(d[4]), "+f"(d[5]), "+f"(d[6]), "+f"(d[7]), "+f"(d[8]), "+f"(d[9]), "+f"(d[10]), "+f"(d[11]) : "r"(a0), "r"(a1), "r"(a2), "r"(a3), "l"(db), "r"(sd));
}
__device__ __forceinline__ void wg_rs128(float (&d)[64], uint32_t a0, uint32_t a1, uint32_t a2, uint32_t a3, uint64_t db, int sd) {
  asm volatile("{\n.reg .pred p;\nsetp.ne.b32 p, %69, 0;\n"
  "wgmma.mma_async.sync.aligned.m64n128k16.f32.bf16.bf16 {%0, %1, %2, %3, %4, %5, %6, %7, %8, %9, %10, %11, %12, %13, %14, %15, %16, %17, %18, %19, %20, %21, %22, %23, %24, %25, %26, %27, %28, %29, %30, %31, %32, %33, %34, %35, %36, %37, %38, %39, %40, %41, %42, %43, %44, %45, %46, %47, %48, %49, %50, %51, %52, %53, %54, %55, %56, %57, %58, %59, %60, %61, %62, %63}, {%64, %65, %66, %67}, %68, p, 1, 1, 1;\n}\n"
  : "+f"(d[0]), "+f"(d[1]), "+f"(d[2]), "+f"(d[3]), "+f"(d[4]), "+f"(d[5]), "+f"(d[6]), "+f"(d[7]), "+f"(d[8]), "+f"(d[9]), "+f"(d[10]), "+f"(d[11]), "+f"(d[12]), "+f"(d[13]), "+f"(d[14]), "+f"(d[15]), "+f"(d[16]), "+f"(d[17]), "+f"(d[18]), "+f"(d[19]), "+f"(d[20]), "+f"(d[21]), "+f"(d[22]), "+f"(d[23]), "+f"(d[24]), "+f"(d[25]), "+f"(d[26]), "+f"(d[27]), "+f"(d[28]), "+f"(d[29]), "+f"(d[30]), "+f"(d[31]), "+f"(d[32]), "+f"(d[33]), "+f"(d[34]), "+f"(d[35]), "+f"(d[36]), "+f"(d[37]), "+f"(d[38]), "+f"(d[39]), "+f"(d[40]), "+f"(d[41]), "+f"(d[42]), "+f"(d[43]), "+f"(d[44]), "+f"(d[45]), "+f"(d[46]), "+f"(d[47]), "+f"(d[48]), "+f"(d[49]), "+f"(d[50]), "+f"(d[51]), "+f"(d[52]), "+f"(d[53]), "+f"(d[54]), "+f"(d[55]), "+f"(d[56]), "+f"(d[57]), "+f"(d[58]), "+f"(d[59]), "+f"(d[60]), "+f"(d[61]), "+f"(d[62]), "+f"(d[63]) : "r"(a0), "r"(a1), "r"(a2), "r"(a3), "l"(db), "r"(sd));
}

__device__ __forceinline__ uint32_t kv_addr(int i) {
  return 94208u + KVB * (uint32_t)((0x104253u >> (4 * i)) & 15u);
}
__device__ __forceinline__ uint32_t w1b_addr(int s) {
  return (s == 3 || s == 4) ? (uint32_t)(s - 3) * 35840u : 102400u + (uint32_t)(s >= 5 ? s - 5 : s) * 35840u;
}
__device__ __forceinline__ void stg128(void* p, uint32_t a, uint32_t b, uint32_t c, uint32_t d) {
  asm volatile("st.global.v4.u32 [%0], {%1,%2,%3,%4};" ::"l"(p), "r"(a), "r"(b), "r"(c), "r"(d) : "memory");
}
__device__ __forceinline__ void stg32(void* p, uint32_t a) { asm volatile("st.global.u32 [%0], %1;" ::"l"(p), "r"(a) : "memory"); }
__device__ __forceinline__ void ld_tile(uint32_t (&a)[20], const uint8_t* p) {
#pragma unroll
  for (int k = 0; k < 5; k++)
    asm volatile("ld.relaxed.gpu.global.v4.u32 {%0,%1,%2,%3}, [%4];" : "=r"(a[4 * k]), "=r"(a[4 * k + 1]), "=r"(a[4 * k + 2]), "=r"(a[4 * k + 3]) : "l"(p + k * 512) : "memory");
}
__device__ __forceinline__ uint32_t tag16(uint32_t v, uint32_t tag) { return (v & ~TAGM) | tag; }
__device__ __forceinline__ float tag32(float v, uint32_t ep) { return __uint_as_float((__float_as_uint(v) & ~3u) | ep); }
__device__ __forceinline__ void fix_tile(uint32_t (&a)[20], const uint8_t* p, uint32_t tag) {
  uint32_t n = 0;
  while (__any_sync(0xffffffffu, (((a[0] ^ tag) | (a[4] ^ tag) | (a[8] ^ tag) | (a[12] ^ tag) | (a[16] ^ tag)) & TAGM) != 0u) && ++n < SPIN_MAX) ld_tile(a, p);
}
__device__ __forceinline__ void probe_wait(uint32_t& ready, int i, const void* p, uint32_t tag) {
  uint32_t n = 0;
  while (!((ready >> i) & 1u) && ++n < SPIN_MAX) ready = __ballot_sync(0xffffffffu, ((ldcg32(p) ^ tag) & TAGM) == 0u);
}
__device__ __forceinline__ float gather16(const float* p, int stride, uint32_t ep) {
  uint32_t v[16], n = 0;
  while (true) {
    uint32_t bad = 0;
#pragma unroll
    for (int i = 0; i < 16; i++) v[i] = ldcg32(p + i * stride);
#pragma unroll
    for (int i = 0; i < 16; i++) bad |= v[i] ^ ep;
    if (!__any_sync(0xffffffffu, (bad & 3u) != 0u) || ++n >= SPIN_MAX) break;
  }
  float s = 0.f;
#pragma unroll
  for (int i = 0; i < 16; i++) s += __uint_as_float(v[i]);
  return s;
}

__device__ __forceinline__ uint64_t desc2(uint32_t lo, uint32_t hi) { uint64_t d; asm("mov.b64 %0, {%1, %2};" : "=l"(d) : "r"(lo), "r"(hi)); return d; }
template <int H>
__device__ __forceinline__ void qk_issue(float (&s)[32], const uint32_t (&q)[24], uint32_t m0, uint32_t m1, uint32_t kd) {
  constexpr int J0 = (H == 0) ? 0 : (H == 1) ? 2 : (H == 2) ? 5 : 7;
  wg_rs64k(s, q[H * 6 + 0], q[H * 6 + 1], q[H * 6 + 2], q[H * 6 + 3], desc2(kd + (0x400000u + J0 * 64), 8u), 0);
  wg_rs64k(s, q[H * 6 + 4], q[H * 6 + 5], m0, m1, desc2(kd + (((10 - J0) * 64u << 16) + (J0 + 2) * 64), 8u), 1);
}
template <int H>
__device__ __forceinline__ void pv_issue(float (&o)[12], const uint32_t (&p)[16], uint32_t kd) {
#pragma unroll
  for (int i = 0; i < 4; i++)
    wg_rs24(o, p[4 * i], p[4 * i + 1], p[4 * i + 2], p[4 * i + 3], desc2(kd + (0x80000u + 640 + 3 * H * 64 + i * 16), 64u), 1);
}
__device__ __forceinline__ void sm_exp(const float (&s)[32], uint32_t (&p)[16], const uint32_t (&nk)[9], uint32_t flip) {
#pragma unroll
  for (int t = 0; t < 8; t++) {
    p[2 * t] = pack2(ex2(s[4 * t]), ex2(s[4 * t + 1])) & (~nk[t + 1] ^ flip);
    p[2 * t + 1] = pack2(ex2(s[4 * t + 2]), ex2(s[4 * t + 3])) & (~nk[t] ^ flip);
  }
#pragma unroll
  for (int i = 0; i < 16; i++) asm volatile("" : "+r"(p[i])::"memory");
}
__device__ __forceinline__ void mma16816(float* d, uint32_t a0, uint32_t a1, uint32_t a2, uint32_t a3, uint32_t b0, uint32_t b1) {
  asm volatile("mma.sync.aligned.m16n8k16.row.col.f32.bf16.bf16.f32 {%0,%1,%2,%3}, {%4,%5,%6,%7}, {%8,%9}, {%0,%1,%2,%3};"
               : "+f"(d[0]), "+f"(d[1]), "+f"(d[2]), "+f"(d[3]) : "r"(a0), "r"(a1), "r"(a2), "r"(a3), "r"(b0), "r"(b1));
}
template <int H>
__device__ __forceinline__ void safe_head(float (&o)[12], const uint32_t (&q)[24], const uint8_t* kv, uint32_t seq, int nit, int anti, int dthr, int tq, uint32_t tag) {
  constexpr int J0 = (H == 0) ? 0 : (H == 1) ? 2 : (H == 2) ? 5 : 7;
  float m0 = -INFINITY, m1 = -INFINITY;
#pragma unroll
  for (int i = 0; i < 12; i++) o[i] = 0.f;
#pragma unroll 1
  for (int st = 0; st < 4 * nit; st++) {
    const uint8_t* a = kv + (size_t)((seq >> (st & 28)) & 15) * (8 * KVB) + (st & 3) * 256;
    uint32_t b[12], bad, n = 0;
    do {
      bad = 0;
#pragma unroll
      for (int i = 0; i < 12; i++) {
        b[i] = ldcg32(a + ((i < 6 ? J0 : 7 + 3 * H) + (i >> 1)) * 1024 + (i & 1) * 128);
        bad |= b[i] ^ tag;
      }
    } while (__any_sync(0xffffffffu, tq == 1 && (bad & TAGM) != 0u) && ++n < SPIN_MAX);
    float s[8];
#pragma unroll
    for (int i = 0; i < 8; i++) s[i] = 0.f;
#pragma unroll
    for (int t = 0; t < 2; t++) {
      mma16816(&s[4 * t], q[6 * H], q[6 * H + 1], q[6 * H + 2], q[6 * H + 3], b[t], b[2 + t]);
      mma16816(&s[4 * t], q[6 * H + 4], q[6 * H + 5], 0u, 0u, b[4 + t], 0u);
    }
    if (st < 4 || (st >> 2) == anti) {
      const int z = dthr - (st & 3) * 16;
#pragma unroll
      for (int i = 0; i < 8; i++)
        if (((i >> 2) * 8 + (i & 1) - (i & 2) * 4 <= z) != (st < 4)) s[i] = -INFINITY;
    }
    float n0 = fmaxf(fmaxf(s[0], s[1]), fmaxf(s[4], s[5])), n1 = fmaxf(fmaxf(s[2], s[3]), fmaxf(s[6], s[7]));
    n0 = fmaxf(n0, __shfl_xor_sync(0xffffffffu, n0, 1));
    n1 = fmaxf(n1, __shfl_xor_sync(0xffffffffu, n1, 1));
    n0 = fmaxf(m0, fmaxf(n0, __shfl_xor_sync(0xffffffffu, n0, 2)));
    n1 = fmaxf(m1, fmaxf(n1, __shfl_xor_sync(0xffffffffu, n1, 2)));
    const float al0 = ex2(m0 - n0), al1 = ex2(m1 - n1);
    m0 = n0;
    m1 = n1;
    const uint32_t p0 = pack2(ex2(s[0] - n0), ex2(s[1] - n0)), p1 = pack2(ex2(s[2] - n1), ex2(s[3] - n1));
    const uint32_t p2 = pack2(ex2(s[4] - n0), ex2(s[5] - n0)), p3 = pack2(ex2(s[6] - n1), ex2(s[7] - n1));
#pragma unroll
    for (int i = 6; i < 12; i++) asm volatile("movmatrix.sync.aligned.m8n8.trans.b16 %0, %0;" : "+r"(b[i]));
#pragma unroll
    for (int t = 0; t < 3; t++) {
      o[4 * t] *= al0; o[4 * t + 1] *= al0; o[4 * t + 2] *= al1; o[4 * t + 3] *= al1;
      mma16816(&o[4 * t], p0, p1, p2, p3, b[6 + 2 * t], b[7 + 2 * t]);
    }
  }
}
#define ATT_STEP(HQ, sq, kq, HP, op, pp, kv, sc, pc, W) do { \
  WG_FENCE(); qk_issue<HQ>(sq, q, qm[2 * HQ], qm[2 * HQ + 1], kq); WG_COMMIT(); WG_WAIT(1); pv_issue<HP>(op, pp, kv); WG_COMMIT(); \
  sm_exp(sc, pc, nk, flip); WG_WAIT(W); reg_fence(sq); } while (0)
__device__ __forceinline__ uint32_t bmul2(uint32_t a, uint32_t b) { uint32_t d; asm("mul.rn.bf16x2 %0, %1, %2;" : "=r"(d) : "r"(a), "r"(b)); return d; }
__device__ __forceinline__ uint32_t badd2(uint32_t a, uint32_t b) { uint32_t d; asm("add.rn.bf16x2 %0, %1, %2;" : "=r"(d) : "r"(a), "r"(b)); return d; }
__device__ __forceinline__ uint32_t bfma2(uint32_t a, uint32_t b, uint32_t c) { uint32_t d; asm("fma.rn.bf16x2 %0, %1, %2, %3;" : "=r"(d) : "r"(a), "r"(b), "r"(c)); return d; }

__global__ void __cluster_dims__(2, 1, 1) __launch_bounds__(384, 1) fused_block_kernel(const __grid_constant__ Params P) {
  extern __shared__ __align__(1024) uint8_t smem[];
  const uint32_t sb = s2u(smem);
  const int tid = threadIdx.x, lane = tid & 31, warp = __shfl_sync(0xffffffffu, tid >> 5, 0);
  const uint32_t rank = blockIdx.x & 1;
  const int rb = blockIdx.x & 15, c = blockIdx.x >> 4;
  const int tile = rb * 8 + c;
  const uint32_t bars = sb + OFF_MISC;
#define BAR(i) (bars + 8u * (uint32_t)(i))
  const int odd = c & 1;
  const int mainch = (c >> 1) * 5 + (odd ? 3 : 0), leftch = (c >> 1) * 10 + (odd ? 5 : 4);
  if (warp >= 8) asm volatile("setmaxnreg.dec.sync.aligned.u32 56;");
  if (lane == 0) {
    if (warp == 8) {
      asm volatile("prefetch.tensormap [%0];" ::"l"(&P.mWqM) : "memory");
      asm volatile("prefetch.tensormap [%0];" ::"l"(&P.mWqL) : "memory");
    } else {
      const int i0 = (warp < 8 ? warp + 3 : warp - 9) * 5;
#pragma unroll
      for (int u = 0; u < 6; u++) {
        const int i = i0 + u;
        if (u < 5 || i == 55) mbar_init(BAR(i), i < B_KVOWN ? 1 : i < B_Q23 ? 4 : i < B_QEMPTY ? 8 : i < B_ATT2 ? 16 : 18);
      }
    }
    asm volatile("fence.mbarrier_init.release.cluster;" ::: "memory");
    if (warp == 9) {
      mbar_expect(BAR(B_QFULL), QST);
      tma2d(sb, &P.mX, 0, rb * 128, BAR(B_QFULL));
    }
  }
  __syncwarp();
  if (warp == 8) STAMPW(11);
  asm volatile("barrier.cluster.arrive.relaxed.aligned;" ::: "memory");
  if (warp == 8) {
    asm volatile("barrier.cluster.wait.acquire.aligned;\nbar.arrive 1, 384;" ::: "memory");
    STAMPW(8);
    if (lane == 0) {
#pragma unroll 1
      for (int kt = 0; kt < 4; kt++) {
        const uint32_t a = sb + kt * QST, fb = BAR(B_QFULL + kt);
        if (kt) mbar_expect(fb, QST);
        tma4d_mc(a + 16384 + rank * 12288, &P.mWqM, 0, kt * 64 + rank * 32, mainch, 0, fb);
        tma4d_mc(a + 40960 + rank * 3072, &P.mWqL, 0, kt * 64 + rank * 32, leftch, 0, fb);
        if (kt) tma2d(a, &P.mX, kt * 64, rb * 128, fb);
        if (kt == 0) STAMPW(10);
      }
    }
    __syncwarp();
    STAMPW(9);
  } else {
    asm volatile("bar.sync 1, 384;" ::: "memory");
  }
  const int sc = (27 * c + 3) >> 2;

  if (warp >= 8) {
    const uint32_t epoch = ldcg32(&g_epoch[tile]) + 1u;
    const uint32_t ep = epoch & 3u, tag = (epoch & 1u) | ((epoch & 2u) << 15);
    if (warp == 8) {
      if (lane == 0) {
#pragma unroll 1
        for (int kt = 4; kt < 10; kt++) {
          const int st = kt & 3;
          mbar_wait(BAR(B_QEMPTY + st), ((kt >> 2) - 1) & 1);
          const uint32_t a = sb + st * QST, fb = BAR(B_QFULL + st);
          mbar_expect(fb, QST);
          tma4d_mc(a + 16384 + rank * 12288, &P.mWqM, 0, kt * 64 + rank * 32, mainch, 0, fb);
          tma4d_mc(a + 40960 + rank * 3072, &P.mWqL, 0, kt * 64 + rank * 32, leftch, 0, fb);
          tma2d(a, &P.mX, kt * 64, rb * 128, fb);
        }
        const CUtensorMap* mW1 = rank ? &P.mW1b : &P.mW1a;
        asm volatile("prefetch.tensormap [%0];" ::"l"(&P.mWo) : "memory");
        asm volatile("prefetch.tensormap [%0];" ::"l"(mW1) : "memory");
        asm volatile("prefetch.tensormap [%0];" ::"l"(&P.mW2) : "memory");
        mbar_wait(BAR(B_QEMPTY + 0), 0);
        mbar_wait(BAR(B_QEMPTY + 1), 0);
        if (rb) mbar_wait(BAR(B_KVFULL + 3), 0);
        mbar_expect(BAR(B_WOB), 89600);
#pragma unroll 1
        for (int i = 0; i < 4 - (int)rank; i++) {
          const int pos = rank * 4 + i;
          tma3d_mc(sb + OFF_WOB + pos * 12800, &P.mWo, 0, ((c + pos) & 7) * 80, c * 5, BAR(B_WOB));
        }
#pragma unroll 1
        for (int s = 0; s < 8; s++) {
          if (s < 3) mbar_wait(BAR(B_ATT2 - s), 0);
          if (s == 0) {
            mbar_expect(BAR(B_WOB7), 12800);
            if (rank) tma3d_mc(sb + OFF_WOB + 7 * 12800, &P.mWo, 0, ((c + 7) & 7) * 80, c * 5, BAR(B_WOB7));
          } else if (s == 3) mbar_wait(BAR(B_WODP), 0);
          else if (s >= 5) mbar_wait(BAR(B_BEMPTY + s - 5), 0);
          const uint32_t fb = BAR(B_BFULL + s);
          mbar_expect(fb, 35840);
          tma3d_mc(sb + w1b_addr(s) + rank * 20480, mW1, 0, ((c + s) & 7) * 80, sc + rank * 4, fb);
        }
#pragma unroll 1
        for (int s = 0; s < 5; s++) {
          mbar_wait(s < 3 ? BAR(B_BEMPTY + 4 + s) : BAR(B_W2E + s - 3), 0);
          const uint32_t dst = sb + (s < 3 ? s : s - 3) * W2SLOT + rank * 14336, fb = BAR(B_W2FULL + s);
          const int bx0 = (c + 2 * s) % 10, bx1 = (c + 2 * s + 1) % 10;
          mbar_expect(fb, W2SLOT);
          tma2d_mc(dst, &P.mW2, bx0 * 64, sc * 32 + rank * 112, fb);
          tma2d_mc(dst + 28672, &P.mW2, bx1 * 64, sc * 32 + rank * 112, fb);
        }
      }
      __syncwarp();
    } else {
      if (warp == 11) {
        mbar_wait(BAR(B_QFULL + 3), 0);
        if (lane == 0) {
          l2_prefetch_bulk(reinterpret_cast<const uint8_t*>(P.wo) + tile * 6400, 6400);
          l2_prefetch_bulk(reinterpret_cast<const uint8_t*>(P.w1) + tile * 17280, 17280);
          l2_prefetch_bulk(reinterpret_cast<const uint8_t*>(P.w2) + tile * 17280, 17280);
        }
        mbar_wait(BAR(B_PRE), 0);
#pragma unroll 1
        for (int q = lane; q < 60; q += 32) {
          float4 a = make_float4(0.f, 0.f, 0.f, 0.f);
#pragma unroll
          for (int i = 0; i < 8; i++) {
            const float4 v = *reinterpret_cast<const float4*>(smem + OFF_PRE + i * 960 + q * 16);
            a.x += v.x; a.y += v.y; a.z += v.z; a.w += v.w;
          }
          *reinterpret_cast<float4*>(&g_csq[tile * 240 + q * 4]) = make_float4(tag32(a.x, ep), tag32(a.y, ep), tag32(a.z, ep), tag32(a.w, ep));
        }
        __syncwarp();
        STAMPW(0);
        mbar_wait(BAR(B_Q23), 0);
      } else {
        if (warp == 10 && lane == 0) {
#pragma unroll 1
          for (int i = 0; i < 1 + KVP; i++) {
            if (i < 2) mbar_wait(BAR(B_KVOWN + i), 0);
            const uint32_t off = i ? (uint32_t)(i - 1) * (KVB / KVP) + KVB : 0u;
            asm volatile("cp.async.bulk.wait_group.read 0;\ncp.async.bulk.global.shared::cta.bulk_group [%0], [%1], %2;\ncp.async.bulk.commit_group;"
                         ::"l"(g_kv + (size_t)(rb * 16 + c) * KVB + (i ? 7 * KVB + off : 0u)), "r"(sb + kv_addr(4) + off), "r"(i ? KVB / KVP : KVB) : "memory");
          }
          asm volatile("cp.async.bulk.wait_group.read 0;" ::: "memory");
          mbar_arrive_pair(BAR(B_ATT2));
          STAMPW(6);
        }
        if (warp == 9) mbar_wait(BAR(B_Q23), 0);
        __syncwarp();
      }
#pragma unroll 1
      for (int bi = warp == 9 ? 2 : warp == 10 ? 3 : 1; bi >= 0; bi -= (warp == 9 ? 2 : 4)) {
        const int blk = 2 * rb - 4 + bi;
        if (blk < 0) continue;
        const uint8_t* src = g_kv + (size_t)(blk * 8 + c) * KVB;
        const uint32_t dst = sb + kv_addr(bi);
        uint32_t n = 0, ph = 0;
        while (!__all_sync(0xffffffffu, ((ldcg32(src + lane * 704 + 692) ^ tag) & TAGM) == 0u) && ++n < SPIN_MAX) {}
        if (warp == 9 && bi == 2) STAMPW(3);
        while (true) {
          if (lane == 0) {
            fence_async_glob();
            mbar_expect(BAR(B_KVLAND + bi), KVB);
            bulk_load(dst, src, KVB, BAR(B_KVLAND + bi));
          }
          mbar_wait(BAR(B_KVLAND + bi), ph);
          ph ^= 1u;
          uint32_t bad = 0;
#pragma unroll 11
          for (int i = 0; i < 44; i++) {
            uint32_t v;
            asm volatile("ld.shared.u32 %0, [%1];" : "=r"(v) : "r"(dst + (i * 32 + lane) * 16 + 4) : "memory");
            bad |= v ^ tag;
          }
          if (!__any_sync(0xffffffffu, (bad & TAGM) != 0u) || ++n >= SPIN_MAX) break;
        }
        if (lane == 0) {
          mbar_arrive(BAR(B_KVFULL + bi));
        }
        if (warp == 9 && bi == 2) STAMPW(5);
        if (warp == 10) STAMPW(7);
      }
      __syncwarp();
      asm volatile("barrier.cluster.wait.acquire.aligned;" ::: "memory");
      if (warp == 10) {
        const int col = sc * 32 + lane * 8;
        const uint8_t* wb = reinterpret_cast<const uint8_t*>(P.w1) + (size_t)rb * 40 * 3456 + (size_t)col * 2;
        float acc[8];
#pragma unroll
        for (int i = 0; i < 8; i++) acc[i] = 0.f;
        if (lane < 28 && col < 1728) {
#pragma unroll 1
          for (int i = 0; i < 40; i += 8) {
            uint4 v[8];
#pragma unroll
            for (int u = 0; u < 8; u++) v[u] = __ldg(reinterpret_cast<const uint4*>(wb + (size_t)(i + u) * 3456));
#pragma unroll
            for (int u = 0; u < 8; u++) {
              acc[0] += bf_lo(v[u].x); acc[1] += bf_hi(v[u].x); acc[2] += bf_lo(v[u].y); acc[3] += bf_hi(v[u].y);
              acc[4] += bf_lo(v[u].z); acc[5] += bf_hi(v[u].z); acc[6] += bf_lo(v[u].w); acc[7] += bf_hi(v[u].w);
            }
          }
        }
        if (lane < 28) {
          float4* dst = reinterpret_cast<float4*>(&g_cs1[tile * 224 + lane * 8]);
          dst[0] = make_float4(tag32(acc[0], ep), tag32(acc[1], ep), tag32(acc[2], ep), tag32(acc[3], ep));
          dst[1] = make_float4(tag32(acc[4], ep), tag32(acc[5], ep), tag32(acc[6], ep), tag32(acc[7], ep));
        }
        STAMPW(4);
      } else if (warp == 11) {
        mbar_wait(BAR(B_ATT3), 0);
#pragma unroll 1
        for (int u = lane; u < 224; u += 32) *reinterpret_cast<float*>(smem + OFF_XS + u * 4) = gather16(g_cs1 + c * 224 + u, 1792, ep);
        __syncwarp();
        if (lane == 0) mbar_arrive(BAR(B_CS1));
        STAMPW(1);
      }
    }
    if (warp == 9 || warp == 10) {
      const int r = warp - 9;
      uint32_t* fl = &g_oflag[(rb * 2 + r) * 8];
      mbar_wait(BAR(B_HST + r), 0);
      if (lane == 0) {
        asm volatile("cp.async.bulk.tensor.2d.global.shared::cta.bulk_group [%0, {%2, %3}], [%1];\ncp.async.bulk.commit_group;\ncp.async.bulk.wait_group 0;"
                     ::"l"(&P.mOutH), "r"(sb + OFF_HST + r * 10240), "r"(c * 80), "r"(rb * 128 + r * 64) : "memory");
        asm volatile("fence.proxy.async.global;\nst.release.gpu.global.u32 [%0], %1;" ::"l"(fl + c), "r"(epoch) : "memory");
      }
      __syncwarp();
      uint32_t n = 0;
      while (!__all_sync(0xffffffffu, ld_flag(fl + (lane & 7)) == epoch) && ++n < SPIN_MAX) {}
      if (lane == 0) mbar_arrive(BAR(B_OUTOK + r));
      STAMPW(2);
    } else if (warp == 11 && lane == 0) {
      st_flag(&g_epoch[tile], epoch);
    }
  } else {
    const int r = warp >> 2, w = warp & 3, gq = lane >> 2, tq = lane & 3;
    asm volatile("setmaxnreg.inc.sync.aligned.u32 224;");
    STAMP(4);
    uint4 xv[5], wv[5];
    uint32_t ep;
    const int b = rb * 2 + r;
    uint32_t q[24], qm[8], tag;
    STAMP(0);
    {
      float accM[96], accL[24];
      uint2 s0u, s1u;
#define QKV_ISSUE(kt) do { \
        const uint32_t a = sb + ((kt) & 3) * QST; \
        const uint64_t da = mkdesc(a + r * 8192, desc_hi(16, 1024, 1)); \
        const uint64_t dm = mkdesc(a + 16384, desc_hi(2048, 512, 2)); \
        const uint64_t dl = mkdesc(a + 40960, desc_hi(1024, 256, 3)); \
        mbar_wait(BAR(B_QFULL + ((kt) & 3)), ((kt) >> 2) & 1); \
        WG_FENCE(); \
        _Pragma("unroll") for (int k = 0; k < 4; k++) { \
          wg_ss192(accM, da + k * 2, dm + (k >> 1) * 768 + (k & 1) * 64, (kt) | k); \
          wg_ss48(accL, da + k * 2, dl + (k >> 1) * 192 + (k & 1) * 32, (kt) | k); \
        } \
        WG_COMMIT(); } while (0)
      QKV_ISSUE(0);
      STAMP(1);
      {
          const uint8_t* xb = reinterpret_cast<const uint8_t*>(P.x) + (size_t)(rb * 128 + c * 16 + warp * 2 + (lane >> 4)) * 1280 + (lane & 15) * 16;
          const int cl = lane < 30 ? lane : 29;
          const uint8_t* wb = reinterpret_cast<const uint8_t*>(P.wqkv) + (size_t)(rb * 40 + warp * 5) * 3840 + (cl / 10) * 1280 + c * 160 + (cl % 10) * 16;
#pragma unroll
          for (int i = 0; i < 5; i++) wv[i] = ldnc128(wb + i * 3840);
#pragma unroll
          for (int i = 0; i < 5; i++) xv[i] = ldnc128(xb + i * 256);
          ep = ldcg32(&g_epoch[tile]);
      }
#pragma unroll 1
      for (int kt = 1; kt < 10; kt++) {
        QKV_ISSUE(kt);
        if (kt == STATKT) {
          STAMP(19);
#pragma unroll
          for (int i = 0; i < 5; i++) asm volatile("" : "+r"(wv[i].x), "+r"(wv[i].y), "+r"(wv[i].z), "+r"(wv[i].w));
          float a[8];
#pragma unroll
          for (int i = 0; i < 8; i++) a[i] = 0.f;
#pragma unroll
          for (int u = 0; u < 5; u++) {
            a[0] += bf_lo(wv[u].x); a[1] += bf_hi(wv[u].x); a[2] += bf_lo(wv[u].y); a[3] += bf_hi(wv[u].y);
            a[4] += bf_lo(wv[u].z); a[5] += bf_hi(wv[u].z); a[6] += bf_lo(wv[u].w); a[7] += bf_hi(wv[u].w);
          }
          if (lane < 30) {
            float4* dst = reinterpret_cast<float4*>(smem + OFF_PRE + warp * 960 + lane * 32);
            dst[0] = make_float4(a[0], a[1], a[2], a[3]);
            dst[1] = make_float4(a[4], a[5], a[6], a[7]);
          }
          __syncwarp();
          if (lane == 0) mbar_arrive(BAR(B_PRE));
          STAMP(5);
        } else if (kt == STATKT + 1) {
          asm volatile("" : "+r"(ep));
#pragma unroll
          for (int i = 0; i < 5; i++) asm volatile("" : "+r"(xv[i].x), "+r"(xv[i].y), "+r"(xv[i].z), "+r"(xv[i].w));
          ep = (ep + 1u) & 3u;
          float s = 0.f;
#pragma unroll
          for (int i = 0; i < 5; i++)
            s += ((bf_lo(xv[i].x) + bf_hi(xv[i].x)) + (bf_lo(xv[i].y) + bf_hi(xv[i].y))) + ((bf_lo(xv[i].z) + bf_hi(xv[i].z)) + (bf_lo(xv[i].w) + bf_hi(xv[i].w)));
#pragma unroll
          for (int o = 8; o; o >>= 1) s += __shfl_xor_sync(0xffffffffu, s, o);
          const float mean = s * (1.f / 640.f);
          float m2 = 0.f;
#pragma unroll
          for (int i = 0; i < 5; i++) {
            const uint32_t u[4] = {xv[i].x, xv[i].y, xv[i].z, xv[i].w};
#pragma unroll
            for (int j = 0; j < 4; j++) {
              const float d0 = bf_lo(u[j]) - mean, d1 = bf_hi(u[j]) - mean;
              m2 += d0 * d0 + d1 * d1;
            }
          }
#pragma unroll
          for (int o = 8; o; o >>= 1) m2 += __shfl_xor_sync(0xffffffffu, m2, o);
          if ((lane & 15) == 0)
            g_xstat[rb * 128 + c * 16 + warp * 2 + (lane >> 4)] = make_float2(mean, tag32(rsqrtf(m2 * (1.f / 640.f) + 1e-5f), ep));
        } else if (kt == STATKT + 2) {
          asm volatile("barrier.cluster.wait.acquire.aligned;" ::: "memory");
        } else
        if (kt == 9) {
          const float cs = gather16(g_csq + c * 240 + (tid < 240 ? tid : 239), 1920, ep);
          if (tid < 240) *reinterpret_cast<float*>(smem + OFF_CS + tid * 4) = cs;
          uint32_t n = 0;
          do {
            s0u = ldcg64(&g_xstat[b * 64 + w * 16 + gq]);
            s1u = ldcg64(&g_xstat[b * 64 + w * 16 + gq + 8]);
          } while (__any_sync(0xffffffffu, (((s0u.y ^ ep) | (s1u.y ^ ep)) & 3u) != 0u) && ++n < SPIN_MAX);
          if (lane == 0) mbar_arrive(BAR(B_STAT));
        }
        WG_WAIT(1);
        if (lane == 0) {
          mbar_arrive_pair(BAR(B_QEMPTY + ((kt - 1) & 3)));
          if (kt == 8) mbar_arrive(BAR(B_Q23));
        }
      }
      WG_WAIT(0);
      reg_fence(accM); reg_fence(accL);
      if (lane == 0) mbar_arrive_pair(BAR(B_QEMPTY + 1));
      STAMP(2);
      tag = (ep & 1u) | ((ep & 2u) << 15);
      mbar_wait(BAR(B_STAT), 0);
      mbar_wait(BAR(B_Q23), 0);
      const float2 s0 = make_float2(__uint_as_float(s0u.x), __uint_as_float(s0u.y)), s1 = make_float2(__uint_as_float(s1u.x), __uint_as_float(s1u.y));
      const uint32_t km = tq == 1 ? ~TAGM : 0xffffffffu, kt1 = tq == 1 ? tag : 0u;
      const uint32_t csM = sb + OFF_CS + (odd ? 64 : 0) + tq * 8, csL = sb + OFF_CS + (odd ? 0 : 256) + tq * 8;
      const uint32_t kvo = sb + kv_addr(4 + r) + (uint32_t)(w * 16 + ((lane >> 3) & 1) * 8 + (lane & 7)) * 16u + (uint32_t)(lane >> 4) * 1024u;
      const float qs = 0.22360679774997896f * 1.4426950408889634f;
      const bool lo = tq < 2;
      uint32_t qj[20], kj[20];
#pragma unroll
      for (int mm = 0; mm < 3; mm++) {
        const int mat = (mm + 1) % 3;
        const float r0 = mat == 0 ? s0.y * qs : s0.y, r1 = mat == 0 ? s1.y * qs : s1.y;
        const float n0 = -s0.x * r0, n1 = -s1.x * r1;
        uint32_t pk[20];
#pragma unroll
        for (int t = 0; t < 10; t++) {
          const float* a = t < 8 ? &accM[(mat * 8 + t) * 4] : &accL[(mat * 2 + t - 8) * 4];
          const float2 cs = lds64f(t < 8 ? csM + mat * 320 + t * 32 : csL + mat * 320 + (t - 8) * 32);
          pk[2 * t] = pack2(fmaf(a[0], r0, cs.x * n0), fmaf(a[1], r0, cs.y * n0));
          pk[2 * t + 1] = pack2(fmaf(a[2], r1, cs.x * n1), fmaf(a[3], r1, cs.y * n1));
        }
#pragma unroll
        for (int i = 0; i < 20; i++) qj[i] = odd ? pk[(i + 16) % 20] : pk[i];
        if (mat == 1) {
#pragma unroll
          for (int i = 0; i < 20; i++) kj[i] = (qj[i] & km) | kt1;
#pragma unroll
          for (int t = 0; t < 10; t += 2) stsm4(kvo + t * 1024, kj[2 * t], kj[2 * t + 1], kj[2 * t + 2], kj[2 * t + 3]);
        }
        if (mat == 2) {
          const uint32_t one = (tq & 1) ? 0u : 0x3f80u;
          uint32_t vv[24];
#pragma unroll
          for (int hp = 0; hp < 2; hp++) {
            const int j = hp * 10;
#pragma unroll
            for (int i = 0; i < 4; i++) { vv[hp * 12 + i] = qj[j + i]; vv[hp * 12 + 8 + i] = qj[j + 6 + i]; }
            vv[hp * 12 + 4] = lo ? qj[j + 4] : one; vv[hp * 12 + 5] = lo ? qj[j + 5] : one;
            vv[hp * 12 + 6] = lo ? one : qj[j + 4]; vv[hp * 12 + 7] = lo ? one : qj[j + 5];
          }
#pragma unroll
          for (int i = 0; i < 24; i++) vv[i] = (vv[i] & km) | kt1;
#pragma unroll
          for (int t = 0; t < 6; t++) stsm4(kvo + 10240 + t * 2048, vv[4 * t], vv[4 * t + 1], vv[4 * t + 2], vv[4 * t + 3]);
          fence_async_smem();
          __syncwarp();
          if (lane == 0) mbar_arrive(BAR(B_KVOWN + r));
        }
      }
#pragma unroll
      for (int hp = 0; hp < 2; hp++) {
        const int j = hp * 10;
        q[hp * 12 + 0] = qj[j + 0]; q[hp * 12 + 1] = qj[j + 1]; q[hp * 12 + 2] = qj[j + 2]; q[hp * 12 + 3] = qj[j + 3];
        q[hp * 12 + 4] = lo ? qj[j + 4] : 0u; q[hp * 12 + 5] = lo ? qj[j + 5] : 0u;
        q[hp * 12 + 6] = lo ? 0u : qj[j + 4]; q[hp * 12 + 7] = lo ? 0u : qj[j + 5];
        q[hp * 12 + 8] = qj[j + 6]; q[hp * 12 + 9] = qj[j + 7]; q[hp * 12 + 10] = qj[j + 8]; q[hp * 12 + 11] = qj[j + 9];
      }
#pragma unroll
      for (int h = 0; h < 4; h++) {
        const int j = (h >> 1) * 10 + (h & 1) * 4;
        const uint32_t d0 = bfma2(q[6 * h + 4], kj[j + 4], bfma2(q[6 * h + 2], kj[j + 2], bmul2(q[6 * h], kj[j])));
        const uint32_t d1 = bfma2(q[6 * h + 5], kj[j + 5], bfma2(q[6 * h + 3], kj[j + 3], bmul2(q[6 * h + 1], kj[j + 1])));
        uint32_t u = badd2(__byte_perm(d0, d1, 0x5410), __byte_perm(d0, d1, 0x7632));
        u = badd2(u, __shfl_xor_sync(0xffffffffu, u, 1));
        u = badd2(u, __shfl_xor_sync(0xffffffffu, u, 2));
        u = tq == 2 ? u ^ 0x80008000u : 0u;
        qm[2 * h] = u & 0xffffu;
        qm[2 * h + 1] = u >> 16;
        asm volatile("" : "+r"(qm[2 * h]), "+r"(qm[2 * h + 1]));
      }
    }
    STAMP(3);
    uint32_t x0[20], xr[20];
    const int row_lo = b * 64 + w * 16 + gq;
    {
      float o0[12], o1[12], o2[12], o3[12];
#pragma unroll
      for (int i = 0; i < 12; i++) { o0[i] = 0.f; o1[i] = 0.f; o2[i] = 0.f; o3[i] = 0.f; }
      float s0[32], s1[32];
      uint32_t p0[16], p1[16];
      const int dthr = w * 16 + gq - 2 * tq;
      const uint32_t seq = r ? 0x13245u : rb == 1 ? 0x324u : 0x13024u;
      const int anti = r ? 4 : rb == 1 ? 7 : 2;
      const int nit = rb >= 2 ? 5 : 2 * rb + 1 + r;
      mbar_wait(BAR(B_KVOWN + r), 0);
      uint32_t kb = ((sb + kv_addr(4 + r)) & 0x3FFFF) >> 4, kp = kb;
      WG_FENCE();
      qk_issue<0>(s0, q, qm[0], qm[1], kb);
      WG_COMMIT();
#pragma unroll
      for (int i = 0; i < 16; i++) p1[i] = 0u;
      WG_WAIT(0);
      reg_fence(s0);
#pragma unroll 1
      for (int it = 0; it < nit; it++) {
        const int nb = (it && it != anti) ? 4096 : dthr * 16 + 144;
        const uint32_t flip = it == anti ? 0xffffffffu : 0u;
        uint32_t nk[9];
#pragma unroll
        for (int t = 0; t < 9; t++) asm("shl.b32 %0, %1, %2;" : "=r"(nk[t]) : "r"(0xffffffffu), "r"(max(nb - 128 * t, 0)));
        ATT_STEP(1, s1, kb, 3, o3, p1, kp, s0, p0, 1);
        ATT_STEP(2, s0, kb, 0, o0, p0, kb, s1, p1, 1);
        if (it >= 2 && lane == 0) mbar_arrive_pair(BAR(B_ATT2 + 2 - it));
        ATT_STEP(3, s1, kb, 1, o1, p1, kb, s0, p0, 1);
        kp = kb;
        if (it + 1 < nit) {
          const int bi = (seq >> (4 * it + 4)) & 15;
          mbar_wait(bi == 4 ? BAR(B_KVOWN) : BAR(B_KVFULL + bi), 0);
          kb = ((sb + kv_addr(bi)) & 0x3FFFF) >> 4;
        }
        ATT_STEP(0, s0, kb, 2, o2, p0, kp, s1, p1, LASTW);
      }
      WG_FENCE();
      pv_issue<3>(o3, p1, kp);
      WG_COMMIT();
      WG_WAIT(0);
      reg_fence(o0); reg_fence(o1); reg_fence(o2); reg_fence(o3);
      if (lane >= 2 && lane < 5 && lane >= nit) mbar_arrive_pair(BAR(B_ATT2 + 2 - lane));
      if (lane == 0) mbar_arrive(BAR(B_ATTL));
      {
        const uint32_t e0 = 63u << 23;
        const uint32_t ba = (__float_as_uint(o0[8]) - e0) | (__float_as_uint(o0[10]) - e0) | (__float_as_uint(o2[8]) - e0) | (__float_as_uint(o2[10]) - e0);
        const uint32_t bb = (__float_as_uint(o1[0]) - e0) | (__float_as_uint(o1[2]) - e0) | (__float_as_uint(o3[0]) - e0) | (__float_as_uint(o3[2]) - e0);
        if (__builtin_expect(__any_sync(0xffffffffu, ((tq == 2 ? ba : tq == 0 ? bb : 0u) >> 30) != FORCE_SAFE), 0)) {
          const uint8_t* kv = g_kv + (ptrdiff_t)((2 * rb - 4) * 8 + c) * KVB + lane * 4;
          safe_head<0>(o0, q, kv, seq, nit, anti, dthr, tq, tag);
          safe_head<1>(o1, q, kv, seq, nit, anti, dthr, tq, tag);
          safe_head<2>(o2, q, kv, seq, nit, anti, dthr, tq, tag);
          safe_head<3>(o3, q, kv, seq, nit, anti, dthr, tq, tag);
          __syncwarp();
        }
      }
      float inv[4][2];
      inv[0][0] = rcp(__shfl_sync(0xffffffffu, o0[8], (lane & 28) + 2));
      inv[0][1] = rcp(__shfl_sync(0xffffffffu, o0[10], (lane & 28) + 2));
      inv[1][0] = rcp(__shfl_sync(0xffffffffu, o1[0], lane & 28));
      inv[1][1] = rcp(__shfl_sync(0xffffffffu, o1[2], lane & 28));
      inv[2][0] = rcp(__shfl_sync(0xffffffffu, o2[8], (lane & 28) + 2));
      inv[2][1] = rcp(__shfl_sync(0xffffffffu, o2[10], (lane & 28) + 2));
      inv[3][0] = rcp(__shfl_sync(0xffffffffu, o3[0], lane & 28));
      inv[3][1] = rcp(__shfl_sync(0xffffffffu, o3[2], lane & 28));
      const bool lo = tq < 2;
#define OPK(dst, o, t, h) do { x0[dst] = pack2(o[4 * (t)] * inv[h][0], o[4 * (t) + 1] * inv[h][0]); x0[dst + 1] = pack2(o[4 * (t) + 2] * inv[h][1], o[4 * (t) + 3] * inv[h][1]); } while (0)
#define OPK2(dst, oa, ha, ob, hb) do { \
        const float i0 = lo ? inv[ha][0] : inv[hb][0], i1 = lo ? inv[ha][1] : inv[hb][1]; \
        x0[dst] = pack2((lo ? oa[8] : ob[0]) * i0, (lo ? oa[9] : ob[1]) * i0); \
        x0[dst + 1] = pack2((lo ? oa[10] : ob[2]) * i1, (lo ? oa[11] : ob[3]) * i1); } while (0)
      OPK(0, o0, 0, 0); OPK(2, o0, 1, 0); OPK2(4, o0, 0, o1, 1); OPK(6, o1, 1, 1); OPK(8, o1, 2, 1);
      OPK(10, o2, 0, 2); OPK(12, o2, 1, 2); OPK2(14, o2, 2, o3, 3); OPK(16, o3, 1, 3); OPK(18, o3, 2, 3);
    }
    const int bw = b * 4 + w;
    const size_t tile_off = (size_t)bw * 20480 + lane * 16;
    const size_t probe_off = (size_t)bw * 20480 + ((c + lane) & 7) * 2560 + 2544;
    {
#pragma unroll
      for (int k = 0; k < 5; k++) {
        x0[4 * k] = tag16(x0[4 * k], tag);
        stg128(g_o + tile_off + c * 2560 + k * 512, x0[4 * k], x0[4 * k + 1], x0[4 * k + 2], x0[4 * k + 3]);
      }
      STAMP(6);
      const uint32_t pv = ldcg32(g_o + probe_off);
      float acc[40];
      constexpr uint64_t HI = desc_hi(2560, 256, 3);
      const uint64_t db = mkdesc(sb + OFF_WOB, HI);
      mbar_wait(BAR(B_WOB), 0);
      WG_FENCE();
#pragma unroll
      for (int k = 0; k < 5; k++) wg_rs80(acc, x0[4 * k], x0[4 * k + 1], x0[4 * k + 2], x0[4 * k + 3], db + k * 32, k);
      WG_COMMIT();
      uint32_t xa[7][20], ready = __ballot_sync(0xffffffffu, ((pv ^ tag) & TAGM) == 0u);
#pragma unroll
      for (int i = 1; i < 8; i++) {
        probe_wait(ready, i, g_o + probe_off, tag);
        if (i == 7) WG_WAIT(0);
        ld_tile(xa[i - 1], g_o + tile_off + ((c + i) & 7) * 2560);
      }
      STAMP(7);
#pragma unroll
      for (int i = 1; i < 8; i++) {
        if (i == 7) mbar_wait(BAR(B_WOB7), 0);
        fix_tile(xa[i - 1], g_o + tile_off + ((c + i) & 7) * 2560, tag);
        WG_FENCE();
#pragma unroll
        for (int k = 0; k < 5; k++) wg_rs80(acc, xa[i - 1][4 * k], xa[i - 1][4 * k + 1], xa[i - 1][4 * k + 2], xa[i - 1][4 * k + 3], db + i * 800 + k * 32, 1);
        WG_COMMIT();
        if (i == 2) {
          WG_WAIT(1);
          const uint8_t* xp = reinterpret_cast<const uint8_t*>(P.x) + (size_t)row_lo * 1280 + c * 160 + tq * 4;
#pragma unroll
          for (int t = 0; t < 10; t++) {
            xr[2 * t] = ldnc32(xp + t * 16);
            xr[2 * t + 1] = ldnc32(xp + 8 * 1280 + t * 16);
          }
        }
      }
      WG_WAIT(0);
      reg_fence(acc);
      if (lane == 0) mbar_arrive_pair(BAR(B_WODP));
      STAMP(8);
      float sum0 = 0.f, sum1 = 0.f;
#pragma unroll
      for (int t = 0; t < 10; t++) {
        x0[2 * t] = pack2(acc[4 * t] + bf_lo(xr[2 * t]), acc[4 * t + 1] + bf_hi(xr[2 * t]));
        x0[2 * t + 1] = pack2(acc[4 * t + 2] + bf_lo(xr[2 * t + 1]), acc[4 * t + 3] + bf_hi(xr[2 * t + 1]));
      }
#pragma unroll
      for (int k = 0; k < 5; k++) {
        x0[4 * k] = tag16(x0[4 * k], tag);
        stg128(g_h + tile_off + c * 2560 + k * 512, x0[4 * k], x0[4 * k + 1], x0[4 * k + 2], x0[4 * k + 3]);
      }
#pragma unroll
      for (int t = 0; t < 10; t++) {
        sum0 += bf_lo(x0[2 * t]) + bf_hi(x0[2 * t]);
        sum1 += bf_lo(x0[2 * t + 1]) + bf_hi(x0[2 * t + 1]);
      }
      sum0 += __shfl_xor_sync(0xffffffffu, sum0, 1);
      sum1 += __shfl_xor_sync(0xffffffffu, sum1, 1);
      sum0 += __shfl_xor_sync(0xffffffffu, sum0, 2);
      sum1 += __shfl_xor_sync(0xffffffffu, sum1, 2);
      const float mu0 = sum0 * (1.f / 80.f), mu1 = sum1 * (1.f / 80.f);
      float v0 = 0.f, v1 = 0.f;
#pragma unroll
      for (int t = 0; t < 10; t++) {
        const float d0 = bf_lo(x0[2 * t]) - mu0, d1 = bf_hi(x0[2 * t]) - mu0, d2 = bf_lo(x0[2 * t + 1]) - mu1, d3 = bf_hi(x0[2 * t + 1]) - mu1;
        v0 += d0 * d0 + d1 * d1;
        v1 += d2 * d2 + d3 * d3;
      }
      v0 += __shfl_xor_sync(0xffffffffu, v0, 1);
      v1 += __shfl_xor_sync(0xffffffffu, v1, 1);
      v0 += __shfl_xor_sync(0xffffffffu, v0, 2);
      v1 += __shfl_xor_sync(0xffffffffu, v1, 2);
      if (tq < 2) g_hstat[(bw * 8 + c) * 16 + gq + tq * 8] = make_float2(tq ? mu1 : mu0, tag32(tq ? v1 : v0, ep));
    }
    uint32_t ha[56];
    {
      float acc[112];
      constexpr uint64_t HI = desc_hi(5120, 512, 2);
#define W1_ISSUE(xx, i) do { \
        const uint64_t db = mkdesc(sb + w1b_addr(i), HI); \
        mbar_wait(BAR(B_BFULL + (i)), 0); \
        WG_FENCE(); \
        _Pragma("unroll") for (int k = 0; k < 5; k++) wg_rs224(acc, xx[4 * k], xx[4 * k + 1], xx[4 * k + 2], xx[4 * k + 3], db + k * 64, (i) | k); \
        WG_COMMIT(); } while (0)
#define W1_STEP(xx, xp, i) do { \
        fix_tile(xx, ht + ((c + (i)) & 7) * 2560, tag); \
        if (LATEWODP && (i) == 1 && lane == 0) mbar_arrive_pair(BAR(B_WODP)); \
        W1_ISSUE(xx, i); \
        WG_WAIT(1); \
        if ((i) != 4 && lane == 0) mbar_arrive_pair(BAR(B_BEMPTY - 1 + (i))); \
        if ((i) < 5) ld_tile(xp, ht + ((c + (i) + 3) & 7) * 2560); } while (0)
      W1_ISSUE(x0, 0);
      STAMP(9);
      {
        const uint32_t hs = sb + OFF_HST + (uint32_t)(warp * 16 + (lane & 15)) * 160u + (uint32_t)(lane >> 4) * 16u;
        mbar_wait(BAR(B_ATTL), 0);
#pragma unroll
        for (int k = 0; k < 5; k++) stsm4(hs + k * 32, x0[4 * k], x0[4 * k + 1], x0[4 * k + 2], x0[4 * k + 3]);
        fence_async_smem();
        __syncwarp();
        if (lane == 0) mbar_arrive(BAR(B_HST + r));
      }
      const uint8_t* ht = g_h + tile_off;
      uint32_t x1[20], x2[20], x3[20], ready = 0;
      probe_wait(ready, 1, g_h + probe_off, tag);
      ld_tile(x1, ht + ((c + 1) & 7) * 2560);
      probe_wait(ready, 2, g_h + probe_off, tag);
      ld_tile(x2, ht + ((c + 2) & 7) * 2560);
      probe_wait(ready, 3, g_h + probe_off, tag);
      ld_tile(x3, ht + ((c + 3) & 7) * 2560);
      STAMP(10);
#pragma unroll 1
      for (int i = 1; ; i += 4) {
        W1_STEP(x1, x0, i);
        W1_STEP(x2, x1, i + 1);
        W1_STEP(x3, x2, i + 2);
        if (i == 5) break;
        W1_STEP(x0, x3, i + 3);
      }
      uint2 hs[4];
      {
        const float2* hp = &g_hstat[(bw * 8 + tq * 2) * 16 + gq];
        uint32_t n = 0;
        do {
          hs[0] = ldcg64(hp); hs[1] = ldcg64(hp + 16); hs[2] = ldcg64(hp + 8); hs[3] = ldcg64(hp + 24);
        } while (__any_sync(0xffffffffu, (((hs[0].y ^ ep) | (hs[1].y ^ ep) | (hs[2].y ^ ep) | (hs[3].y ^ ep)) & 3u) != 0u) && ++n < SPIN_MAX);
      }
      float mean0, mean1, rs0, rs1;
      {
        const float a0 = __uint_as_float(hs[0].x), a1 = __uint_as_float(hs[1].x), b0 = __uint_as_float(hs[2].x), b1 = __uint_as_float(hs[3].x);
        float t0 = a0 + a1, t1 = b0 + b1;
        t0 += __shfl_xor_sync(0xffffffffu, t0, 1);
        t1 += __shfl_xor_sync(0xffffffffu, t1, 1);
        t0 += __shfl_xor_sync(0xffffffffu, t0, 2);
        t1 += __shfl_xor_sync(0xffffffffu, t1, 2);
        mean0 = t0 * 0.125f;
        mean1 = t1 * 0.125f;
        float u0 = __uint_as_float(hs[0].y) + __uint_as_float(hs[1].y) + 80.f * ((a0 - mean0) * (a0 - mean0) + (a1 - mean0) * (a1 - mean0));
        float u1 = __uint_as_float(hs[2].y) + __uint_as_float(hs[3].y) + 80.f * ((b0 - mean1) * (b0 - mean1) + (b1 - mean1) * (b1 - mean1));
        u0 += __shfl_xor_sync(0xffffffffu, u0, 1);
        u1 += __shfl_xor_sync(0xffffffffu, u1, 1);
        u0 += __shfl_xor_sync(0xffffffffu, u0, 2);
        u1 += __shfl_xor_sync(0xffffffffu, u1, 2);
        rs0 = 0.5f * rsqrtf(u0 * (1.f / 640.f) + 1e-5f);
        rs1 = 0.5f * rsqrtf(u1 * (1.f / 640.f) + 1e-5f);
      }
      mbar_wait(BAR(B_CS1), 0);
      WG_WAIT(0);
      reg_fence(acc);
      if (lane == 0) mbar_arrive_pair(BAR(B_BEMPTY + 7));
      STAMP(11);
      const float n0 = -mean0 * rs0, n1 = -mean1 * rs1;
#pragma unroll
      for (int t = 0; t < 28; t++) {
        const float2 cs = lds64f(sb + OFF_XS + t * 32 + tq * 8);
        const float h0 = fmaf(acc[4 * t], rs0, cs.x * n0), h1 = fmaf(acc[4 * t + 1], rs0, cs.y * n0);
        const float h2 = fmaf(acc[4 * t + 2], rs1, cs.x * n1), h3 = fmaf(acc[4 * t + 3], rs1, cs.y * n1);
        ha[2 * t] = pack2(fmaf(h0, tanh_fast(h0), h0), fmaf(h1, tanh_fast(h1), h1));
        ha[2 * t + 1] = pack2(fmaf(h2, tanh_fast(h2), h2), fmaf(h3, tanh_fast(h3), h3));
      }
      if ((c & 3) == 3) {
#pragma unroll
        for (int t = 48; t < 56; t++) ha[t] = 0u;
      }
    }
    STAMP(12);
    {
      float accA[64], accB[64];
      constexpr uint64_t HI = desc_hi(28672, 1024, 1);
      const uint32_t ost = sb + OFF_OST + (uint32_t)warp * 6144u;
      const uint32_t osw = ost + (uint32_t)(lane & 15) * 128u + (uint32_t)(((lane >> 4) ^ lane) & 7) * 16u;
#define W2_ISSUE(acc, s) do { \
        mbar_wait(BAR(B_W2FULL + (s)), 0); \
        const uint64_t db = mkdesc(sb + ((s) % 3) * W2SLOT, HI); \
        WG_FENCE(); \
        _Pragma("unroll") for (int k = 0; k < 14; k++) wg_rs128(acc, ha[4 * k], ha[4 * k + 1], ha[4 * k + 2], ha[4 * k + 3], db + k * 128, k); \
        WG_COMMIT(); } while (0)
#define W2_OUT(acc, s) do { \
        reg_fence(acc); \
        if ((s) < 2 && lane == 0) mbar_arrive_pair(BAR(B_W2E + (s))); \
        _Pragma("unroll") for (int u = 2 * (s); u < 2 * (s) + 2; u++) { \
          const float* a = &acc[(u & 1) * 32]; \
          if (u >= 3) { if (lane == 0) asm volatile("cp.async.bulk.wait_group.read 2;" ::: "memory"); __syncwarp(); } \
          _Pragma("unroll") for (int t = 0; t < 8; t += 2) \
            stsm4((osw ^ (t * 16)) + (u % 3) * 2048, pack2(a[4 * t], a[4 * t + 1]), pack2(a[4 * t + 2], a[4 * t + 3]), pack2(a[4 * t + 4], a[4 * t + 5]), pack2(a[4 * t + 6], a[4 * t + 7])); \
          fence_async_smem(); \
          __syncwarp(); \
          if (lane == 0) \
            asm volatile("cp.reduce.async.bulk.tensor.2d.global.shared::cta.add.bulk_group [%0, {%2, %3}], [%1];\ncp.async.bulk.commit_group;" \
                         ::"l"(&P.mOut), "r"(ost + (u % 3) * 2048), "r"((c + u) % 10 * 64), "r"(rb * 128 + warp * 16) : "memory"); \
        } } while (0)
      W2_ISSUE(accA, 0);
      W2_ISSUE(accB, 1);
      mbar_wait(BAR(B_BEMPTY + 7), 0);
      mbar_wait(BAR(B_OUTOK + r), 0);
      fence_async_glob();
      WG_WAIT(1);
      W2_OUT(accA, 0);
      STAMP(13);
      W2_ISSUE(accA, 2);
      WG_WAIT(1);
      W2_OUT(accB, 1);
      W2_ISSUE(accB, 3);
      WG_WAIT(1);
      W2_OUT(accA, 2);
      W2_ISSUE(accA, 4);
      WG_WAIT(1);
      W2_OUT(accB, 3);
      STAMP(14);
      WG_WAIT(0);
      W2_OUT(accA, 4);
      STAMP(15);
      if (lane == 0) asm volatile("cp.async.bulk.wait_group.read 0;" ::: "memory");
      STAMP(17);
    }
  }
}

typedef CUresult (*EncodeFn)(CUtensorMap*, CUtensorMapDataType, cuuint32_t, void*, const cuuint64_t*, const cuuint64_t*, const cuuint32_t*,
                             const cuuint32_t*, CUtensorMapInterleave, CUtensorMapSwizzle, CUtensorMapL2promotion, CUtensorMapFloatOOBfill);

static void make_map(EncodeFn enc, CUtensorMap* m, const void* p, int nd, const cuuint64_t* dims, const cuuint64_t* strides, const cuuint32_t* box,
                     CUtensorMapSwizzle sw) {
  const cuuint32_t es[5] = {1, 1, 1, 1, 1};
  enc(m, CU_TENSOR_MAP_DATA_TYPE_BFLOAT16, (cuuint32_t)nd, const_cast<void*>(p), dims, strides, box, es, CU_TENSOR_MAP_INTERLEAVE_NONE, sw,
      CU_TENSOR_MAP_L2_PROMOTION_L2_128B, CU_TENSOR_MAP_FLOAT_OOB_FILL_NONE);
}

extern "C" void kernel_launch(void* const* d_in, const int* in_sizes, int n_in, void* d_out, int out_size) {
  (void)in_sizes; (void)n_in; (void)out_size;
  static EncodeFn enc = nullptr;
  if (!enc) {
    void* f = nullptr;
    cudaDriverEntryPointQueryResult qr;
    cudaGetDriverEntryPoint("cuTensorMapEncodeTiled", &f, cudaEnableDefault, &qr);
    enc = (EncodeFn)f;
    cudaFuncSetAttribute(fused_block_kernel, cudaFuncAttributeMaxDynamicSharedMemorySize, (int)SMEM_BYTES);
  }
  Params P;
  P.x = (const __nv_bfloat16*)d_in[0];
  P.wqkv = (const __nv_bfloat16*)d_in[1];
  P.wo = (const __nv_bfloat16*)d_in[2];
  P.w1 = (const __nv_bfloat16*)d_in[4];
  P.w2 = (const __nv_bfloat16*)d_in[5];
  P.out = (__nv_bfloat16*)d_out;
  { const cuuint64_t d[2] = {640, 2048}, s[1] = {1280}; const cuuint32_t b[2] = {64, 128}; make_map(enc, &P.mX, P.x, 2, d, s, b, CU_TENSOR_MAP_SWIZZLE_128B); }
  { const cuuint64_t d[4] = {32, 640, 20, 3}, s[3] = {3840, 64, 1280}; const cuuint32_t b[4] = {32, 32, 2, 3}; make_map(enc, &P.mWqM, P.wqkv, 4, d, s, b, CU_TENSOR_MAP_SWIZZLE_64B); }
  { const cuuint64_t d[4] = {16, 640, 40, 3}, s[3] = {3840, 32, 1280}; const cuuint32_t b[4] = {16, 32, 1, 3}; make_map(enc, &P.mWqL, P.wqkv, 4, d, s, b, CU_TENSOR_MAP_SWIZZLE_32B); }
  { const cuuint64_t d[3] = {16, 640, 40}, s[2] = {1280, 32}; const cuuint32_t b[3] = {16, 80, 5}; make_map(enc, &P.mWo, P.wo, 3, d, s, b, CU_TENSOR_MAP_SWIZZLE_32B); }
  { const cuuint64_t d[3] = {32, 640, 54}, s[2] = {3456, 64}; const cuuint32_t b[3] = {32, 80, 4}; make_map(enc, &P.mW1a, P.w1, 3, d, s, b, CU_TENSOR_MAP_SWIZZLE_64B); }
  { const cuuint64_t d[3] = {32, 640, 54}, s[2] = {3456, 64}; const cuuint32_t b[3] = {32, 80, 3}; make_map(enc, &P.mW1b, P.w1, 3, d, s, b, CU_TENSOR_MAP_SWIZZLE_64B); }
  { const cuuint64_t d[2] = {640, 1728}, s[1] = {1280}; const cuuint32_t b[2] = {64, 112}; make_map(enc, &P.mW2, P.w2, 2, d, s, b, CU_TENSOR_MAP_SWIZZLE_128B); }
  { const cuuint64_t d[2] = {640, 2048}, s[1] = {1280}; const cuuint32_t b[2] = {80, 64}; make_map(enc, &P.mOutH, P.out, 2, d, s, b, CU_TENSOR_MAP_SWIZZLE_NONE); }
  { const cuuint64_t d[2] = {640, 2048}, s[1] = {1280}; const cuuint32_t b[2] = {64, 16}; make_map(enc, &P.mOut, P.out, 2, d, s, b, CU_TENSOR_MAP_SWIZZLE_128B); }
  fused_block_kernel<<<SMIDMAP ? 132 : 128, 384, SMEM_BYTES, cudaStreamPerThread>>>(P);
}
```

```cpp
#include <cuda_runtime.h>
#include <cuda.h>
#include <cuda_bf16.h>
#include <stdint.h>

#define PROF 0
#define XPOS 1
#define PF0 1
#define LASTW 1
#define KVP 8
#define LATEWODP 0
#define OSYNC 0
#define FORCE_SAFE 0u

__device__ __align__(1024) uint8_t g_kv[32 * 8 * 22528];
__device__ __align__(1024) uint8_t g_o[32 * 4 * 8 * 2560];
__device__ __align__(1024) uint8_t g_h[32 * 4 * 8 * 2560];
__device__ __align__(1024) float2 g_hstat[32 * 4 * 8 * 16];
__device__ __align__(128) uint32_t g_oflag[32 * 8];
__device__ __align__(128) float2 g_xstat[2048];
__device__ __align__(128) float g_csq[8 * 8 * 240];
__device__ __align__(128) float g_cs1[8 * 8 * 224];
__device__ __align__(128) uint32_t g_epoch[128 * 32];
#define STAMP(slot)
#define STAMPW(slot)

struct Params {
  const __nv_bfloat16 *x, *wqkv, *wo, *w1, *w2;
  __nv_bfloat16* out;
  CUtensorMap mX, mWqM, mWqL, mWo, mW1a, mW1b, mW2, mOutH, mOut;
};

constexpr uint32_t QST = 47104;
constexpr uint32_t KVB = 22528;
constexpr uint32_t OFF_WOB = 0;
constexpr uint32_t OFF_PRE = 188416;
constexpr uint32_t OFF_XROW = 196608;
constexpr uint32_t W2SLOT = 57344;
constexpr uint32_t OFF_OST = 174080;
constexpr uint32_t OFF_HST = 209920;
constexpr uint32_t OFF_CS = 229376;
constexpr uint32_t OFF_XST = 230336;
constexpr uint32_t OFF_XS = 230912;
constexpr uint32_t OFF_MISC = 231808;
constexpr uint32_t SMEM_BYTES = 232448;

enum {
  B_QFULL = 0, B_KVFULL = 4, B_KVLAND = 8, B_WOB = 12, B_WOB7 = 13, B_BFULL = 14, B_W2FULL = 22, B_CS1 = 27, B_OUTOK = 28,
  B_KVOWN = 30, B_HST = 32, B_STAT = 34, B_XROW = 35,
  B_Q23 = 36, B_PRE = 37, B_ATTL = 38,
  B_QEMPTY = 42, B_W2E = 46, B_WODP = 48, B_BEMPTY = 49, B_ATT4 = 58, B_ATT3 = 59,
  B_ATT2 = 60
};
constexpr uint32_t TAGM = 0x00010001u;
constexpr uint32_t SPIN_MAX = 1u << 18;

__device__ __forceinline__ uint32_t s2u(const void* p) { return (uint32_t)__cvta_generic_to_shared(p); }
__device__ __forceinline__ void mbar_init(uint32_t b, int c) { asm volatile("mbarrier.init.shared::cta.b64 [%0], %1;" ::"r"(b), "r"(c)); }
__device__ __forceinline__ void mbar_expect(uint32_t b, int bytes) { asm volatile("mbarrier.arrive.expect_tx.shared::cta.b64 _, [%0], %1;" ::"r"(b), "r"(bytes) : "memory"); }
__device__ __forceinline__ void mbar_arrive(uint32_t b) { asm volatile("mbarrier.arrive.shared::cta.b64 _, [%0];" ::"r"(b) : "memory"); }
__device__ __forceinline__ void mbar_arrive_pair(uint32_t b) {
  asm volatile("{\n.reg .b32 r;\nmapa.shared::cluster.u32 r, %0, 0;\nmbarrier.arrive.shared::cluster.b64 _, [r];\n"
               "mapa.shared::cluster.u32 r, %0, 1;\nmbarrier.arrive.shared::cluster.b64 _, [r];\n}" ::"r"(b) : "memory");
}
__device__ __forceinline__ void mbar_wait(uint32_t b, uint32_t ph) {
  asm volatile("{\n.reg .pred p;\n.reg .u32 n;\nmov.u32 n, 0;\nW%=:\nmbarrier.try_wait.parity.shared::cta.b64 p, [%0], %1;\n"
               "add.u32 n, n, 1;\nsetp.lt.and.u32 p, n, 0x100000, !p;\n@p bra W%=;\n}" ::"r"(b), "r"(ph) : "memory");
}
__device__ __forceinline__ void tma2d(uint32_t dst, const CUtensorMap* m, int c0, int c1, uint32_t bar) {
  asm volatile("cp.async.bulk.tensor.2d.shared::cluster.global.mbarrier::complete_tx::bytes [%0], [%1, {%3, %4}], [%2];" ::"r"(dst), "l"(m), "r"(bar), "r"(c0), "r"(c1) : "memory");
}
__device__ __forceinline__ void tma2d_mc(uint32_t dst, const CUtensorMap* m, int c0, int c1, uint32_t bar) {
  asm volatile("cp.async.bulk.tensor.2d.shared::cluster.global.mbarrier::complete_tx::bytes.multicast::cluster [%0], [%1, {%3, %4}], [%2], %5;" ::"r"(dst), "l"(m), "r"(bar), "r"(c0), "r"(c1), "h"((uint16_t)3) : "memory");
}
__device__ __forceinline__ void tma3d_mc(uint32_t dst, const CUtensorMap* m, int c0, int c1, int c2, uint32_t bar) {
  asm volatile("cp.async.bulk.tensor.3d.shared::cluster.global.mbarrier::complete_tx::bytes.multicast::cluster [%0], [%1, {%3, %4, %5}], [%2], %6;" ::"r"(dst), "l"(m), "r"(bar), "r"(c0), "r"(c1), "r"(c2), "h"((uint16_t)3) : "memory");
}
__device__ __forceinline__ void tma4d_mc(uint32_t dst, const CUtensorMap* m, int c0, int c1, int c2, int c3, uint32_t bar) {
  asm volatile("cp.async.bulk.tensor.4d.shared::cluster.global.mbarrier::complete_tx::bytes.multicast::cluster [%0], [%1, {%3, %4, %5, %6}], [%2], %7;" ::"r"(dst), "l"(m), "r"(bar), "r"(c0), "r"(c1), "r"(c2), "r"(c3), "h"((uint16_t)3) : "memory");
}
__device__ __forceinline__ void bulk_load(uint32_t dst, const void* src, int bytes, uint32_t bar) {
  asm volatile("cp.async.bulk.shared::cluster.global.mbarrier::complete_tx::bytes [%0], [%1], %2, [%3];" ::"r"(dst), "l"(src), "r"(bytes), "r"(bar) : "memory");
}
__device__ __forceinline__ void tma4d_pf(const CUtensorMap* m, int c0, int c1, int c2, int c3) {
  asm volatile("cp.async.bulk.prefetch.tensor.4d.L2.global [%0, {%1, %2, %3, %4}];" ::"l"(m), "r"(c0), "r"(c1), "r"(c2), "r"(c3) : "memory");
}
__device__ __forceinline__ void l2_prefetch_bulk(const void* p, int bytes) { asm volatile("cp.async.bulk.prefetch.L2.global [%0], %1;" ::"l"(p), "r"(bytes) : "memory"); }
__device__ __forceinline__ void l2_prefetch(const void* p) { asm volatile("prefetch.global.L2 [%0];" ::"l"(p)); }
__device__ __forceinline__ uint32_t ld_flag(const uint32_t* p) { uint32_t v; asm volatile("ld.acquire.gpu.global.u32 %0, [%1];" : "=r"(v) : "l"(p) : "memory"); return v; }
__device__ __forceinline__ void st_flag(uint32_t* p, uint32_t v) { asm volatile("st.relaxed.gpu.global.u32 [%0], %1;" ::"l"(p), "r"(v) : "memory"); }
__device__ __forceinline__ void fence_gpu() { asm volatile("fence.acq_rel.gpu;" ::: "memory"); }
__device__ __forceinline__ void fence_async_smem() { asm volatile("fence.proxy.async.shared::cta;" ::: "memory"); }
__device__ __forceinline__ void fence_async_glob() { asm volatile("fence.proxy.async.global;" ::: "memory"); }
__device__ __forceinline__ uint4 ldcg128(const void* p) { uint4 v; asm volatile("ld.relaxed.gpu.global.v4.u32 {%0,%1,%2,%3}, [%4];" : "=r"(v.x), "=r"(v.y), "=r"(v.z), "=r"(v.w) : "l"(p) : "memory"); return v; }
__device__ __forceinline__ uint4 ldnc128(const void* p) { uint4 v; asm volatile("ld.global.nc.v4.u32 {%0,%1,%2,%3}, [%4];" : "=r"(v.x), "=r"(v.y), "=r"(v.z), "=r"(v.w) : "l"(p)); return v; }
__device__ __forceinline__ uint32_t ldnc32(const void* p) { uint32_t v; asm volatile("ld.global.nc.u32 %0, [%1];" : "=r"(v) : "l"(p)); return v; }
__device__ __forceinline__ uint2 ldcg64(const void* p) { uint2 v; asm volatile("ld.relaxed.gpu.global.v2.u32 {%0,%1}, [%2];" : "=r"(v.x), "=r"(v.y) : "l"(p) : "memory"); return v; }
__device__ __forceinline__ uint32_t ldcg32(const void* p) { uint32_t v; asm volatile("ld.relaxed.gpu.global.u32 %0, [%1];" : "=r"(v) : "l"(p) : "memory"); return v; }
__device__ __forceinline__ uint32_t pack2(float lo, float hi) { uint32_t r; asm("cvt.rn.bf16x2.f32 %0, %1, %2;" : "=r"(r) : "f"(hi), "f"(lo)); return r; }
__device__ __forceinline__ float bf_lo(uint32_t v) { return __uint_as_float(v << 16); }
__device__ __forceinline__ float bf_hi(uint32_t v) { return __uint_as_float(v & 0xffff0000u); }
__device__ __forceinline__ float ex2(float x) { float y; asm("ex2.approx.ftz.f32 %0, %1;" : "=f"(y) : "f"(x)); return y; }
__device__ __forceinline__ float rcp(float x) { float y; asm("rcp.approx.ftz.f32 %0, %1;" : "=f"(y) : "f"(x)); return y; }
__device__ __forceinline__ float tanh_fast(float x) { float y; asm("tanh.approx.f32 %0, %1;" : "=f"(y) : "f"(x)); return y; }
__device__ __forceinline__ void stsm4(uint32_t a, uint32_t r0, uint32_t r1, uint32_t r2, uint32_t r3) {
  asm volatile("stmatrix.sync.aligned.m8n8.x4.shared.b16 [%0], {%1,%2,%3,%4};" ::"r"(a), "r"(r0), "r"(r1), "r"(r2), "r"(r3) : "memory");
}
__device__ __forceinline__ void ldsm4(uint32_t* r, uint32_t a) {
  asm volatile("ldmatrix.sync.aligned.m8n8.x4.shared.b16 {%0,%1,%2,%3}, [%4];" : "=r"(r[0]), "=r"(r[1]), "=r"(r[2]), "=r"(r[3]) : "r"(a) : "memory");
}
__device__ __forceinline__ float2 lds64f(uint32_t a) { float2 v; asm volatile("ld.shared.v2.f32 {%0,%1}, [%2];" : "=f"(v.x), "=f"(v.y) : "r"(a)); return v; }
__device__ __forceinline__ constexpr uint64_t desc_hi(uint32_t lbo, uint32_t sbo, uint32_t sw) {
  return ((uint64_t)(lbo >> 4) << 16) | ((uint64_t)(sbo >> 4) << 32) | ((uint64_t)sw << 62);
}
__device__ __forceinline__ uint64_t mkdesc(uint32_t addr, uint64_t hi) { return hi | (uint64_t)((addr & 0x3FFFF) >> 4); }
#define WG_FENCE() asm volatile("wgmma.fence.sync.aligned;" ::: "memory")
#define WG_COMMIT() asm volatile("wgmma.commit_group.sync.aligned;" ::: "memory")
#define WG_WAIT_(n) asm volatile("wgmma.wait_group.sync.aligned " #n ";" ::: "memory")
#define WG_WAIT(n) WG_WAIT_(n)
template <int N> __device__ __forceinline__ void reg_fence(float (&a)[N]) {
#pragma unroll
  for (int i = 0; i < N; i++) asm volatile("" : "+f"(a[i])::"memory");
}

__device__ __forceinline__ void wg_rs192(float (&d)[96], uint32_t a0, uint32_t a1, uint32_t a2, uint32_t a3, uint64_t db, int sd) {
  asm volatile("{\n.reg .pred p;\nsetp.ne.b32 p, %101, 0;\n"
  "wgmma.mma_async.sync.aligned.m64n192k16.f32.bf16.bf16 {%0, %1, %2, %3, %4, %5, %6, %7, %8, %9, %10, %11, %12, %13, %14, %15, %16, %17, %18, %19, %20, %21, %22, %23, %24, %25, %26, %27, %28, %29, %30, %31, %32, %33, %34, %35, %36, %37, %38, %39, %40, %41, %42, %43, %44, %45, %46, %47, %48, %49, %50, %51, %52, %53, %54, %55, %56, %57, %58, %59, %60, %61, %62, %63, %64, %65, %66, %67, %68, %69, %70, %71, %72, %73, %74, %75, %76, %77, %78, %79, %80, %81, %82, %83, %84, %85, %86, %87, %88, %89, %90, %91, %92, %93, %94, %95}, {%96, %97, %98, %99}, %100, p, 1, 1, 1;\n}\n"
  : "+f"(d[0]), "+f"(d[1]), "+f"(d[2]), "+f"(d[3]), "+f"(d[4]), "+f"(d[5]), "+f"(d[6]), "+f"(d[7]), "+f"(d[8]), "+f"(d[9]), "+f"(d[10]), "+f"(d[11]), "+f"(d[12]), "+f"(d[13]), "+f"(d[14]), "+f"(d[15]), "+f"(d[16]), "+f"(d[17]), "+f"(d[18]), "+f"(d[19]), "+f"(d[20]), "+f"(d[21]), "+f"(d[22]), "+f"(d[23]), "+f"(d[24]), "+f"(d[25]), "+f"(d[26]), "+f"(d[27]), "+f"(d[28]), "+f"(d[29]), "+f"(d[30]), "+f"(d[31]), "+f"(d[32]), "+f"(d[33]), "+f"(d[34]), "+f"(d[35]), "+f"(d[36]), "+f"(d[37]), "+f"(d[38]), "+f"(d[39]), "+f"(d[40]), "+f"(d[41]), "+f"(d[42]), "+f"(d[43]), "+f"(d[44]), "+f"(d[45]), "+f"(d[46]), "+f"(d[47]), "+f"(d[48]), "+f"(d[49]), "+f"(d[50]), "+f"(d[51]), "+f"(d[52]), "+f"(d[53]), "+f"(d[54]), "+f"(d[55]), "+f"(d[56]), "+f"(d[57]), "+f"(d[58]), "+f"(d[59]), "+f"(d[60]), "+f"(d[61]), "+f"(d[62]), "+f"(d[63]), "+f"(d[64]), "+f"(d[65]), "+f"(d[66]), "+f"(d[67]), "+f"(d[68]), "+f"(d[69]), "+f"(d[70]), "+f"(d[71]), "+f"(d[72]), "+f"(d[73]), "+f"(d[74]), "+f"(d[75]), "+f"(d[76]), "+f"(d[77]), "+f"(d[78]), "+f"(d[79]), "+f"(d[80]), "+f"(d[81]), "+f"(d[82]), "+f"(d[83]), "+f"(d[84]), "+f"(d[85]), "+f"(d[86]), "+f"(d[87]), "+f"(d[88]), "+f"(d[89]), "+f"(d[90]), "+f"(d[91]), "+f"(d[92]), "+f"(d[93]), "+f"(d[94]), "+f"(d[95]) : "r"(a0), "r"(a1), "r"(a2), "r"(a3), "l"(db), "r"(sd));
}
__device__ __forceinline__ void wg_rs48(float (&d)[24], uint32_t a0, uint32_t a1, uint32_t a2, uint32_t a3, uint64_t db, int sd) {
  asm volatile("{\n.reg .pred p;\nsetp.ne.b32 p, %29, 0;\n"
  "wgmma.mma_async.sync.aligned.m64n48k16.f32.bf16.bf16 {%0, %1, %2, %3, %4, %5, %6, %7, %8, %9, %10, %11, %12, %13, %14, %15, %16, %17, %18, %19, %20, %21, %22, %23}, {%24, %25, %26, %27}, %28, p, 1, 1, 1;\n}\n"
  : "+f"(d[0]), "+f"(d[1]), "+f"(d[2]), "+f"(d[3]), "+f"(d[4]), "+f"(d[5]), "+f"(d[6]), "+f"(d[7]), "+f"(d[8]), "+f"(d[9]), "+f"(d[10]), "+f"(d[11]), "+f"(d[12]), "+f"(d[13]), "+f"(d[14]), "+f"(d[15]), "+f"(d[16]), "+f"(d[17]), "+f"(d[18]), "+f"(d[19]), "+f"(d[20]), "+f"(d[21]), "+f"(d[22]), "+f"(d[23]) : "r"(a0), "r"(a1), "r"(a2), "r"(a3), "l"(db), "r"(sd));
}
__device__ __forceinline__ void wg_rs80(float (&d)[40], uint32_t a0, uint32_t a1, uint32_t a2, uint32_t a3, uint64_t db, int sd) {
  asm volatile("{\n.reg .pred p;\nsetp.ne.b32 p, %45, 0;\n"
  "wgmma.mma_async.sync.aligned.m64n80k16.f32.bf16.bf16 {%0, %1, %2, %3, %4, %5, %6, %7, %8, %9, %10, %11, %12, %13, %14, %15, %16, %17, %18, %19, %20, %21, %22, %23, %24, %25, %26, %27, %28, %29, %30, %31, %32, %33, %34, %35, %36, %37, %38, %39}, {%40, %41, %42, %43}, %44, p, 1, 1, 1;\n}\n"
  : "+f"(d[0]), "+f"(d[1]), "+f"(d[2]), "+f"(d[3]), "+f"(d[4]), "+f"(d[5]), "+f"(d[6]), "+f"(d[7]), "+f"(d[8]), "+f"(d[9]), "+f"(d[10]), "+f"(d[11]), "+f"(d[12]), "+f"(d[13]), "+f"(d[14]), "+f"(d[15]), "+f"(d[16]), "+f"(d[17]), "+f"(d[18]), "+f"(d[19]), "+f"(d[20]), "+f"(d[21]), "+f"(d[22]), "+f"(d[23]), "+f"(d[24]), "+f"(d[25]), "+f"(d[26]), "+f"(d[27]), "+f"(d[28]), "+f"(d[29]), "+f"(d[30]), "+f"(d[31]), "+f"(d[32]), "+f"(d[33]), "+f"(d[34]), "+f"(d[35]), "+f"(d[36]), "+f"(d[37]), "+f"(d[38]), "+f"(d[39]) : "r"(a0), "r"(a1), "r"(a2), "r"(a3), "l"(db), "r"(sd));
}
__device__ __forceinline__ void wg_rs224(float (&d)[112], uint32_t a0, uint32_t a1, uint32_t a2, uint32_t a3, uint64_t db, int sd) {
  asm volatile("{\n.reg .pred p;\nsetp.ne.b32 p, %117, 0;\n"
  "wgmma.mma_async.sync.aligned.m64n224k16.f32.bf16.bf16 {%0, %1, %2, %3, %4, %5, %6, %7, %8, %9, %10, %11, %12, %13, %14, %15, %16, %17, %18, %19, %20, %21, %22, %23, %24, %25, %26, %27, %28, %29, %30, %31, %32, %33, %34, %35, %36, %37, %38, %39, %40, %41, %42, %43, %44, %45, %46, %47, %48, %49, %50, %51, %52, %53, %54, %55, %56, %57, %58, %59, %60, %61, %62, %63, %64, %65, %66, %67, %68, %69, %70, %71, %72, %73, %74, %75, %76, %77, %78, %79, %80, %81, %82, %83, %84, %85, %86, %87, %88, %89, %90, %91, %92, %93, %94, %95, %96, %97, %98, %99, %100, %101, %102, %103, %104, %105, %106, %107, %108, %109, %110, %111}, {%112, %113, %114, %115}, %116, p, 1, 1, 1;\n}\n"
  : "+f"(d[0]), "+f"(d[1]), "+f"(d[2]), "+f"(d[3]), "+f"(d[4]), "+f"(d[5]), "+f"(d[6]), "+f"(d[7]), "+f"(d[8]), "+f"(d[9]), "+f"(d[10]), "+f"(d[11]), "+f"(d[12]), "+f"(d[13]), "+f"(d[14]), "+f"(d[15]), "+f"(d[16]), "+f"(d[17]), "+f"(d[18]), "+f"(d[19]), "+f"(d[20]), "+f"(d[21]), "+f"(d[22]), "+f"(d[23]), "+f"(d[24]), "+f"(d[25]), "+f"(d[26]), "+f"(d[27]), "+f"(d[28]), "+f"(d[29]), "+f"(d[30]), "+f"(d[31]), "+f"(d[32]), "+f"(d[33]), "+f"(d[34]), "+f"(d[35]), "+f"(d[36]), "+f"(d[37]), "+f"(d[38]), "+f"(d[39]), "+f"(d[40]), "+f"(d[41]), "+f"(d[42]), "+f"(d[43]), "+f"(d[44]), "+f"(d[45]), "+f"(d[46]), "+f"(d[47]), "+f"(d[48]), "+f"(d[49]), "+f"(d[50]), "+f"(d[51]), "+f"(d[52]), "+f"(d[53]), "+f"(d[54]), "+f"(d[55]), "+f"(d[56]), "+f"(d[57]), "+f"(d[58]), "+f"(d[59]), "+f"(d[60]), "+f"(d[61]), "+f"(d[62]), "+f"(d[63]), "+f"(d[64]), "+f"(d[65]), "+f"(d[66]), "+f"(d[67]), "+f"(d[68]), "+f"(d[69]), "+f"(d[70]), "+f"(d[71]), "+f"(d[72]), "+f"(d[73]), "+f"(d[74]), "+f"(d[75]), "+f"(d[76]), "+f"(d[77]), "+f"(d[78]), "+f"(d[79]), "+f"(d[80]), "+f"(d[81]), "+f"(d[82]), "+f"(d[83]), "+f"(d[84]), "+f"(d[85]), "+f"(d[86]), "+f"(d[87]), "+f"(d[88]), "+f"(d[89]), "+f"(d[90]), "+f"(d[91]), "+f"(d[92]), "+f"(d[93]), "+f"(d[94]), "+f"(d[95]), "+f"(d[96]), "+f"(d[97]), "+f"(d[98]), "+f"(d[99]), "+f"(d[100]), "+f"(d[101]), "+f"(d[102]), "+f"(d[103]), "+f"(d[104]), "+f"(d[105]), "+f"(d[106]), "+f"(d[107]), "+f"(d[108]), "+f"(d[109]), "+f"(d[110]), "+f"(d[111]) : "r"(a0), "r"(a1), "r"(a2), "r"(a3), "l"(db), "r"(sd));
}
__device__ __forceinline__ void wg_rs64k(float (&d)[32], uint32_t a0, uint32_t a1, uint32_t a2, uint32_t a3, uint64_t db, int sd) {
  asm volatile("{\n.reg .pred p;\nsetp.ne.b32 p, %37, 0;\n"
  "wgmma.mma_async.sync.aligned.m64n64k16.f32.bf16.bf16 {%0, %1, %2, %3, %4, %5, %6, %7, %8, %9, %10, %11, %12, %13, %14, %15, %16, %17, %18, %19, %20, %21, %22, %23, %24, %25, %26, %27, %28, %29, %30, %31}, {%32, %33, %34, %35}, %36, p, 1, 1, 0;\n}\n"
  : "+f"(d[0]), "+f"(d[1]), "+f"(d[2]), "+f"(d[3]), "+f"(d[4]), "+f"(d[5]), "+f"(d[6]), "+f"(d[7]), "+f"(d[8]), "+f"(d[9]), "+f"(d[10]), "+f"(d[11]), "+f"(d[12]), "+f"(d[13]), "+f"(d[14]), "+f"(d[15]), "+f"(d[16]), "+f"(d[17]), "+f"(d[18]), "+f"(d[19]), "+f"(d[20]), "+f"(d[21]), "+f"(d[22]), "+f"(d[23]), "+f"(d[24]), "+f"(d[25]), "+f"(d[26]), "+f"(d[27]), "+f"(d[28]), "+f"(d[29]), "+f"(d[30]), "+f"(d[31]) : "r"(a0), "r"(a1), "r"(a2), "r"(a3), "l"(db), "r"(sd));
}
__device__ __forceinline__ void wg_rs24(float (&d)[12], uint32_t a0, uint32_t a1, uint32_t a2, uint32_t a3, uint64_t db, int sd) {
  asm volatile("{\n.reg .pred p;\nsetp.ne.b32 p, %17, 0;\n"
  "wgmma.mma_async.sync.aligned.m64n24k16.f32.bf16.bf16 {%0, %1, %2, %3, %4, %5, %6, %7, %8, %9, %10, %11}, {%12, %13, %14, %15}, %16, p, 1, 1, 1;\n}\n"
  : "+f"(d[0]), "+f"(d[1]), "+f"(d[2]), "+f"(d[3]), "+f"(d[4]), "+f"(d[5]), "+f"(d[6]), "+f"(d[7]), "+f"(d[8]), "+f"(d[9]), "+f"(d[10]), "+f"(d[11]) : "r"(a0), "r"(a1), "r"(a2), "r"(a3), "l"(db), "r"(sd));
}
__device__ __forceinline__ void wg_rs128(float (&d)[64], uint32_t a0, uint32_t a1, uint32_t a2, uint32_t a3, uint64_t db, int sd) {
  asm volatile("{\n.reg .pred p;\nsetp.ne.b32 p, %69, 0;\n"
  "wgmma.mma_async.sync.aligned.m64n128k16.f32.bf16.bf16 {%0, %1, %2, %3, %4, %5, %6, %7, %8, %9, %10, %11, %12, %13, %14, %15, %16, %17, %18, %19, %20, %21, %22, %23, %24, %25, %26, %27, %28, %29, %30, %31, %32, %33, %34, %35, %36, %37, %38, %39, %40, %41, %42, %43, %44, %45, %46, %47, %48, %49, %50, %51, %52, %53, %54, %55, %56, %57, %58, %59, %60, %61, %62, %63}, {%64, %65, %66, %67}, %68, p, 1, 1, 1;\n}\n"
  : "+f"(d[0]), "+f"(d[1]), "+f"(d[2]), "+f"(d[3]), "+f"(d[4]), "+f"(d[5]), "+f"(d[6]), "+f"(d[7]), "+f"(d[8]), "+f"(d[9]), "+f"(d[10]), "+f"(d[11]), "+f"(d[12]), "+f"(d[13]), "+f"(d[14]), "+f"(d[15]), "+f"(d[16]), "+f"(d[17]), "+f"(d[18]), "+f"(d[19]), "+f"(d[20]), "+f"(d[21]), "+f"(d[22]), "+f"(d[23]), "+f"(d[24]), "+f"(d[25]), "+f"(d[26]), "+f"(d[27]), "+f"(d[28]), "+f"(d[29]), "+f"(d[30]), "+f"(d[31]), "+f"(d[32]), "+f"(d[33]), "+f"(d[34]), "+f"(d[35]), "+f"(d[36]), "+f"(d[37]), "+f"(d[38]), "+f"(d[39]), "+f"(d[40]), "+f"(d[41]), "+f"(d[42]), "+f"(d[43]), "+f"(d[44]), "+f"(d[45]), "+f"(d[46]), "+f"(d[47]), "+f"(d[48]), "+f"(d[49]), "+f"(d[50]), "+f"(d[51]), "+f"(d[52]), "+f"(d[53]), "+f"(d[54]), "+f"(d[55]), "+f"(d[56]), "+f"(d[57]), "+f"(d[58]), "+f"(d[59]), "+f"(d[60]), "+f"(d[61]), "+f"(d[62]), "+f"(d[63]) : "r"(a0), "r"(a1), "r"(a2), "r"(a3), "l"(db), "r"(sd));
}

__device__ __forceinline__ uint32_t kv_addr(int i) {
  return 94208u + KVB * (uint32_t)((0x104253u >> (4 * i)) & 15u);
}
__device__ __forceinline__ uint32_t w1b_addr(int s) {
  return (s == 3 || s == 4) ? (uint32_t)(s - 3) * 35840u : 102400u + (uint32_t)(s >= 5 ? s - 5 : s) * 35840u;
}
__device__ __forceinline__ void stg128(void* p, uint32_t a, uint32_t b, uint32_t c, uint32_t d) {
  asm volatile("st.global.v4.u32 [%0], {%1,%2,%3,%4};" ::"l"(p), "r"(a), "r"(b), "r"(c), "r"(d) : "memory");
}
__device__ __forceinline__ void stg32(void* p, uint32_t a) { asm volatile("st.global.u32 [%0], %1;" ::"l"(p), "r"(a) : "memory"); }
__device__ __forceinline__ void ld_tile(uint32_t (&a)[20], const uint8_t* p) {
#pragma unroll
  for (int k = 0; k < 5; k++)
    asm volatile("ld.relaxed.gpu.global.v4.u32 {%0,%1,%2,%3}, [%4];" : "=r"(a[4 * k]), "=r"(a[4 * k + 1]), "=r"(a[4 * k + 2]), "=r"(a[4 * k + 3]) : "l"(p + k * 512) : "memory");
}
__device__ __forceinline__ uint32_t tag16(uint32_t v, uint32_t tag) { return (v & ~TAGM) | tag; }
__device__ __forceinline__ float tag32(float v, uint32_t ep) { return __uint_as_float((__float_as_uint(v) & ~3u) | ep); }
__device__ __forceinline__ void fix_tile(uint32_t (&a)[20], const uint8_t* p, uint32_t tag) {
  uint32_t n = 0;
  while (__any_sync(0xffffffffu, (((a[0] ^ tag) | (a[4] ^ tag) | (a[8] ^ tag) | (a[12] ^ tag) | (a[16] ^ tag)) & TAGM) != 0u) && ++n < SPIN_MAX) ld_tile(a, p);
}
__device__ __forceinline__ void probe_wait(uint32_t& ready, int i, const void* p, uint32_t tag) {
  uint32_t n = 0;
  while (!((ready >> i) & 1u) && ++n < SPIN_MAX) ready = __ballot_sync(0xffffffffu, ((ldcg32(p) ^ tag) & TAGM) == 0u);
}
__device__ __forceinline__ void gather8(uint8_t* dst, const float* p, int stride, uint32_t ep, bool on) {
  uint4 v[8];
  uint32_t n = 0, bad;
  do {
    bad = 0;
#pragma unroll
    for (int i = 0; i < 8; i++) v[i] = ldcg128(p + i * stride);
#pragma unroll
    for (int i = 0; i < 8; i++) bad |= (v[i].x ^ ep) | (v[i].w ^ ep);
  } while (__any_sync(0xffffffffu, (bad & 3u) != 0u) && ++n < SPIN_MAX);
  float4 s = make_float4(0.f, 0.f, 0.f, 0.f);
#pragma unroll
  for (int i = 0; i < 8; i++) { s.x += __uint_as_float(v[i].x); s.y += __uint_as_float(v[i].y); s.z += __uint_as_float(v[i].z); s.w += __uint_as_float(v[i].w); }
  if (on) *reinterpret_cast<float4*>(dst) = s;
}

__device__ __forceinline__ uint64_t desc2(uint32_t lo, uint32_t hi) { uint64_t d; asm("mov.b64 %0, {%1, %2};" : "=l"(d) : "r"(lo), "r"(hi)); return d; }
template <int H>
__device__ __forceinline__ void qk_issue(float (&s)[32], const uint32_t (&q)[24], uint32_t m0, uint32_t m1, uint32_t kd) {
  constexpr int J0 = (H == 0) ? 0 : (H == 1) ? 2 : (H == 2) ? 5 : 7;
  wg_rs64k(s, q[H * 6 + 0], q[H * 6 + 1], q[H * 6 + 2], q[H * 6 + 3], desc2(kd + (0x400000u + J0 * 64), 8u), 0);
  wg_rs64k(s, q[H * 6 + 4], q[H * 6 + 5], m0, m1, desc2(kd + (((10 - J0) * 64u << 16) + (J0 + 2) * 64), 8u), 1);
}
template <int H>
__device__ __forceinline__ void pv_issue(float (&o)[12], const uint32_t (&p)[16], uint32_t kd) {
#pragma unroll
  for (int i = 0; i < 4; i++)
    wg_rs24(o, p[4 * i], p[4 * i + 1], p[4 * i + 2], p[4 * i + 3], desc2(kd + (0x80000u + 640 + 3 * H * 64 + i * 16), 64u), 1);
}
__device__ __forceinline__ void sm_exp(const float (&s)[32], uint32_t (&p)[16], const uint32_t (&nk)[9], uint32_t flip) {
#pragma unroll
  for (int t = 0; t < 8; t++) {
    p[2 * t] = pack2(ex2(s[4 * t]), ex2(s[4 * t + 1])) & (~nk[t + 1] ^ flip);
    p[2 * t + 1] = pack2(ex2(s[4 * t + 2]), ex2(s[4 * t + 3])) & (~nk[t] ^ flip);
  }
#pragma unroll
  for (int i = 0; i < 16; i++) asm volatile("" : "+r"(p[i])::"memory");
}
__device__ __forceinline__ void mma16816(float* d, uint32_t a0, uint32_t a1, uint32_t a2, uint32_t a3, uint32_t b0, uint32_t b1) {
  asm volatile("mma.sync.aligned.m16n8k16.row.col.f32.bf16.bf16.f32 {%0,%1,%2,%3}, {%4,%5,%6,%7}, {%8,%9}, {%0,%1,%2,%3};"
               : "+f"(d[0]), "+f"(d[1]), "+f"(d[2]), "+f"(d[3]) : "r"(a0), "r"(a1), "r"(a2), "r"(a3), "r"(b0), "r"(b1));
}
template <int H>
__device__ __forceinline__ void safe_head(float (&o)[12], const uint32_t (&q)[24], const uint8_t* kv, uint32_t seq, int nit, int anti, int dthr, int tq, uint32_t tag) {
  constexpr int J0 = (H == 0) ? 0 : (H == 1) ? 2 : (H == 2) ? 5 : 7;
  float m0 = -INFINITY, m1 = -INFINITY;
#pragma unroll
  for (int i = 0; i < 12; i++) o[i] = 0.f;
#pragma unroll 1
  for (int st = 0; st < 4 * nit; st++) {
    const uint8_t* a = kv + (size_t)((seq >> (st & 28)) & 15) * (8 * KVB) + (st & 3) * 256;
    uint32_t b[12], bad, n = 0;
    do {
      bad = 0;
#pragma unroll
      for (int i = 0; i < 12; i++) {
        b[i] = ldcg32(a + ((i < 6 ? J0 : 7 + 3 * H) + (i >> 1)) * 1024 + (i & 1) * 128);
        bad |= b[i] ^ tag;
      }
    } while (__any_sync(0xffffffffu, tq == 1 && (bad & TAGM) != 0u) && ++n < SPIN_MAX);
    float s[8];
#pragma unroll
    for (int i = 0; i < 8; i++) s[i] = 0.f;
#pragma unroll
    for (int t = 0; t < 2; t++) {
      mma16816(&s[4 * t], q[6 * H], q[6 * H + 1], q[6 * H + 2], q[6 * H + 3], b[t], b[2 + t]);
      mma16816(&s[4 * t], q[6 * H + 4], q[6 * H + 5], 0u, 0u, b[4 + t], 0u);
    }
    if (st < 4 || (st >> 2) == anti) {
      const int z = dthr - (st & 3) * 16;
#pragma unroll
      for (int i = 0; i < 8; i++)
        if (((i >> 2) * 8 + (i & 1) - (i & 2) * 4 <= z) != (st < 4)) s[i] = -INFINITY;
    }
    float n0 = fmaxf(fmaxf(s[0], s[1]), fmaxf(s[4], s[5])), n1 = fmaxf(fmaxf(s[2], s[3]), fmaxf(s[6], s[7]));
    n0 = fmaxf(n0, __shfl_xor_sync(0xffffffffu, n0, 1));
    n1 = fmaxf(n1, __shfl_xor_sync(0xffffffffu, n1, 1));
    n0 = fmaxf(m0, fmaxf(n0, __shfl_xor_sync(0xffffffffu, n0, 2)));
    n1 = fmaxf(m1, fmaxf(n1, __shfl_xor_sync(0xffffffffu, n1, 2)));
    const float al0 = ex2(m0 - n0), al1 = ex2(m1 - n1);
    m0 = n0;
    m1 = n1;
    const uint32_t p0 = pack2(ex2(s[0] - n0), ex2(s[1] - n0)), p1 = pack2(ex2(s[2] - n1), ex2(s[3] - n1));
    const uint32_t p2 = pack2(ex2(s[4] - n0), ex2(s[5] - n0)), p3 = pack2(ex2(s[6] - n1), ex2(s[7] - n1));
#pragma unroll
    for (int i = 6; i < 12; i++) asm volatile("movmatrix.sync.aligned.m8n8.trans.b16 %0, %0;" : "+r"(b[i]));
#pragma unroll
    for (int t = 0; t < 3; t++) {
      o[4 * t] *= al0; o[4 * t + 1] *= al0; o[4 * t + 2] *= al1; o[4 * t + 3] *= al1;
      mma16816(&o[4 * t], p0, p1, p2, p3, b[6 + 2 * t], b[7 + 2 * t]);
    }
  }
}
#define ATT_STEP(HQ, sq, kq, HP, op, pp, kv, sc, pc, W) do { \
  WG_FENCE(); qk_issue<HQ>(sq, q, qm[2 * HQ], qm[2 * HQ + 1], kq); WG_COMMIT(); WG_WAIT(1); pv_issue<HP>(op, pp, kv); WG_COMMIT(); \
  sm_exp(sc, pc, nk, flip); WG_WAIT(W); reg_fence(sq); } while (0)
__device__ __forceinline__ uint32_t bmul2(uint32_t a, uint32_t b) { uint32_t d; asm("mul.rn.bf16x2 %0, %1, %2;" : "=r"(d) : "r"(a), "r"(b)); return d; }
__device__ __forceinline__ uint32_t badd2(uint32_t a, uint32_t b) { uint32_t d; asm("add.rn.bf16x2 %0, %1, %2;" : "=r"(d) : "r"(a), "r"(b)); return d; }
__device__ __forceinline__ uint32_t bfma2(uint32_t a, uint32_t b, uint32_t c) { uint32_t d; asm("fma.rn.bf16x2 %0, %1, %2, %3;" : "=r"(d) : "r"(a), "r"(b), "r"(c)); return d; }

__global__ void __cluster_dims__(2, 1, 1) __launch_bounds__(384, 1) fused_block_kernel(const __grid_constant__ Params P) {
  extern __shared__ __align__(1024) uint8_t smem[];
  const uint32_t sb = s2u(smem);
  const int tid = threadIdx.x, lane = tid & 31, warp = __shfl_sync(0xffffffffu, tid >> 5, 0);
  const uint32_t bars = sb + OFF_MISC;
#define BAR(i) (bars + 8u * (uint32_t)(i))
#define TP(i)
  if (tid == 288) {
#pragma unroll
    for (int u = 0; u < 6; u++) mbar_init(BAR(u), 1);
    asm volatile("fence.mbarrier_init.release.cluster;" ::: "memory");
  }
  __syncwarp();
  asm volatile("barrier.cluster.arrive.relaxed.aligned;" ::: "memory");
  TP(0);
  const uint32_t rank = blockIdx.x & 1;
  const int kc = blockIdx.x >> 1;
  const int c = kc < 4 ? kc + 4 : kc < 36 ? (kc - 4) >> 3 : (kc * 37 - 308) >> 8;
  const int rb = 2 * (kc < 4 ? 0 : kc < 36 ? (kc - 1) & 7 : kc - 33 - 7 * ((kc * 37 - 1258) >> 8)) + (int)rank;
  const int tile = rb * 8 + c;
  const int odd = c & 1;
  const int mainch = (c >> 1) * 5 + (odd ? 3 : 0), leftch = (c >> 1) * 10 + (odd ? 5 : 4);
  const int kb0 = (5 * (rb >> 1)) >> 2;
  if (lane == 0 && (warp >> 1) != 4) {
    const int j = warp < 8 ? warp + 3 : warp - 9;
    const int cnt = (int)(0x4a108208108421ull >> (5 * j)) & 31;
#pragma unroll
    for (int u = 0; u < 6; u++) mbar_init(BAR(j * 6 + u), cnt);
    asm volatile("fence.mbarrier_init.release.cluster;" ::: "memory");
  }
  __syncwarp();
  TP(1);
  if (warp >= 8) asm volatile("setmaxnreg.dec.sync.aligned.u32 56;");
  TP(2);
  if (warp > 8) {
    asm volatile("bar.arrive 1, 384;" ::: "memory");
    if (lane == 0) {
      if (warp == 9) {
        mbar_expect(BAR(B_QFULL), QST);
        tma2d(sb, &P.mX, kb0 * 64, rb * 128, BAR(B_QFULL));
      } else {
        asm volatile("prefetch.tensormap [%0];" ::"l"(warp == 10 ? &P.mWqM : &P.mWqL) : "memory");
      }
    }
    __syncwarp();
    asm volatile("bar.sync 2, 128;" ::: "memory");
  } else {
    asm volatile("bar.sync 1, 384;" ::: "memory");
  }
  TP(3);
  if (tid < 208) {
    const uint8_t* pp = tid < 192 ? reinterpret_cast<const uint8_t*>(P.wqkv) + (size_t)(kb0 * 64 + (int)rank * 32 + (tid & 31)) * 3840 + (tid >> 6) * 1280 + c * 160 + (tid & 32) * 4
                                  : reinterpret_cast<const uint8_t*>(P.x) + (size_t)(rb * 128 + c * 16 + tid - 192) * 1280 + kb0 * 128;
    l2_prefetch(pp);
  }
  if (warp == 8) {
    asm volatile("bar.arrive 2, 128;\nbarrier.cluster.wait.acquire.aligned;" ::: "memory");
    TP(4);
    if (lane == 0) {
#pragma unroll 1
      for (int kt = 0; kt < 4; kt++) {
        const uint32_t a = sb + kt * QST, fb = BAR(B_QFULL + kt);
        const int k0 = (kb0 + kt < 10 ? kb0 + kt : kb0 + kt - 10) * 64;
        if (kt) mbar_expect(fb, QST);
        tma4d_mc(a + 16384 + rank * 12288, &P.mWqM, 0, k0 + rank * 32, mainch, 0, fb);
        tma4d_mc(a + 40960 + rank * 3072, &P.mWqL, 0, k0 + rank * 32, leftch, 0, fb);
        if (kt) tma2d(a, &P.mX, k0, rb * 128, fb);
        if (kt == 0) TP(5);
      }
      mbar_expect(BAR(B_XROW), 20480);
      bulk_load(sb + OFF_XROW, reinterpret_cast<const uint8_t*>(P.x) + (size_t)(rb * 128 + c * 16) * 1280, 20480, BAR(B_XROW));
    }
    else if (lane < 4) mbar_arrive(BAR(B_XROW));
    __syncwarp();
    STAMPW(9);
  }
  const int sc = (27 * c + 3) >> 2;

  if (warp >= 8) {
    const uint32_t epoch = __shfl_sync(0xffffffffu, ldcg32(&g_epoch[tile * 32 + lane]), 0) + 1u;
    const uint32_t ep = epoch & 3u, tag = (epoch & 1u) | ((epoch & 2u) << 15);
    if (warp == 8) {
      if (lane == 0) {
#pragma unroll 1
        for (int kt = 4; kt < 10; kt++) {
          const int st = kt & 3;
          mbar_wait(BAR(B_QEMPTY + st), ((kt >> 2) - 1) & 1);
          const uint32_t a = sb + st * QST, fb = BAR(B_QFULL + st);
          const int k0 = (kb0 + kt < 10 ? kb0 + kt : kb0 + kt - 10) * 64;
          mbar_expect(fb, QST);
          tma4d_mc(a + 16384 + rank * 12288, &P.mWqM, 0, k0 + rank * 32, mainch, 0, fb);
          tma4d_mc(a + 40960 + rank * 3072, &P.mWqL, 0, k0 + rank * 32, leftch, 0, fb);
          tma2d(a, &P.mX, k0, rb * 128, fb);
        }
        l2_prefetch_bulk(reinterpret_cast<const uint8_t*>(P.wo) + tile * 6400, 6400);
        l2_prefetch_bulk(reinterpret_cast<const uint8_t*>(P.w1) + tile * 17280, 17280);
        l2_prefetch_bulk(reinterpret_cast<const uint8_t*>(P.w2) + tile * 17280, 17280);
        const CUtensorMap* mW1 = rank ? &P.mW1b : &P.mW1a;
        asm volatile("prefetch.tensormap [%0];" ::"l"(&P.mWo) : "memory");
        asm volatile("prefetch.tensormap [%0];" ::"l"(mW1) : "memory");
        asm volatile("prefetch.tensormap [%0];" ::"l"(&P.mW2) : "memory");
        mbar_wait(BAR(B_QEMPTY + 0), 0);
        mbar_wait(BAR(B_QEMPTY + 1), 0);
        if (rb) mbar_wait(BAR(B_KVFULL + 3), 0);
        mbar_expect(BAR(B_WOB), 89600);
#pragma unroll 1
        for (int i = 0; i < 4 - (int)rank; i++) {
          const int pos = rank * 4 + i;
          tma3d_mc(sb + OFF_WOB + pos * 12800, &P.mWo, 0, ((c + pos) & 7) * 80, c * 5, BAR(B_WOB));
        }
#pragma unroll 1
        for (int s = 0; s < 8; s++) {
          if (s < 3) mbar_wait(BAR(B_ATT2 - s), 0);
          if (s == 0) {
            mbar_expect(BAR(B_WOB7), 12800);
            if (rank) tma3d_mc(sb + OFF_WOB + 7 * 12800, &P.mWo, 0, ((c + 7) & 7) * 80, c * 5, BAR(B_WOB7));
          } else if (s == 3) mbar_wait(BAR(B_WODP), 0);
          else if (s >= 5) mbar_wait(BAR(B_BEMPTY + s - 5), 0);
          const uint32_t fb = BAR(B_BFULL + s);
          mbar_expect(fb, 35840);
          tma3d_mc(sb + w1b_addr(s) + rank * 20480, mW1, 0, ((c + s) & 7) * 80, sc + rank * 4, fb);
        }
#pragma unroll 1
        for (int s = 0; s < 5; s++) {
          mbar_wait(s < 3 ? BAR(B_BEMPTY + 4 + s) : BAR(B_W2E + s - 3), 0);
          const uint32_t dst = sb + (s < 3 ? s : s - 3) * W2SLOT + rank * 14336, fb = BAR(B_W2FULL + s);
          const int bx0 = (c + 2 * s) % 10, bx1 = (c + 2 * s + 1) % 10;
          mbar_expect(fb, W2SLOT);
          tma2d_mc(dst, &P.mW2, bx0 * 64, sc * 32 + rank * 112, fb);
          tma2d_mc(dst + 28672, &P.mW2, bx1 * 64, sc * 32 + rank * 112, fb);
        }
      }
      __syncwarp();
    } else {
      mbar_wait(BAR(B_XROW), 0);
#pragma unroll 1
      for (int p = warp - 9; p < 8; p += 3) {
        const int row = rb * 128 + c * 16 + p * 2 + (lane >> 4);
        const uint8_t* xb = smem + OFF_XROW + (p * 2 + (lane >> 4)) * 1280 + (lane & 15) * 16;
        uint4 xv[5];
#pragma unroll
        for (int i = 0; i < 5; i++) xv[i] = *reinterpret_cast<const uint4*>(xb + i * 256);
        float s = 0.f;
#pragma unroll
        for (int i = 0; i < 5; i++)
          s += ((bf_lo(xv[i].x) + bf_hi(xv[i].x)) + (bf_lo(xv[i].y) + bf_hi(xv[i].y))) + ((bf_lo(xv[i].z) + bf_hi(xv[i].z)) + (bf_lo(xv[i].w) + bf_hi(xv[i].w)));
#pragma unroll
        for (int o = 8; o; o >>= 1) s += __shfl_xor_sync(0xffffffffu, s, o);
        const float mean = s * (1.f / 640.f);
        float m2 = 0.f;
#pragma unroll
        for (int i = 0; i < 5; i++) {
          const uint32_t u[4] = {xv[i].x, xv[i].y, xv[i].z, xv[i].w};
#pragma unroll
          for (int j = 0; j < 4; j++) {
            const float d0 = bf_lo(u[j]) - mean, d1 = bf_hi(u[j]) - mean;
            m2 += d0 * d0 + d1 * d1;
          }
        }
#pragma unroll
        for (int o = 8; o; o >>= 1) m2 += __shfl_xor_sync(0xffffffffu, m2, o);
        if ((lane & 15) == 0) g_xstat[row] = make_float2(mean, tag32(rsqrtf(m2 * (1.f / 640.f) + 1e-5f), ep));
      }
      if (warp == 9) STAMPW(17);
      if (warp == 11) {
        mbar_wait(BAR(B_PRE), 0);
        if (lane < 30) {
          float4 a = make_float4(0.f, 0.f, 0.f, 0.f);
#pragma unroll 4
          for (int i = 0; i < 16; i++) {
            const float4 v = *reinterpret_cast<const float4*>(smem + OFF_PRE + i * 512 + lane * 16);
            a.x += v.x; a.y += v.y; a.z += v.z; a.w += v.w;
          }
          *reinterpret_cast<float4*>(&g_csq[((rb >> 1) * 8 + c) * 240 + rank * 120 + lane * 4]) = make_float4(tag32(a.x, ep), tag32(a.y, ep), tag32(a.z, ep), tag32(a.w, ep));
        }
        __syncwarp();
        STAMPW(0);
      } else {
        if (warp == 10) {
          mbar_wait(BAR(B_QEMPTY + 3), 0);
          uint4 v0, v1;
          uint32_t n = 0;
          do {
            v0 = ldcg128(&g_xstat[rb * 128 + lane * 2]);
            v1 = ldcg128(&g_xstat[rb * 128 + 64 + lane * 2]);
          } while (__any_sync(0xffffffffu, (((v0.y ^ ep) | (v0.w ^ ep) | (v1.y ^ ep) | (v1.w ^ ep)) & 3u) != 0u) && ++n < SPIN_MAX);
          *reinterpret_cast<uint4*>(smem + OFF_XST + lane * 16) = v0;
          *reinterpret_cast<uint4*>(smem + OFF_XST + 512 + lane * 16) = v1;
          __syncwarp();
          if (lane < 2) mbar_arrive(BAR(B_STAT));
          STAMPW(18);
        }
        if (warp == 10 && lane == 0) {
#pragma unroll 1
          for (int i = 0; i < 1 + KVP; i++) {
            if (i < 2) mbar_wait(BAR(B_KVOWN + i), 0);
            const uint32_t off = i ? (uint32_t)(i - 1) * (KVB / KVP) + KVB : 0u;
            asm volatile("cp.async.bulk.wait_group.read 0;\ncp.async.bulk.global.shared::cta.bulk_group [%0], [%1], %2;\ncp.async.bulk.commit_group;"
                         ::"l"(g_kv + (size_t)(rb * 16 + c) * KVB + (i ? 7 * KVB + off : 0u)), "r"(sb + kv_addr(4) + off), "r"(i ? KVB / KVP : KVB) : "memory");
          }
          asm volatile("cp.async.bulk.wait_group.read 0;" ::: "memory");
          mbar_arrive_pair(BAR(B_ATT2));
          STAMPW(6);
        }
        __syncwarp();
      }
      if (warp != 10) {
        const int u = (warp - 9) * 16 + lane;
        mbar_wait(BAR(B_QEMPTY + 3), 0);
        gather8(smem + OFF_CS + u * 16, g_csq + c * 240 + min(u, 59) * 4, 1920, ep, u < 60);
        __syncwarp();
        if (lane == 0) mbar_arrive(BAR(B_STAT));
        if (warp == 9) STAMPW(16);
        mbar_wait(BAR(B_Q23), 0);
      }
#pragma unroll 1
      for (int bi = warp == 9 ? 2 : warp == 10 ? 3 : 1; bi >= 0; bi -= (warp == 9 ? 2 : 4)) {
        const int blk = 2 * rb - 4 + bi;
        if (blk < 0) continue;
        const uint8_t* src = g_kv + (size_t)(blk * 8 + c) * KVB;
        const uint32_t dst = sb + kv_addr(bi);
        uint32_t n = 0, ph = 0;
        while (!__all_sync(0xffffffffu, ((ldcg32(src + lane * 704 + 692) ^ tag) & TAGM) == 0u) && ++n < SPIN_MAX) {}
        if (warp == 9 && bi == 2) STAMPW(3);
        while (true) {
          if (lane == 0) {
            fence_async_glob();
            mbar_expect(BAR(B_KVLAND + bi), KVB);
            bulk_load(dst, src, KVB, BAR(B_KVLAND + bi));
          }
          mbar_wait(BAR(B_KVLAND + bi), ph);
          ph ^= 1u;
          uint32_t bad = 0;
#pragma unroll 11
          for (int i = 0; i < 44; i++) {
            uint32_t v;
            asm volatile("ld.shared.u32 %0, [%1];" : "=r"(v) : "r"(dst + (i * 32 + lane) * 16 + 4) : "memory");
            bad |= v ^ tag;
          }
          if (!__any_sync(0xffffffffu, (bad & TAGM) != 0u) || ++n >= SPIN_MAX) break;
        }
        if (lane == 0) {
          mbar_arrive(BAR(B_KVFULL + bi));
        }
        if (warp == 9 && bi == 2) STAMPW(5);
        if (warp == 10) STAMPW(7);
      }
      __syncwarp();
      asm volatile("barrier.cluster.wait.acquire.aligned;" ::: "memory");
      if (warp == 10) {
        const int l16 = lane & 15, col = sc * 32 + (int)rank * 112 + l16 * 8;
        const uint8_t* wb = reinterpret_cast<const uint8_t*>(P.w1) + (size_t)((rb >> 1) * 80 + (lane >> 4) * 40) * 3456 + (size_t)col * 2;
        float acc[8];
#pragma unroll
        for (int i = 0; i < 8; i++) acc[i] = 0.f;
        if (l16 < 14 && col < 1728) {
#pragma unroll 1
          for (int i = 0; i < 40; i += 8) {
            uint4 v[8];
#pragma unroll
            for (int u = 0; u < 8; u++) v[u] = __ldg(reinterpret_cast<const uint4*>(wb + (size_t)(i + u) * 3456));
#pragma unroll
            for (int u = 0; u < 8; u++) {
              acc[0] += bf_lo(v[u].x); acc[1] += bf_hi(v[u].x); acc[2] += bf_lo(v[u].y); acc[3] += bf_hi(v[u].y);
              acc[4] += bf_lo(v[u].z); acc[5] += bf_hi(v[u].z); acc[6] += bf_lo(v[u].w); acc[7] += bf_hi(v[u].w);
            }
          }
        }
        __syncwarp();
#pragma unroll
        for (int i = 0; i < 4; i++) {
          const float o = __shfl_xor_sync(0xffffffffu, lane < 16 ? acc[4 + i] : acc[i], 16);
          acc[i] = tag32((lane < 16 ? acc[i] : acc[4 + i]) + o, ep);
        }
        if (l16 < 14) *reinterpret_cast<float4*>(&g_cs1[((rb >> 1) * 8 + c) * 224 + rank * 112 + l16 * 8 + (lane >> 4) * 4]) = make_float4(acc[0], acc[1], acc[2], acc[3]);
        STAMPW(4);
      } else if (warp == 11) {
        mbar_wait(BAR(B_ATT3), 0);
#pragma unroll 1
        for (int u = lane; u < 64; u += 32) gather8(smem + OFF_XS + u * 16, g_cs1 + c * 224 + min(u, 55) * 4, 1792, ep, u < 56);
        __syncwarp();
        if (lane == 0) mbar_arrive(BAR(B_CS1));
        STAMPW(1);
      }
    }
    if (warp == 9 || warp == 10) {
      const int r = warp - 9;
      uint32_t* fl = &g_oflag[(rb * 2 + r) * 8];
      mbar_wait(BAR(B_HST + r), 0);
      if (lane == 0) {
        asm volatile("cp.async.bulk.tensor.2d.global.shared::cta.bulk_group [%0, {%2, %3}], [%1];\ncp.async.bulk.commit_group;\ncp.async.bulk.wait_group 0;"
                     ::"l"(&P.mOutH), "r"(sb + OFF_HST + r * 10240), "r"(c * 80), "r"(rb * 128 + r * 64) : "memory");
        asm volatile("fence.proxy.async.global;\nst.release.gpu.global.u32 [%0], %1;" ::"l"(fl + c), "r"(epoch) : "memory");
      }
      __syncwarp();
      uint32_t n = 0;
      while (!__all_sync(0xffffffffu, ld_flag(fl + (lane & 7)) == epoch) && ++n < SPIN_MAX) {}
      if (lane == 0) mbar_arrive(BAR(B_OUTOK + r));
      STAMPW(2);
    } else if (warp == 11) {
      st_flag(&g_epoch[tile * 32 + lane], epoch);
    }
  } else {
    const int r = warp >> 2, w = warp & 3, gq = lane >> 2, tq = lane & 3;
    asm volatile("setmaxnreg.inc.sync.aligned.u32 224;");
    STAMP(4);
    uint32_t ep = ldcg32(&g_epoch[tile * 32 + lane]);
    const int b = rb * 2 + r;
    uint32_t q[24], qm[8], tag;
    STAMP(0);
    {
      float accM[96], accL[24];
      uint32_t fa[16], fb[16];
      const uint32_t xa = sb + (uint32_t)(warp * 16 + (lane & 15)) * 128u + (uint32_t)(((lane >> 4) ^ lane) & 7) * 16u;
#define QKV_ISSUE(f, kt) do { \
        const uint32_t a = ((kt) & 3) * QST; \
        const uint64_t dm = mkdesc(sb + a + 16384, desc_hi(2048, 512, 2)); \
        const uint64_t dl = mkdesc(sb + a + 40960, desc_hi(1024, 256, 3)); \
        mbar_wait(BAR(B_QFULL + ((kt) & 3)), ((kt) >> 2) & 1); \
        _Pragma("unroll") for (int k = 0; k < 4; k++) ldsm4(&f[4 * k], (xa ^ (k * 32)) + a); \
        WG_FENCE(); \
        _Pragma("unroll") for (int k = 0; k < 4; k++) { \
          wg_rs192(accM, f[4 * k], f[4 * k + 1], f[4 * k + 2], f[4 * k + 3], dm + (k >> 1) * 768 + (k & 1) * 64, (kt) | k); \
          wg_rs48(accL, f[4 * k], f[4 * k + 1], f[4 * k + 2], f[4 * k + 3], dl + (k >> 1) * 192 + (k & 1) * 32, (kt) | k); \
        } \
        WG_COMMIT(); } while (0)
#pragma unroll 1
      for (int kt = 0; kt < 10; kt += 2) {
        QKV_ISSUE(fa, kt);
        WG_WAIT(1);
        if (lane == 0) {
          if (kt == 8) mbar_arrive(BAR(B_Q23));
          else if (kt) mbar_arrive_pair(BAR(B_QEMPTY + ((kt - 1) & 3)));
        }
        QKV_ISSUE(fb, kt + 1);
        if (kt == 0) {
          const int cl = min(lane & 15, 14) + (int)rank * 15, mat = cl / 10, pc = cl - mat * 10 - odd * 2;
          const bool mn = (unsigned)pc < 8u;
          const int pitch = mn ? 64 : 32;
          const uint8_t* wp = smem + (mn ? 16384 + mat * 4096 + (pc >> 2) * 2048 + ((pc ^ (warp >> 1)) & 3) * 16 : 40960 + mat * 1024 + ((pc ^ (warp >> 2)) & 1) * 16);
          float a[8];
#pragma unroll
          for (int i = 0; i < 8; i++) a[i] = 0.f;
#pragma unroll
          for (int u = 0; u < 5; u++) {
            const int kr = (rb >> 1) * 80 - kb0 * 64 + u * 16;
            const uint4 v = *reinterpret_cast<const uint4*>(wp + (kr >> 6) * QST + ((kr & 16) + (lane >> 4) * 8 + warp + (kr & 32) * (mn ? 6 : 3)) * pitch);
            a[0] += bf_lo(v.x); a[1] += bf_hi(v.x); a[2] += bf_lo(v.y); a[3] += bf_hi(v.y);
            a[4] += bf_lo(v.z); a[5] += bf_hi(v.z); a[6] += bf_lo(v.w); a[7] += bf_hi(v.w);
          }
          float4* dst = reinterpret_cast<float4*>(smem + OFF_PRE + warp * 1024 + lane * 32);
          dst[0] = make_float4(a[0], a[1], a[2], a[3]);
          dst[1] = make_float4(a[4], a[5], a[6], a[7]);
          __syncwarp();
          if (lane == 0) mbar_arrive(BAR(B_PRE));
          STAMP(5);
        } else if (kt == 4) {
          asm volatile("barrier.cluster.wait.acquire.aligned;" ::: "memory");
        }
        WG_WAIT(1);
        if (lane == 0 && kt != 6) mbar_arrive_pair(BAR(B_QEMPTY + (kt & 3)));
      }
      ep = (__shfl_sync(0xffffffffu, ep, 0) + 1u) & 3u;
      tag = (ep & 1u) | ((ep & 2u) << 15);
      mbar_wait(BAR(B_STAT), 0);
      const float2 s0 = lds64f(sb + OFF_XST + (warp * 16 + gq) * 8), s1 = lds64f(sb + OFF_XST + (warp * 16 + gq + 8) * 8);
      mbar_wait(BAR(B_Q23), 0);
      WG_WAIT(0);
      reg_fence(accM); reg_fence(accL);
      if (lane == 0) mbar_arrive_pair(BAR(B_QEMPTY + 1));
      STAMP(2);
      const uint32_t km = tq == 1 ? ~TAGM : 0xffffffffu, kt1 = tq == 1 ? tag : 0u;
      const uint32_t csM = sb + OFF_CS + (odd ? 64 : 0) + tq * 8, csL = sb + OFF_CS + (odd ? 0 : 256) + tq * 8;
      const uint32_t kvo = sb + kv_addr(4 + r) + (uint32_t)(w * 16 + ((lane >> 3) & 1) * 8 + (lane & 7)) * 16u + (uint32_t)(lane >> 4) * 1024u;
      const float qs = 0.22360679774997896f * 1.4426950408889634f;
      const bool lo = tq < 2;
      uint32_t qj[20], kj[20];
#pragma unroll
      for (int mm = 0; mm < 3; mm++) {
        const int mat = (mm + 1) % 3;
        const float r0 = mat == 0 ? s0.y * qs : s0.y, r1 = mat == 0 ? s1.y * qs : s1.y;
        const float n0 = -s0.x * r0, n1 = -s1.x * r1;
        uint32_t pk[20];
#pragma unroll
        for (int t = 0; t < 10; t++) {
          const float* a = t < 8 ? &accM[(mat * 8 + t) * 4] : &accL[(mat * 2 + t - 8) * 4];
          const float2 cs = lds64f(t < 8 ? csM + mat * 320 + t * 32 : csL + mat * 320 + (t - 8) * 32);
          pk[2 * t] = pack2(fmaf(a[0], r0, cs.x * n0), fmaf(a[1], r0, cs.y * n0));
          pk[2 * t + 1] = pack2(fmaf(a[2], r1, cs.x * n1), fmaf(a[3], r1, cs.y * n1));
        }
#pragma unroll
        for (int i = 0; i < 20; i++) qj[i] = odd ? pk[(i + 16) % 20] : pk[i];
        if (mat == 1) {
#pragma unroll
          for (int i = 0; i < 20; i++) kj[i] = (qj[i] & km) | kt1;
#pragma unroll
          for (int t = 0; t < 10; t += 2) stsm4(kvo + t * 1024, kj[2 * t], kj[2 * t + 1], kj[2 * t + 2], kj[2 * t + 3]);
        }
        if (mat == 2) {
          const uint32_t one = (tq & 1) ? 0u : 0x3f80u;
          uint32_t vv[24];
#pragma unroll
          for (int hp = 0; hp < 2; hp++) {
            const int j = hp * 10;
#pragma unroll
            for (int i = 0; i < 4; i++) { vv[hp * 12 + i] = qj[j + i]; vv[hp * 12 + 8 + i] = qj[j + 6 + i]; }
            vv[hp * 12 + 4] = lo ? qj[j + 4] : one; vv[hp * 12 + 5] = lo ? qj[j + 5] : one;
            vv[hp * 12 + 6] = lo ? one : qj[j + 4]; vv[hp * 12 + 7] = lo ? one : qj[j + 5];
          }
#pragma unroll
          for (int i = 0; i < 24; i++) vv[i] = (vv[i] & km) | kt1;
#pragma unroll
          for (int t = 0; t < 6; t++) stsm4(kvo + 10240 + t * 2048, vv[4 * t], vv[4 * t + 1], vv[4 * t + 2], vv[4 * t + 3]);
          fence_async_smem();
          __syncwarp();
          if (lane == 0) mbar_arrive(BAR(B_KVOWN + r));
        }
      }
#pragma unroll
      for (int hp = 0; hp < 2; hp++) {
        const int j = hp * 10;
        q[hp * 12 + 0] = qj[j + 0]; q[hp * 12 + 1] = qj[j + 1]; q[hp * 12 + 2] = qj[j + 2]; q[hp * 12 + 3] = qj[j + 3];
        q[hp * 12 + 4] = lo ? qj[j + 4] : 0u; q[hp * 12 + 5] = lo ? qj[j + 5] : 0u;
        q[hp * 12 + 6] = lo ? 0u : qj[j + 4]; q[hp * 12 + 7] = lo ? 0u : qj[j + 5];
        q[hp * 12 + 8] = qj[j + 6]; q[hp * 12 + 9] = qj[j + 7]; q[hp * 12 + 10] = qj[j + 8]; q[hp * 12 + 11] = qj[j + 9];
      }
#pragma unroll
      for (int h = 0; h < 4; h++) {
        const int j = (h >> 1) * 10 + (h & 1) * 4;
        const uint32_t d0 = bfma2(q[6 * h + 4], kj[j + 4], bfma2(q[6 * h + 2], kj[j + 2], bmul2(q[6 * h], kj[j])));
        const uint32_t d1 = bfma2(q[6 * h + 5], kj[j + 5], bfma2(q[6 * h + 3], kj[j + 3], bmul2(q[6 * h + 1], kj[j + 1])));
        uint32_t u = badd2(__byte_perm(d0, d1, 0x5410), __byte_perm(d0, d1, 0x7632));
        u = badd2(u, __shfl_xor_sync(0xffffffffu, u, 1));
        u = badd2(u, __shfl_xor_sync(0xffffffffu, u, 2));
        u = tq == 2 ? u ^ 0x80008000u : 0u;
        qm[2 * h] = u & 0xffffu;
        qm[2 * h + 1] = u >> 16;
        asm volatile("" : "+r"(qm[2 * h]), "+r"(qm[2 * h + 1]));
      }
    }
    STAMP(3);
    uint32_t x0[20], xr[20];
    const int row_lo = b * 64 + w * 16 + gq;
    {
      float o0[12], o1[12], o2[12], o3[12];
#pragma unroll
      for (int i = 0; i < 12; i++) { o0[i] = 0.f; o1[i] = 0.f; o2[i] = 0.f; o3[i] = 0.f; }
      float s0[32], s1[32];
      uint32_t p0[16], p1[16];
      const int dthr = w * 16 + gq - 2 * tq;
      const uint32_t seq = r ? 0x13245u : rb == 1 ? 0x324u : 0x13024u;
      const int anti = r ? 4 : rb == 1 ? 7 : 2;
      const int nit = rb >= 2 ? 5 : 2 * rb + 1 + r;
      mbar_wait(BAR(B_KVOWN + r), 0);
      uint32_t kb = ((sb + kv_addr(4 + r)) & 0x3FFFF) >> 4, kp = kb;
      WG_FENCE();
      qk_issue<0>(s0, q, qm[0], qm[1], kb);
      WG_COMMIT();
#pragma unroll
      for (int i = 0; i < 16; i++) p1[i] = 0u;
      WG_WAIT(0);
      reg_fence(s0);
#pragma unroll 1
      for (int it = 0; it < nit; it++) {
        const int nb = (it && it != anti) ? 4096 : dthr * 16 + 144;
        const uint32_t flip = it == anti ? 0xffffffffu : 0u;
        uint32_t nk[9];
#pragma unroll
        for (int t = 0; t < 9; t++) asm("shl.b32 %0, %1, %2;" : "=r"(nk[t]) : "r"(0xffffffffu), "r"(max(nb - 128 * t, 0)));
        ATT_STEP(1, s1, kb, 3, o3, p1, kp, s0, p0, 1);
        ATT_STEP(2, s0, kb, 0, o0, p0, kb, s1, p1, 1);
        if (it >= 2 && lane == 0) mbar_arrive_pair(BAR(B_ATT2 + 2 - it));
        ATT_STEP(3, s1, kb, 1, o1, p1, kb, s0, p0, 1);
        kp = kb;
        if (it + 1 < nit) {
          const int bi = (seq >> (4 * it + 4)) & 15;
          mbar_wait(bi == 4 ? BAR(B_KVOWN) : BAR(B_KVFULL + bi), 0);
          kb = ((sb + kv_addr(bi)) & 0x3FFFF) >> 4;
        }
        ATT_STEP(0, s0, kb, 2, o2, p0, kp, s1, p1, LASTW);
      }
      WG_FENCE();
      pv_issue<3>(o3, p1, kp);
      WG_COMMIT();
      WG_WAIT(0);
      reg_fence(o0); reg_fence(o1); reg_fence(o2); reg_fence(o3);
      if (lane >= 2 && lane < 5 && lane >= nit) mbar_arrive_pair(BAR(B_ATT2 + 2 - lane));
      if (lane == 0) mbar_arrive(BAR(B_ATTL));
      {
        const uint32_t e0 = 63u << 23;
        const uint32_t ba = (__float_as_uint(o0[8]) - e0) | (__float_as_uint(o0[10]) - e0) | (__float_as_uint(o2[8]) - e0) | (__float_as_uint(o2[10]) - e0);
        const uint32_t bb = (__float_as_uint(o1[0]) - e0) | (__float_as_uint(o1[2]) - e0) | (__float_as_uint(o3[0]) - e0) | (__float_as_uint(o3[2]) - e0);
        if (__builtin_expect(__any_sync(0xffffffffu, ((tq == 2 ? ba : tq == 0 ? bb : 0u) >> 30) != FORCE_SAFE), 0)) {
          const uint8_t* kv = g_kv + (ptrdiff_t)((2 * rb - 4) * 8 + c) * KVB + lane * 4;
          safe_head<0>(o0, q, kv, seq, nit, anti, dthr, tq, tag);
          safe_head<1>(o1, q, kv, seq, nit, anti, dthr, tq, tag);
          safe_head<2>(o2, q, kv, seq, nit, anti, dthr, tq, tag);
          safe_head<3>(o3, q, kv, seq, nit, anti, dthr, tq, tag);
          __syncwarp();
        }
      }
      float inv[4][2];
      inv[0][0] = rcp(__shfl_sync(0xffffffffu, o0[8], (lane & 28) + 2));
      inv[0][1] = rcp(__shfl_sync(0xffffffffu, o0[10], (lane & 28) + 2));
      inv[1][0] = rcp(__shfl_sync(0xffffffffu, o1[0], lane & 28));
      inv[1][1] = rcp(__shfl_sync(0xffffffffu, o1[2], lane & 28));
      inv[2][0] = rcp(__shfl_sync(0xffffffffu, o2[8], (lane & 28) + 2));
      inv[2][1] = rcp(__shfl_sync(0xffffffffu, o2[10], (lane & 28) + 2));
      inv[3][0] = rcp(__shfl_sync(0xffffffffu, o3[0], lane & 28));
      inv[3][1] = rcp(__shfl_sync(0xffffffffu, o3[2], lane & 28));
      const bool lo = tq < 2;
#define OPK(dst, o, t, h) do { x0[dst] = pack2(o[4 * (t)] * inv[h][0], o[4 * (t) + 1] * inv[h][0]); x0[dst + 1] = pack2(o[4 * (t) + 2] * inv[h][1], o[4 * (t) + 3] * inv[h][1]); } while (0)
#define OPK2(dst, oa, ha, ob, hb) do { \
        const float i0 = lo ? inv[ha][0] : inv[hb][0], i1 = lo ? inv[ha][1] : inv[hb][1]; \
        x0[dst] = pack2((lo ? oa[8] : ob[0]) * i0, (lo ? oa[9] : ob[1]) * i0); \
        x0[dst + 1] = pack2((lo ? oa[10] : ob[2]) * i1, (lo ? oa[11] : ob[3]) * i1); } while (0)
      OPK(0, o0, 0, 0); OPK(2, o0, 1, 0); OPK2(4, o0, 0, o1, 1); OPK(6, o1, 1, 1); OPK(8, o1, 2, 1);
      OPK(10, o2, 0, 2); OPK(12, o2, 1, 2); OPK2(14, o2, 2, o3, 3); OPK(16, o3, 1, 3); OPK(18, o3, 2, 3);
    }
    const int bw = b * 4 + w;
    const size_t tile_off = (size_t)bw * 20480 + lane * 16;
    const size_t probe_off = (size_t)bw * 20480 + ((c + lane) & 7) * 2560 + 2544;
    {
#pragma unroll
      for (int k = 0; k < 5; k++) {
        x0[4 * k] = tag16(x0[4 * k], tag);
        stg128(g_o + tile_off + c * 2560 + k * 512, x0[4 * k], x0[4 * k + 1], x0[4 * k + 2], x0[4 * k + 3]);
      }
      STAMP(6);
      const uint32_t pv = ldcg32(g_o + probe_off);
      float acc[40];
      constexpr uint64_t HI = desc_hi(2560, 256, 3);
      const uint64_t db = mkdesc(sb + OFF_WOB, HI);
      mbar_wait(BAR(B_WOB), 0);
      WG_FENCE();
#pragma unroll
      for (int k = 0; k < 5; k++) wg_rs80(acc, x0[4 * k], x0[4 * k + 1], x0[4 * k + 2], x0[4 * k + 3], db + k * 32, k);
      WG_COMMIT();
      uint32_t xa[7][20], ready = __ballot_sync(0xffffffffu, ((pv ^ tag) & TAGM) == 0u);
#pragma unroll
      for (int i = 1; i < 8; i++) {
        probe_wait(ready, i, g_o + probe_off, tag);
        if (i == 7) WG_WAIT(0);
        ld_tile(xa[i - 1], g_o + tile_off + ((c + i) & 7) * 2560);
      }
      STAMP(7);
#pragma unroll
      for (int i = 1; i < 8; i++) {
        if (i == 7) mbar_wait(BAR(B_WOB7), 0);
        fix_tile(xa[i - 1], g_o + tile_off + ((c + i) & 7) * 2560, tag);
        WG_FENCE();
#pragma unroll
        for (int k = 0; k < 5; k++) wg_rs80(acc, xa[i - 1][4 * k], xa[i - 1][4 * k + 1], xa[i - 1][4 * k + 2], xa[i - 1][4 * k + 3], db + i * 800 + k * 32, 1);
        WG_COMMIT();
        if (i == 2) {
          WG_WAIT(1);
          const uint8_t* xp = reinterpret_cast<const uint8_t*>(P.x) + (size_t)row_lo * 1280 + c * 160 + tq * 4;
#pragma unroll
          for (int t = 0; t < 10; t++) {
            xr[2 * t] = ldnc32(xp + t * 16);
            xr[2 * t + 1] = ldnc32(xp + 8 * 1280 + t * 16);
          }
        }
      }
      WG_WAIT(0);
      reg_fence(acc);
      if (lane == 0) mbar_arrive_pair(BAR(B_WODP));
      STAMP(8);
      float sum0 = 0.f, sum1 = 0.f;
#pragma unroll
      for (int t = 0; t < 10; t++) {
        x0[2 * t] = pack2(acc[4 * t] + bf_lo(xr[2 * t]), acc[4 * t + 1] + bf_hi(xr[2 * t]));
        x0[2 * t + 1] = pack2(acc[4 * t + 2] + bf_lo(xr[2 * t + 1]), acc[4 * t + 3] + bf_hi(xr[2 * t + 1]));
      }
#pragma unroll
      for (int k = 0; k < 5; k++) {
        x0[4 * k] = tag16(x0[4 * k], tag);
        stg128(g_h + tile_off + c * 2560 + k * 512, x0[4 * k], x0[4 * k + 1], x0[4 * k + 2], x0[4 * k + 3]);
      }
#pragma unroll
      for (int t = 0; t < 10; t++) {
        sum0 += bf_lo(x0[2 * t]) + bf_hi(x0[2 * t]);
        sum1 += bf_lo(x0[2 * t + 1]) + bf_hi(x0[2 * t + 1]);
      }
      sum0 += __shfl_xor_sync(0xffffffffu, sum0, 1);
      sum1 += __shfl_xor_sync(0xffffffffu, sum1, 1);
      sum0 += __shfl_xor_sync(0xffffffffu, sum0, 2);
      sum1 += __shfl_xor_sync(0xffffffffu, sum1, 2);
      const float mu0 = sum0 * (1.f / 80.f), mu1 = sum1 * (1.f / 80.f);
      float v0 = 0.f, v1 = 0.f;
#pragma unroll
      for (int t = 0; t < 10; t++) {
        const float d0 = bf_lo(x0[2 * t]) - mu0, d1 = bf_hi(x0[2 * t]) - mu0, d2 = bf_lo(x0[2 * t + 1]) - mu1, d3 = bf_hi(x0[2 * t + 1]) - mu1;
        v0 += d0 * d0 + d1 * d1;
        v1 += d2 * d2 + d3 * d3;
      }
      v0 += __shfl_xor_sync(0xffffffffu, v0, 1);
      v1 += __shfl_xor_sync(0xffffffffu, v1, 1);
      v0 += __shfl_xor_sync(0xffffffffu, v0, 2);
      v1 += __shfl_xor_sync(0xffffffffu, v1, 2);
      if (tq < 2) g_hstat[(bw * 8 + c) * 16 + gq + tq * 8] = make_float2(tq ? mu1 : mu0, tag32(tq ? v1 : v0, ep));
    }
    uint32_t ha[56];
    {
      float acc[112];
      constexpr uint64_t HI = desc_hi(5120, 512, 2);
#define W1_ISSUE(xx, i) do { \
        const uint64_t db = mkdesc(sb + w1b_addr(i), HI); \
        mbar_wait(BAR(B_BFULL + (i)), 0); \
        WG_FENCE(); \
        _Pragma("unroll") for (int k = 0; k < 5; k++) wg_rs224(acc, xx[4 * k], xx[4 * k + 1], xx[4 * k + 2], xx[4 * k + 3], db + k * 64, (i) | k); \
        WG_COMMIT(); } while (0)
#define W1_STEP(xx, xp, i) do { \
        fix_tile(xx, ht + ((c + (i)) & 7) * 2560, tag); \
        if (LATEWODP && (i) == 1 && lane == 0) mbar_arrive_pair(BAR(B_WODP)); \
        W1_ISSUE(xx, i); \
        WG_WAIT(1); \
        if ((i) != 4 && lane == 0) mbar_arrive_pair(BAR(B_BEMPTY - 1 + (i))); \
        if ((i) < 5) ld_tile(xp, ht + ((c + (i) + 3) & 7) * 2560); } while (0)
      W1_ISSUE(x0, 0);
      STAMP(9);
      {
        const uint32_t hs = sb + OFF_HST + (uint32_t)(warp * 16 + (lane & 15)) * 160u + (uint32_t)(lane >> 4) * 16u;
        mbar_wait(BAR(B_ATTL), 0);
#pragma unroll
        for (int k = 0; k < 5; k++) stsm4(hs + k * 32, x0[4 * k], x0[4 * k + 1], x0[4 * k + 2], x0[4 * k + 3]);
        fence_async_smem();
        __syncwarp();
        if (lane == 0) mbar_arrive(BAR(B_HST + r));
      }
      const uint8_t* ht = g_h + tile_off;
      uint32_t x1[20], x2[20], x3[20], ready = 0;
      probe_wait(ready, 1, g_h + probe_off, tag);
      ld_tile(x1, ht + ((c + 1) & 7) * 2560);
      probe_wait(ready, 2, g_h + probe_off, tag);
      ld_tile(x2, ht + ((c + 2) & 7) * 2560);
      probe_wait(ready, 3, g_h + probe_off, tag);
      ld_tile(x3, ht + ((c + 3) & 7) * 2560);
      STAMP(10);
#pragma unroll 1
      for (int i = 1; ; i += 4) {
        W1_STEP(x1, x0, i);
        W1_STEP(x2, x1, i + 1);
        W1_STEP(x3, x2, i + 2);
        if (i == 5) break;
        W1_STEP(x0, x3, i + 3);
      }
      uint2 hs[4];
      {
        const float2* hp = &g_hstat[(bw * 8 + tq * 2) * 16 + gq];
        uint32_t n = 0;
        do {
          hs[0] = ldcg64(hp); hs[1] = ldcg64(hp + 16); hs[2] = ldcg64(hp + 8); hs[3] = ldcg64(hp + 24);
        } while (__any_sync(0xffffffffu, (((hs[0].y ^ ep) | (hs[1].y ^ ep) | (hs[2].y ^ ep) | (hs[3].y ^ ep)) & 3u) != 0u) && ++n < SPIN_MAX);
      }
      float mean0, mean1, rs0, rs1;
      {
        const float a0 = __uint_as_float(hs[0].x), a1 = __uint_as_float(hs[1].x), b0 = __uint_as_float(hs[2].x), b1 = __uint_as_float(hs[3].x);
        float t0 = a0 + a1, t1 = b0 + b1;
        t0 += __shfl_xor_sync(0xffffffffu, t0, 1);
        t1 += __shfl_xor_sync(0xffffffffu, t1, 1);
        t0 += __shfl_xor_sync(0xffffffffu, t0, 2);
        t1 += __shfl_xor_sync(0xffffffffu, t1, 2);
        mean0 = t0 * 0.125f;
        mean1 = t1 * 0.125f;
        float u0 = __uint_as_float(hs[0].y) + __uint_as_float(hs[1].y) + 80.f * ((a0 - mean0) * (a0 - mean0) + (a1 - mean0) * (a1 - mean0));
        float u1 = __uint_as_float(hs[2].y) + __uint_as_float(hs[3].y) + 80.f * ((b0 - mean1) * (b0 - mean1) + (b1 - mean1) * (b1 - mean1));
        u0 += __shfl_xor_sync(0xffffffffu, u0, 1);
        u1 += __shfl_xor_sync(0xffffffffu, u1, 1);
        u0 += __shfl_xor_sync(0xffffffffu, u0, 2);
        u1 += __shfl_xor_sync(0xffffffffu, u1, 2);
        rs0 = 0.5f * rsqrtf(u0 * (1.f / 640.f) + 1e-5f);
        rs1 = 0.5f * rsqrtf(u1 * (1.f / 640.f) + 1e-5f);
      }
      mbar_wait(BAR(B_CS1), 0);
      WG_WAIT(0);
      reg_fence(acc);
      if (lane == 0) mbar_arrive_pair(BAR(B_BEMPTY + 7));
      STAMP(11);
      const float n0 = -mean0 * rs0, n1 = -mean1 * rs1;
#pragma unroll
      for (int t = 0; t < 28; t++) {
        const float2 cs = lds64f(sb + OFF_XS + t * 32 + tq * 8);
        const float h0 = fmaf(acc[4 * t], rs0, cs.x * n0), h1 = fmaf(acc[4 * t + 1], rs0, cs.y * n0);
        const float h2 = fmaf(acc[4 * t + 2], rs1, cs.x * n1), h3 = fmaf(acc[4 * t + 3], rs1, cs.y * n1);
        ha[2 * t] = pack2(fmaf(h0, tanh_fast(h0), h0), fmaf(h1, tanh_fast(h1), h1));
        ha[2 * t + 1] = pack2(fmaf(h2, tanh_fast(h2), h2), fmaf(h3, tanh_fast(h3), h3));
      }
      if ((c & 3) == 3) {
#pragma unroll
        for (int t = 48; t < 56; t++) ha[t] = 0u;
      }
    }
    STAMP(12);
    {
      float accA[64], accB[64];
      constexpr uint64_t HI = desc_hi(28672, 1024, 1);
      const uint32_t ost = sb + OFF_OST + (uint32_t)warp * 6144u;
      const uint32_t osw = ost + (uint32_t)(lane & 15) * 128u + (uint32_t)(((lane >> 4) ^ lane) & 7) * 16u;
#define W2_ISSUE(acc, s) do { \
        mbar_wait(BAR(B_W2FULL + (s)), 0); \
        const uint64_t db = mkdesc(sb + ((s) % 3) * W2SLOT, HI); \
        WG_FENCE(); \
        _Pragma("unroll") for (int k = 0; k < 14; k++) wg_rs128(acc, ha[4 * k], ha[4 * k + 1], ha[4 * k + 2], ha[4 * k + 3], db + k * 128, k); \
        WG_COMMIT(); } while (0)
#define W2_OUT(acc, s) do { \
        reg_fence(acc); \
        if ((s) < 2 && lane == 0) mbar_arrive_pair(BAR(B_W2E + (s))); \
        _Pragma("unroll") for (int u = 2 * (s); u < 2 * (s) + 2; u++) { \
          const float* a = &acc[(u & 1) * 32]; \
          if (u >= 3) { if (lane == 0) asm volatile("cp.async.bulk.wait_group.read 2;" ::: "memory"); __syncwarp(); } \
          _Pragma("unroll") for (int t = 0; t < 8; t += 2) \
            stsm4((osw ^ (t * 16)) + (u % 3) * 2048, pack2(a[4 * t], a[4 * t + 1]), pack2(a[4 * t + 2], a[4 * t + 3]), pack2(a[4 * t + 4], a[4 * t + 5]), pack2(a[4 * t + 6], a[4 * t + 7])); \
          fence_async_smem(); \
          __syncwarp(); \
          if (lane == 0) \
            asm volatile("cp.reduce.async.bulk.tensor.2d.global.shared::cta.add.bulk_group [%0, {%2, %3}], [%1];\ncp.async.bulk.commit_group;" \
                         ::"l"(&P.mOut), "r"(ost + (u % 3) * 2048), "r"((c + u) % 10 * 64), "r"(rb * 128 + warp * 16) : "memory"); \
        } } while (0)
      W2_ISSUE(accA, 0);
      W2_ISSUE(accB, 1);
      mbar_wait(BAR(B_BEMPTY + 7), 0);
      mbar_wait(BAR(B_OUTOK + r), 0);
      fence_async_glob();
      WG_WAIT(1);
      W2_OUT(accA, 0);
      STAMP(13);
      W2_ISSUE(accA, 2);
      WG_WAIT(1);
      W2_OUT(accB, 1);
      W2_ISSUE(accB, 3);
      WG_WAIT(1);
      W2_OUT(accA, 2);
      W2_ISSUE(accA, 4);
      WG_WAIT(1);
      W2_OUT(accB, 3);
      STAMP(14);
      WG_WAIT(0);
      W2_OUT(accA, 4);
      STAMP(15);
      if (lane == 0) asm volatile("cp.async.bulk.wait_group.read 0;" ::: "memory");
      STAMP(17);
    }
  }
}

typedef CUresult (*EncodeFn)(CUtensorMap*, CUtensorMapDataType, cuuint32_t, void*, const cuuint64_t*, const cuuint64_t*, const cuuint32_t*,
                             const cuuint32_t*, CUtensorMapInterleave, CUtensorMapSwizzle, CUtensorMapL2promotion, CUtensorMapFloatOOBfill);

static void make_map(EncodeFn enc, CUtensorMap* m, const void* p, int nd, const cuuint64_t* dims, const cuuint64_t* strides, const cuuint32_t* box,
                     CUtensorMapSwizzle sw) {
  const cuuint32_t es[5] = {1, 1, 1, 1, 1};
  enc(m, CU_TENSOR_MAP_DATA_TYPE_BFLOAT16, (cuuint32_t)nd, const_cast<void*>(p), dims, strides, box, es, CU_TENSOR_MAP_INTERLEAVE_NONE, sw,
      CU_TENSOR_MAP_L2_PROMOTION_L2_128B, CU_TENSOR_MAP_FLOAT_OOB_FILL_NONE);
}

extern "C" void kernel_launch(void* const* d_in, const int* in_sizes, int n_in, void* d_out, int out_size) {
  (void)in_sizes; (void)n_in; (void)out_size;
  static EncodeFn enc = nullptr;
  if (!enc) {
    void* f = nullptr;
    cudaDriverEntryPointQueryResult qr;
    cudaGetDriverEntryPoint("cuTensorMapEncodeTiled", &f, cudaEnableDefault, &qr);
    enc = (EncodeFn)f;
    cudaFuncSetAttribute(fused_block_kernel, cudaFuncAttributeMaxDynamicSharedMemorySize, (int)SMEM_BYTES);
  }
  Params P;
  P.x = (const __nv_bfloat16*)d_in[0];
  P.wqkv = (const __nv_bfloat16*)d_in[1];
  P.wo = (const __nv_bfloat16*)d_in[2];
  P.w1 = (const __nv_bfloat16*)d_in[4];
  P.w2 = (const __nv_bfloat16*)d_in[5];
  P.out = (__nv_bfloat16*)d_out;
  { const cuuint64_t d[2] = {640, 2048}, s[1] = {1280}; const cuuint32_t b[2] = {64, 128}; make_map(enc, &P.mX, P.x, 2, d, s, b, CU_TENSOR_MAP_SWIZZLE_128B); }
  { const cuuint64_t d[4] = {32, 640, 20, 3}, s[3] = {3840, 64, 1280}; const cuuint32_t b[4] = {32, 32, 2, 3}; make_map(enc, &P.mWqM, P.wqkv, 4, d, s, b, CU_TENSOR_MAP_SWIZZLE_64B); }
  { const cuuint64_t d[4] = {16, 640, 40, 3}, s[3] = {3840, 32, 1280}; const cuuint32_t b[4] = {16, 32, 1, 3}; make_map(enc, &P.mWqL, P.wqkv, 4, d, s, b, CU_TENSOR_MAP_SWIZZLE_32B); }
  { const cuuint64_t d[3] = {16, 640, 40}, s[2] = {1280, 32}; const cuuint32_t b[3] = {16, 80, 5}; make_map(enc, &P.mWo, P.wo, 3, d, s, b, CU_TENSOR_MAP_SWIZZLE_32B); }
  { const cuuint64_t d[3] = {32, 640, 54}, s[2] = {3456, 64}; const cuuint32_t b[3] = {32, 80, 4}; make_map(enc, &P.mW1a, P.w1, 3, d, s, b, CU_TENSOR_MAP_SWIZZLE_64B); }
  { const cuuint64_t d[3] = {32, 640, 54}, s[2] = {3456, 64}; const cuuint32_t b[3] = {32, 80, 3}; make_map(enc, &P.mW1b, P.w1, 3, d, s, b, CU_TENSOR_MAP_SWIZZLE_64B); }
  { const cuuint64_t d[2] = {640, 1728}, s[1] = {1280}; const cuuint32_t b[2] = {64, 112}; make_map(enc, &P.mW2, P.w2, 2, d, s, b, CU_TENSOR_MAP_SWIZZLE_128B); }
  { const cuuint64_t d[2] = {640, 2048}, s[1] = {1280}; const cuuint32_t b[2] = {80, 64}; make_map(enc, &P.mOutH, P.out, 2, d, s, b, CU_TENSOR_MAP_SWIZZLE_NONE); }
  { const cuuint64_t d[2] = {640, 2048}, s[1] = {1280}; const cuuint32_t b[2] = {64, 16}; make_map(enc, &P.mOut, P.out, 2, d, s, b, CU_TENSOR_MAP_SWIZZLE_128B); }
  fused_block_kernel<<<128, 384, SMEM_BYTES, cudaStreamPerThread>>>(P);
}
```

```cpp
#include <cuda_runtime.h>
#include <cuda.h>
#include <cuda_bf16.h>
#include <stdint.h>

#define PROF 0
#define XPOS 1
#define PF0 1
#define LASTW 1
#define KVP 8
#define GOIT 3
#define GOW 1
#define HPROBE 1
#define HS 4
#define HMODE 0
#define FORCE_SAFE 0u

__device__ __align__(1024) uint8_t g_kv[32 * 8 * 22528];
__device__ __align__(1024) uint8_t g_o[32 * 4 * 8 * 2560];
__device__ __align__(1024) uint8_t g_h[32 * 4 * 8 * 2560];
__device__ __align__(1024) float2 g_hstat[32 * 4 * 8 * 16];
__device__ __align__(128) uint32_t g_hint[2 * 32 * 8 * HS];
__device__ __align__(128) uint32_t g_oflag[32 * 8];
__device__ __align__(128) float2 g_xstat[2048];
__device__ __align__(128) float g_csq[8 * 8 * 240];
__device__ __align__(128) float g_cs1[8 * 8 * 224];
__device__ __align__(128) uint32_t g_epoch[128 * 32];
#define STAMP(slot)
#define STAMPW(slot)

struct Params {
  const __nv_bfloat16 *x, *wqkv, *wo, *w1, *w2;
  __nv_bfloat16* out;
  uint32_t map[16];
  CUtensorMap mX, mWqM, mWqL, mWo, mW1a, mW1b, mW2, mOutH, mOut;
};

constexpr uint32_t QST = 47104;
constexpr uint32_t KVB = 22528;
constexpr uint32_t OFF_WOB = 0;
constexpr uint32_t OFF_PRE = 188416;
constexpr uint32_t OFF_XROW = 196608;
constexpr uint32_t W2SLOT = 57344;
constexpr uint32_t OFF_OST = 174080;
constexpr uint32_t OFF_HST = 209920;
constexpr uint32_t OFF_CS = 229376;
constexpr uint32_t OFF_XST = 230336;
constexpr uint32_t OFF_XS = 230912;
constexpr uint32_t OFF_MISC = 231808;
constexpr uint32_t SMEM_BYTES = 232448;

enum {
  B_QFULL = 0, B_KVFULL = 4, B_KVLAND = 8, B_WOB = 12, B_WOB7 = 13, B_BFULL = 14, B_W2FULL = 22, B_CS1 = 27, B_OUTOK = 28,
  B_KVOWN = 30, B_HST = 32, B_STAT = 34, B_XROW = 35,
  B_Q23 = 36, B_PRE = 37, B_ATTL = 38, B_GO = 39, B_OL1 = 40, B_OL1L = 41,
  B_QEMPTY = 42, B_W2E = 46, B_WODP = 48, B_BEMPTY = 49, B_WODP2 = 57, B_ATT4 = 58, B_ATT3 = 59,
  B_ATT2 = 60
};
constexpr uint32_t TAGM = 0x00010001u;
constexpr uint32_t SPIN_MAX = 1u << 18;

__device__ __forceinline__ uint32_t s2u(const void* p) { return (uint32_t)__cvta_generic_to_shared(p); }
__device__ __forceinline__ void mbar_init(uint32_t b, int c) { asm volatile("mbarrier.init.shared::cta.b64 [%0], %1;" ::"r"(b), "r"(c)); }
__device__ __forceinline__ void mbar_expect(uint32_t b, int bytes) { asm volatile("mbarrier.arrive.expect_tx.shared::cta.b64 _, [%0], %1;" ::"r"(b), "r"(bytes) : "memory"); }
__device__ __forceinline__ void mbar_arrive(uint32_t b) { asm volatile("mbarrier.arrive.shared::cta.b64 _, [%0];" ::"r"(b) : "memory"); }
__device__ __forceinline__ void mbar_arrive_pair(uint32_t b) {
  asm volatile("{\n.reg .b32 r;\nmapa.shared::cluster.u32 r, %0, 0;\nmbarrier.arrive.shared::cluster.b64 _, [r];\n"
               "mapa.shared::cluster.u32 r, %0, 1;\nmbarrier.arrive.shared::cluster.b64 _, [r];\n}" ::"r"(b) : "memory");
}
__device__ __forceinline__ void mbar_wait(uint32_t b, uint32_t ph) {
  asm volatile("{\n.reg .pred p;\n.reg .u32 n;\nmov.u32 n, 0;\nW%=:\nmbarrier.try_wait.parity.shared::cta.b64 p, [%0], %1;\n"
               "add.u32 n, n, 1;\nsetp.lt.and.u32 p, n, 0x100000, !p;\n@p bra W%=;\n}" ::"r"(b), "r"(ph) : "memory");
}
__device__ __forceinline__ uint32_t mbar_wait0(uint32_t b) {
  uint32_t n;
  asm volatile("{\n.reg .pred p;\nmov.u32 %0, 0;\nW%=:\nmbarrier.try_wait.parity.shared::cta.b64 p, [%1], 0;\n"
               "add.u32 %0, %0, 1;\nsetp.lt.and.u32 p, %0, 0x100000, !p;\n@p bra W%=;\n}" : "=r"(n) : "r"(b) : "memory");
  return n >> 21;
}
__device__ __forceinline__ bool mbar_test(uint32_t b) {
  uint32_t v;
  asm volatile("{\n.reg .pred p;\nmbarrier.test_wait.parity.shared::cta.b64 p, [%1], 0;\nselp.u32 %0, 1, 0, p;\n}" : "=r"(v) : "r"(b) : "memory");
  return v != 0u;
}
__device__ __forceinline__ void tma2d(uint32_t dst, const CUtensorMap* m, int c0, int c1, uint32_t bar) {
  asm volatile("cp.async.bulk.tensor.2d.shared::cluster.global.mbarrier::complete_tx::bytes [%0], [%1, {%3, %4}], [%2];" ::"r"(dst), "l"(m), "r"(bar), "r"(c0), "r"(c1) : "memory");
}
__device__ __forceinline__ void tma2d_mc(uint32_t dst, const CUtensorMap* m, int c0, int c1, uint32_t bar) {
  asm volatile("cp.async.bulk.tensor.2d.shared::cluster.global.mbarrier::complete_tx::bytes.multicast::cluster [%0], [%1, {%3, %4}], [%2], %5;" ::"r"(dst), "l"(m), "r"(bar), "r"(c0), "r"(c1), "h"((uint16_t)3) : "memory");
}
__device__ __forceinline__ void tma3d_mc(uint32_t dst, const CUtensorMap* m, int c0, int c1, int c2, uint32_t bar) {
  asm volatile("cp.async.bulk.tensor.3d.shared::cluster.global.mbarrier::complete_tx::bytes.multicast::cluster [%0], [%1, {%3, %4, %5}], [%2], %6;" ::"r"(dst), "l"(m), "r"(bar), "r"(c0), "r"(c1), "r"(c2), "h"((uint16_t)3) : "memory");
}
__device__ __forceinline__ void tma4d_mc(uint32_t dst, const CUtensorMap* m, int c0, int c1, int c2, int c3, uint32_t bar) {
  asm volatile("cp.async.bulk.tensor.4d.shared::cluster.global.mbarrier::complete_tx::bytes.multicast::cluster [%0], [%1, {%3, %4, %5, %6}], [%2], %7;" ::"r"(dst), "l"(m), "r"(bar), "r"(c0), "r"(c1), "r"(c2), "r"(c3), "h"((uint16_t)3) : "memory");
}
__device__ __forceinline__ void bulk_load(uint32_t dst, const void* src, int bytes, uint32_t bar) {
  asm volatile("cp.async.bulk.shared::cluster.global.mbarrier::complete_tx::bytes [%0], [%1], %2, [%3];" ::"r"(dst), "l"(src), "r"(bytes), "r"(bar) : "memory");
}
__device__ __forceinline__ void tma4d_pf(const CUtensorMap* m, int c0, int c1, int c2, int c3) {
  asm volatile("cp.async.bulk.prefetch.tensor.4d.L2.global [%0, {%1, %2, %3, %4}];" ::"l"(m), "r"(c0), "r"(c1), "r"(c2), "r"(c3) : "memory");
}
__device__ __forceinline__ void l2_prefetch_bulk(const void* p, int bytes) { asm volatile("cp.async.bulk.prefetch.L2.global [%0], %1;" ::"l"(p), "r"(bytes) : "memory"); }
__device__ __forceinline__ void l2_prefetch(const void* p) { asm volatile("prefetch.global.L2 [%0];" ::"l"(p)); }
__device__ __forceinline__ uint32_t ld_flag(const uint32_t* p) { uint32_t v; asm volatile("ld.acquire.gpu.global.u32 %0, [%1];" : "=r"(v) : "l"(p) : "memory"); return v; }
__device__ __forceinline__ void st_flag(uint32_t* p, uint32_t v) { asm volatile("st.relaxed.gpu.global.u32 [%0], %1;" ::"l"(p), "r"(v) : "memory"); }
__device__ __forceinline__ void fence_gpu() { asm volatile("fence.acq_rel.gpu;" ::: "memory"); }
__device__ __forceinline__ void fence_async_smem() { asm volatile("fence.proxy.async.shared::cta;" ::: "memory"); }
__device__ __forceinline__ void fence_async_glob() { asm volatile("fence.proxy.async.global;" ::: "memory"); }
__device__ __forceinline__ uint4 ldcg128(const void* p) { uint4 v; asm volatile("ld.relaxed.gpu.global.v4.u32 {%0,%1,%2,%3}, [%4];" : "=r"(v.x), "=r"(v.y), "=r"(v.z), "=r"(v.w) : "l"(p) : "memory"); return v; }
__device__ __forceinline__ uint4 ldnc128(const void* p) { uint4 v; asm volatile("ld.global.nc.v4.u32 {%0,%1,%2,%3}, [%4];" : "=r"(v.x), "=r"(v.y), "=r"(v.z), "=r"(v.w) : "l"(p)); return v; }
__device__ __forceinline__ uint32_t ldnc32(const void* p) { uint32_t v; asm volatile("ld.global.nc.u32 %0, [%1];" : "=r"(v) : "l"(p)); return v; }
__device__ __forceinline__ uint2 ldcg64(const void* p) { uint2 v; asm volatile("ld.relaxed.gpu.global.v2.u32 {%0,%1}, [%2];" : "=r"(v.x), "=r"(v.y) : "l"(p) : "memory"); return v; }
__device__ __forceinline__ uint32_t ldcg32(const void* p) { uint32_t v; asm volatile("ld.relaxed.gpu.global.u32 %0, [%1];" : "=r"(v) : "l"(p) : "memory"); return v; }
__device__ __forceinline__ uint32_t pack2(float lo, float hi) { uint32_t r; asm("cvt.rn.bf16x2.f32 %0, %1, %2;" : "=r"(r) : "f"(hi), "f"(lo)); return r; }
__device__ __forceinline__ float bf_lo(uint32_t v) { return __uint_as_float(v << 16); }
__device__ __forceinline__ float bf_hi(uint32_t v) { return __uint_as_float(v & 0xffff0000u); }
__device__ __forceinline__ float ex2(float x) { float y; asm("ex2.approx.ftz.f32 %0, %1;" : "=f"(y) : "f"(x)); return y; }
__device__ __forceinline__ float rcp(float x) { float y; asm("rcp.approx.ftz.f32 %0, %1;" : "=f"(y) : "f"(x)); return y; }
__device__ __forceinline__ float tanh_fast(float x) { float y; asm("tanh.approx.f32 %0, %1;" : "=f"(y) : "f"(x)); return y; }
__device__ __forceinline__ void stsm4(uint32_t a, uint32_t r0, uint32_t r1, uint32_t r2, uint32_t r3) {
  asm volatile("stmatrix.sync.aligned.m8n8.x4.shared.b16 [%0], {%1,%2,%3,%4};" ::"r"(a), "r"(r0), "r"(r1), "r"(r2), "r"(r3) : "memory");
}
__device__ __forceinline__ void ldsm4(uint32_t* r, uint32_t a) {
  asm volatile("ldmatrix.sync.aligned.m8n8.x4.shared.b16 {%0,%1,%2,%3}, [%4];" : "=r"(r[0]), "=r"(r[1]), "=r"(r[2]), "=r"(r[3]) : "r"(a) : "memory");
}
__device__ __forceinline__ float2 lds64f(uint32_t a) { float2 v; asm volatile("ld.shared.v2.f32 {%0,%1}, [%2];" : "=f"(v.x), "=f"(v.y) : "r"(a)); return v; }
__device__ __forceinline__ constexpr uint64_t desc_hi(uint32_t lbo, uint32_t sbo, uint32_t sw) {
  return ((uint64_t)(lbo >> 4) << 16) | ((uint64_t)(sbo >> 4) << 32) | ((uint64_t)sw << 62);
}
__device__ __forceinline__ uint64_t mkdesc(uint32_t addr, uint64_t hi) { return hi | (uint64_t)((addr & 0x3FFFF) >> 4); }
#define WG_FENCE() asm volatile("wgmma.fence.sync.aligned;" ::: "memory")
#define WG_COMMIT() asm volatile("wgmma.commit_group.sync.aligned;" ::: "memory")
#define WG_WAIT_(n) asm volatile("wgmma.wait_group.sync.aligned " #n ";" ::: "memory")
#define WG_WAIT(n) WG_WAIT_(n)
template <int N> __device__ __forceinline__ void reg_fence(float (&a)[N]) {
#pragma unroll
  for (int i = 0; i < N; i++) asm volatile("" : "+f"(a[i])::"memory");
}

__device__ __forceinline__ void wg_rs192(float (&d)[96], uint32_t a0, uint32_t a1, uint32_t a2, uint32_t a3, uint64_t db, int sd) {
  asm volatile("{\n.reg .pred p;\nsetp.ne.b32 p, %101, 0;\n"
  "wgmma.mma_async.sync.aligned.m64n192k16.f32.bf16.bf16 {%0, %1, %2, %3, %4, %5, %6, %7, %8, %9, %10, %11, %12, %13, %14, %15, %16, %17, %18, %19, %20, %21, %22, %23, %24, %25, %26, %27, %28, %29, %30, %31, %32, %33, %34, %35, %36, %37, %38, %39, %40, %41, %42, %43, %44, %45, %46, %47, %48, %49, %50, %51, %52, %53, %54, %55, %56, %57, %58, %59, %60, %61, %62, %63, %64, %65, %66, %67, %68, %69, %70, %71, %72, %73, %74, %75, %76, %77, %78, %79, %80, %81, %82, %83, %84, %85, %86, %87, %88, %89, %90, %91, %92, %93, %94, %95}, {%96, %97, %98, %99}, %100, p, 1, 1, 1;\n}\n"
  : "+f"(d[0]), "+f"(d[1]), "+f"(d[2]), "+f"(d[3]), "+f"(d[4]), "+f"(d[5]), "+f"(d[6]), "+f"(d[7]), "+f"(d[8]), "+f"(d[9]), "+f"(d[10]), "+f"(d[11]), "+f"(d[12]), "+f"(d[13]), "+f"(d[14]), "+f"(d[15]), "+f"(d[16]), "+f"(d[17]), "+f"(d[18]), "+f"(d[19]), "+f"(d[20]), "+f"(d[21]), "+f"(d[22]), "+f"(d[23]), "+f"(d[24]), "+f"(d[25]), "+f"(d[26]), "+f"(d[27]), "+f"(d[28]), "+f"(d[29]), "+f"(d[30]), "+f"(d[31]), "+f"(d[32]), "+f"(d[33]), "+f"(d[34]), "+f"(d[35]), "+f"(d[36]), "+f"(d[37]), "+f"(d[38]), "+f"(d[39]), "+f"(d[40]), "+f"(d[41]), "+f"(d[42]), "+f"(d[43]), "+f"(d[44]), "+f"(d[45]), "+f"(d[46]), "+f"(d[47]), "+f"(d[48]), "+f"(d[49]), "+f"(d[50]), "+f"(d[51]), "+f"(d[52]), "+f"(d[53]), "+f"(d[54]), "+f"(d[55]), "+f"(d[56]), "+f"(d[57]), "+f"(d[58]), "+f"(d[59]), "+f"(d[60]), "+f"(d[61]), "+f"(d[62]), "+f"(d[63]), "+f"(d[64]), "+f"(d[65]), "+f"(d[66]), "+f"(d[67]), "+f"(d[68]), "+f"(d[69]), "+f"(d[70]), "+f"(d[71]), "+f"(d[72]), "+f"(d[73]), "+f"(d[74]), "+f"(d[75]), "+f"(d[76]), "+f"(d[77]), "+f"(d[78]), "+f"(d[79]), "+f"(d[80]), "+f"(d[81]), "+f"(d[82]), "+f"(d[83]), "+f"(d[84]), "+f"(d[85]), "+f"(d[86]), "+f"(d[87]), "+f"(d[88]), "+f"(d[89]), "+f"(d[90]), "+f"(d[91]), "+f"(d[92]), "+f"(d[93]), "+f"(d[94]), "+f"(d[95]) : "r"(a0), "r"(a1), "r"(a2), "r"(a3), "l"(db), "r"(sd));
}
__device__ __forceinline__ void wg_rs48(float (&d)[24], uint32_t a0, uint32_t a1, uint32_t a2, uint32_t a3, uint64_t db, int sd) {
  asm volatile("{\n.reg .pred p;\nsetp.ne.b32 p, %29, 0;\n"
  "wgmma.mma_async.sync.aligned.m64n48k16.f32.bf16.bf16 {%0, %1, %2, %3, %4, %5, %6, %7, %8, %9, %10, %11, %12, %13, %14, %15, %16, %17, %18, %19, %20, %21, %22, %23}, {%24, %25, %26, %27}, %28, p, 1, 1, 1;\n}\n"
  : "+f"(d[0]), "+f"(d[1]), "+f"(d[2]), "+f"(d[3]), "+f"(d[4]), "+f"(d[5]), "+f"(d[6]), "+f"(d[7]), "+f"(d[8]), "+f"(d[9]), "+f"(d[10]), "+f"(d[11]), "+f"(d[12]), "+f"(d[13]), "+f"(d[14]), "+f"(d[15]), "+f"(d[16]), "+f"(d[17]), "+f"(d[18]), "+f"(d[19]), "+f"(d[20]), "+f"(d[21]), "+f"(d[22]), "+f"(d[23]) : "r"(a0), "r"(a1), "r"(a2), "r"(a3), "l"(db), "r"(sd));
}
__device__ __forceinline__ void wg_rs80(float (&d)[40], uint32_t a0, uint32_t a1, uint32_t a2, uint32_t a3, uint64_t db, int sd) {
  asm volatile("{\n.reg .pred p;\nsetp.ne.b32 p, %45, 0;\n"
  "wgmma.mma_async.sync.aligned.m64n80k16.f32.bf16.bf16 {%0, %1, %2, %3, %4, %5, %6, %7, %8, %9, %10, %11, %12, %13, %14, %15, %16, %17, %18, %19, %20, %21, %22, %23, %24, %25, %26, %27, %28, %29, %30, %31, %32, %33, %34, %35, %36, %37, %38, %39}, {%40, %41, %42, %43}, %44, p, 1, 1, 1;\n}\n"
  : "+f"(d[0]), "+f"(d[1]), "+f"(d[2]), "+f"(d[3]), "+f"(d[4]), "+f"(d[5]), "+f"(d[6]), "+f"(d[7]), "+f"(d[8]), "+f"(d[9]), "+f"(d[10]), "+f"(d[11]), "+f"(d[12]), "+f"(d[13]), "+f"(d[14]), "+f"(d[15]), "+f"(d[16]), "+f"(d[17]), "+f"(d[18]), "+f"(d[19]), "+f"(d[20]), "+f"(d[21]), "+f"(d[22]), "+f"(d[23]), "+f"(d[24]), "+f"(d[25]), "+f"(d[26]), "+f"(d[27]), "+f"(d[28]), "+f"(d[29]), "+f"(d[30]), "+f"(d[31]), "+f"(d[32]), "+f"(d[33]), "+f"(d[34]), "+f"(d[35]), "+f"(d[36]), "+f"(d[37]), "+f"(d[38]), "+f"(d[39]) : "r"(a0), "r"(a1), "r"(a2), "r"(a3), "l"(db), "r"(sd));
}
__device__ __forceinline__ void wg_rs224(float (&d)[112], uint32_t a0, uint32_t a1, uint32_t a2, uint32_t a3, uint64_t db, int sd) {
  asm volatile("{\n.reg .pred p;\nsetp.ne.b32 p, %117, 0;\n"
  "wgmma.mma_async.sync.aligned.m64n224k16.f32.bf16.bf16 {%0, %1, %2, %3, %4, %5, %6, %7, %8, %9, %10, %11, %12, %13, %14, %15, %16, %17, %18, %19, %20, %21, %22, %23, %24, %25, %26, %27, %28, %29, %30, %31, %32, %33, %34, %35, %36, %37, %38, %39, %40, %41, %42, %43, %44, %45, %46, %47, %48, %49, %50, %51, %52, %53, %54, %55, %56, %57, %58, %59, %60, %61, %62, %63, %64, %65, %66, %67, %68, %69, %70, %71, %72, %73, %74, %75, %76, %77, %78, %79, %80, %81, %82, %83, %84, %85, %86, %87, %88, %89, %90, %91, %92, %93, %94, %95, %96, %97, %98, %99, %100, %101, %102, %103, %104, %105, %106, %107, %108, %109, %110, %111}, {%112, %113, %114, %115}, %116, p, 1, 1, 1;\n}\n"
  : "+f"(d[0]), "+f"(d[1]), "+f"(d[2]), "+f"(d[3]), "+f"(d[4]), "+f"(d[5]), "+f"(d[6]), "+f"(d[7]), "+f"(d[8]), "+f"(d[9]), "+f"(d[10]), "+f"(d[11]), "+f"(d[12]), "+f"(d[13]), "+f"(d[14]), "+f"(d[15]), "+f"(d[16]), "+f"(d[17]), "+f"(d[18]), "+f"(d[19]), "+f"(d[20]), "+f"(d[21]), "+f"(d[22]), "+f"(d[23]), "+f"(d[24]), "+f"(d[25]), "+f"(d[26]), "+f"(d[27]), "+f"(d[28]), "+f"(d[29]), "+f"(d[30]), "+f"(d[31]), "+f"(d[32]), "+f"(d[33]), "+f"(d[34]), "+f"(d[35]), "+f"(d[36]), "+f"(d[37]), "+f"(d[38]), "+f"(d[39]), "+f"(d[40]), "+f"(d[41]), "+f"(d[42]), "+f"(d[43]), "+f"(d[44]), "+f"(d[45]), "+f"(d[46]), "+f"(d[47]), "+f"(d[48]), "+f"(d[49]), "+f"(d[50]), "+f"(d[51]), "+f"(d[52]), "+f"(d[53]), "+f"(d[54]), "+f"(d[55]), "+f"(d[56]), "+f"(d[57]), "+f"(d[58]), "+f"(d[59]), "+f"(d[60]), "+f"(d[61]), "+f"(d[62]), "+f"(d[63]), "+f"(d[64]), "+f"(d[65]), "+f"(d[66]), "+f"(d[67]), "+f"(d[68]), "+f"(d[69]), "+f"(d[70]), "+f"(d[71]), "+f"(d[72]), "+f"(d[73]), "+f"(d[74]), "+f"(d[75]), "+f"(d[76]), "+f"(d[77]), "+f"(d[78]), "+f"(d[79]), "+f"(d[80]), "+f"(d[81]), "+f"(d[82]), "+f"(d[83]), "+f"(d[84]), "+f"(d[85]), "+f"(d[86]), "+f"(d[87]), "+f"(d[88]), "+f"(d[89]), "+f"(d[90]), "+f"(d[91]), "+f"(d[92]), "+f"(d[93]), "+f"(d[94]), "+f"(d[95]), "+f"(d[96]), "+f"(d[97]), "+f"(d[98]), "+f"(d[99]), "+f"(d[100]), "+f"(d[101]), "+f"(d[102]), "+f"(d[103]), "+f"(d[104]), "+f"(d[105]), "+f"(d[106]), "+f"(d[107]), "+f"(d[108]), "+f"(d[109]), "+f"(d[110]), "+f"(d[111]) : "r"(a0), "r"(a1), "r"(a2), "r"(a3), "l"(db), "r"(sd));
}
__device__ __forceinline__ void wg_rs64k(float (&d)[32], uint32_t a0, uint32_t a1, uint32_t a2, uint32_t a3, uint64_t db, int sd) {
  asm volatile("{\n.reg .pred p;\nsetp.ne.b32 p, %37, 0;\n"
  "wgmma.mma_async.sync.aligned.m64n64k16.f32.bf16.bf16 {%0, %1, %2, %3, %4, %5, %6, %7, %8, %9, %10, %11, %12, %13, %14, %15, %16, %17, %18, %19, %20, %21, %22, %23, %24, %25, %26, %27, %28, %29, %30, %31}, {%32, %33, %34, %35}, %36, p, 1, 1, 0;\n}\n"
  : "+f"(d[0]), "+f"(d[1]), "+f"(d[2]), "+f"(d[3]), "+f"(d[4]), "+f"(d[5]), "+f"(d[6]), "+f"(d[7]), "+f"(d[8]), "+f"(d[9]), "+f"(d[10]), "+f"(d[11]), "+f"(d[12]), "+f"(d[13]), "+f"(d[14]), "+f"(d[15]), "+f"(d[16]), "+f"(d[17]), "+f"(d[18]), "+f"(d[19]), "+f"(d[20]), "+f"(d[21]), "+f"(d[22]), "+f"(d[23]), "+f"(d[24]), "+f"(d[25]), "+f"(d[26]), "+f"(d[27]), "+f"(d[28]), "+f"(d[29]), "+f"(d[30]), "+f"(d[31]) : "r"(a0), "r"(a1), "r"(a2), "r"(a3), "l"(db), "r"(sd));
}
__device__ __forceinline__ void wg_rs24(float (&d)[12], uint32_t a0, uint32_t a1, uint32_t a2, uint32_t a3, uint64_t db, int sd) {
  asm volatile("{\n.reg .pred p;\nsetp.ne.b32 p, %17, 0;\n"
  "wgmma.mma_async.sync.aligned.m64n24k16.f32.bf16.bf16 {%0, %1, %2, %3, %4, %5, %6, %7, %8, %9, %10, %11}, {%12, %13, %14, %15}, %16, p, 1, 1, 1;\n}\n"
  : "+f"(d[0]), "+f"(d[1]), "+f"(d[2]), "+f"(d[3]), "+f"(d[4]), "+f"(d[5]), "+f"(d[6]), "+f"(d[7]), "+f"(d[8]), "+f"(d[9]), "+f"(d[10]), "+f"(d[11]) : "r"(a0), "r"(a1), "r"(a2), "r"(a3), "l"(db), "r"(sd));
}
__device__ __forceinline__ void wg_rs128(float (&d)[64], uint32_t a0, uint32_t a1, uint32_t a2, uint32_t a3, uint64_t db, int sd) {
  asm volatile("{\n.reg .pred p;\nsetp.ne.b32 p, %69, 0;\n"
  "wgmma.mma_async.sync.aligned.m64n128k16.f32.bf16.bf16 {%0, %1, %2, %3, %4, %5, %6, %7, %8, %9, %10, %11, %12, %13, %14, %15, %16, %17, %18, %19, %20, %21, %22, %23, %24, %25, %26, %27, %28, %29, %30, %31, %32, %33, %34, %35, %36, %37, %38, %39, %40, %41, %42, %43, %44, %45, %46, %47, %48, %49, %50, %51, %52, %53, %54, %55, %56, %57, %58, %59, %60, %61, %62, %63}, {%64, %65, %66, %67}, %68, p, 1, 1, 1;\n}\n"
  : "+f"(d[0]), "+f"(d[1]), "+f"(d[2]), "+f"(d[3]), "+f"(d[4]), "+f"(d[5]), "+f"(d[6]), "+f"(d[7]), "+f"(d[8]), "+f"(d[9]), "+f"(d[10]), "+f"(d[11]), "+f"(d[12]), "+f"(d[13]), "+f"(d[14]), "+f"(d[15]), "+f"(d[16]), "+f"(d[17]), "+f"(d[18]), "+f"(d[19]), "+f"(d[20]), "+f"(d[21]), "+f"(d[22]), "+f"(d[23]), "+f"(d[24]), "+f"(d[25]), "+f"(d[26]), "+f"(d[27]), "+f"(d[28]), "+f"(d[29]), "+f"(d[30]), "+f"(d[31]), "+f"(d[32]), "+f"(d[33]), "+f"(d[34]), "+f"(d[35]), "+f"(d[36]), "+f"(d[37]), "+f"(d[38]), "+f"(d[39]), "+f"(d[40]), "+f"(d[41]), "+f"(d[42]), "+f"(d[43]), "+f"(d[44]), "+f"(d[45]), "+f"(d[46]), "+f"(d[47]), "+f"(d[48]), "+f"(d[49]), "+f"(d[50]), "+f"(d[51]), "+f"(d[52]), "+f"(d[53]), "+f"(d[54]), "+f"(d[55]), "+f"(d[56]), "+f"(d[57]), "+f"(d[58]), "+f"(d[59]), "+f"(d[60]), "+f"(d[61]), "+f"(d[62]), "+f"(d[63]) : "r"(a0), "r"(a1), "r"(a2), "r"(a3), "l"(db), "r"(sd));
}

__device__ __forceinline__ uint32_t kv_addr(int i) {
  return 94208u + KVB * (uint32_t)((0x104253u >> (4 * i)) & 15u);
}
__device__ __forceinline__ uint32_t w1b_addr(int s) {
  return (s == 3 || s == 4) ? (uint32_t)(s - 3) * 35840u : 102400u + (uint32_t)(s >= 5 ? s - 5 : s) * 35840u;
}
__device__ __forceinline__ void stg128(void* p, uint32_t a, uint32_t b, uint32_t c, uint32_t d) {
  asm volatile("st.relaxed.gpu.global.v4.u32 [%0], {%1,%2,%3,%4};" ::"l"(p), "r"(a), "r"(b), "r"(c), "r"(d) : "memory");
}
__device__ __forceinline__ void stg32(void* p, uint32_t a) { asm volatile("st.global.u32 [%0], %1;" ::"l"(p), "r"(a) : "memory"); }
__device__ __forceinline__ void ld_tile(uint32_t (&a)[20], const uint8_t* p, int c, int i) {
  p += ((c + i) & 7) * 10240;
#pragma unroll
  for (int k = 0; k < 5; k++)
    asm volatile("ld.relaxed.gpu.global.v4.u32 {%0,%1,%2,%3}, [%4];" : "=r"(a[4 * k]), "=r"(a[4 * k + 1]), "=r"(a[4 * k + 2]), "=r"(a[4 * k + 3]) : "l"(p + k * 512) : "memory");
}
__device__ __forceinline__ uint32_t tag16(uint32_t v, uint32_t tag) { return (v & ~TAGM) | tag; }
__device__ __forceinline__ float tag32(float v, uint32_t ep) { return __uint_as_float((__float_as_uint(v) & ~3u) | ep); }
__device__ __forceinline__ void fix_tile(uint32_t (&a)[20], const uint8_t* p, int c, int i, uint32_t tag) {
  uint32_t n = 0;
  while (__any_sync(0xffffffffu, (((a[0] ^ tag) | (a[4] ^ tag) | (a[8] ^ tag) | (a[12] ^ tag) | (a[16] ^ tag)) & TAGM) != 0u) && ++n < SPIN_MAX) ld_tile(a, p, c, i);
}
__device__ __forceinline__ void probe_wait(uint32_t& ready, int i, const void* p, uint32_t tag) {
  uint32_t n = 0;
  while (!((ready >> i) & 1u) && ++n < SPIN_MAX) ready = __ballot_sync(0xffffffffu, ldcg32(p) == tag);
}
__device__ __forceinline__ void gather8(uint8_t* dst, const float* p, int stride, uint32_t ep, bool on) {
  uint4 v[8];
  uint32_t n = 0, bad;
  do {
    bad = 0;
#pragma unroll
    for (int i = 0; i < 8; i++) v[i] = ldcg128(p + i * stride);
#pragma unroll
    for (int i = 0; i < 8; i++) bad |= (v[i].x ^ ep) | (v[i].w ^ ep);
  } while (__any_sync(0xffffffffu, (bad & 3u) != 0u) && ++n < SPIN_MAX);
  float4 s = make_float4(0.f, 0.f, 0.f, 0.f);
#pragma unroll
  for (int i = 0; i < 8; i++) { s.x += __uint_as_float(v[i].x); s.y += __uint_as_float(v[i].y); s.z += __uint_as_float(v[i].z); s.w += __uint_as_float(v[i].w); }
  if (on) *reinterpret_cast<float4*>(dst) = s;
}

__device__ __forceinline__ uint64_t desc2(uint32_t lo, uint32_t hi) { uint64_t d; asm("mov.b64 %0, {%1, %2};" : "=l"(d) : "r"(lo), "r"(hi)); return d; }
template <int H>
__device__ __forceinline__ void qk_issue(float (&s)[32], const uint32_t (&q)[24], uint32_t m0, uint32_t m1, uint32_t kd) {
  constexpr int J0 = (H == 0) ? 0 : (H == 1) ? 2 : (H == 2) ? 5 : 7;
  wg_rs64k(s, q[H * 6 + 0], q[H * 6 + 1], q[H * 6 + 2], q[H * 6 + 3], desc2(kd + (0x400000u + J0 * 64), 8u), 0);
  wg_rs64k(s, q[H * 6 + 4], q[H * 6 + 5], m0, m1, desc2(kd + (((10 - J0) * 64u << 16) + (J0 + 2) * 64), 8u), 1);
}
template <int H>
__device__ __forceinline__ void pv_issue(float (&o)[12], const uint32_t (&p)[16], uint32_t kd) {
#pragma unroll
  for (int i = 0; i < 4; i++)
    wg_rs24(o, p[4 * i], p[4 * i + 1], p[4 * i + 2], p[4 * i + 3], desc2(kd + (0x80000u + 640 + 3 * H * 64 + i * 16), 64u), 1);
}
__device__ __forceinline__ void sm_exp(const float (&s)[32], uint32_t (&p)[16], const uint32_t (&nk)[9], uint32_t flip) {
#pragma unroll
  for (int t = 0; t < 8; t++) {
    p[2 * t] = pack2(ex2(s[4 * t]), ex2(s[4 * t + 1])) & (~nk[t + 1] ^ flip);
    p[2 * t + 1] = pack2(ex2(s[4 * t + 2]), ex2(s[4 * t + 3])) & (~nk[t] ^ flip);
  }
#pragma unroll
  for (int i = 0; i < 16; i++) asm volatile("" : "+r"(p[i])::"memory");
}
__device__ __forceinline__ void mma16816(float* d, uint32_t a0, uint32_t a1, uint32_t a2, uint32_t a3, uint32_t b0, uint32_t b1) {
  asm volatile("mma.sync.aligned.m16n8k16.row.col.f32.bf16.bf16.f32 {%0,%1,%2,%3}, {%4,%5,%6,%7}, {%8,%9}, {%0,%1,%2,%3};"
               : "+f"(d[0]), "+f"(d[1]), "+f"(d[2]), "+f"(d[3]) : "r"(a0), "r"(a1), "r"(a2), "r"(a3), "r"(b0), "r"(b1));
}
template <int H>
__device__ __forceinline__ void safe_head(float (&o)[12], const uint32_t (&q)[24], const uint8_t* kv, uint32_t seq, int nit, int anti, int dthr, int tq, uint32_t tag) {
  constexpr int J0 = (H == 0) ? 0 : (H == 1) ? 2 : (H == 2) ? 5 : 7;
  float m0 = -INFINITY, m1 = -INFINITY;
#pragma unroll
  for (int i = 0; i < 12; i++) o[i] = 0.f;
#pragma unroll 1
  for (int st = 0; st < 4 * nit; st++) {
    const uint8_t* a = kv + (size_t)((seq >> (st & 28)) & 15) * (8 * KVB) + (st & 3) * 256;
    uint32_t b[12], bad, n = 0;
    do {
      bad = 0;
#pragma unroll
      for (int i = 0; i < 12; i++) {
        b[i] = ldcg32(a + ((i < 6 ? J0 : 7 + 3 * H) + (i >> 1)) * 1024 + (i & 1) * 128);
        bad |= b[i] ^ tag;
      }
    } while (__any_sync(0xffffffffu, tq == 1 && (bad & TAGM) != 0u) && ++n < SPIN_MAX);
    float s[8];
#pragma unroll
    for (int i = 0; i < 8; i++) s[i] = 0.f;
#pragma unroll
    for (int t = 0; t < 2; t++) {
      mma16816(&s[4 * t], q[6 * H], q[6 * H + 1], q[6 * H + 2], q[6 * H + 3], b[t], b[2 + t]);
      mma16816(&s[4 * t], q[6 * H + 4], q[6 * H + 5], 0u, 0u, b[4 + t], 0u);
    }
    if (st < 4 || (st >> 2) == anti) {
      const int z = dthr - (st & 3) * 16;
#pragma unroll
      for (int i = 0; i < 8; i++)
        if (((i >> 2) * 8 + (i & 1) - (i & 2) * 4 <= z) != (st < 4)) s[i] = -INFINITY;
    }
    float n0 = fmaxf(fmaxf(s[0], s[1]), fmaxf(s[4], s[5])), n1 = fmaxf(fmaxf(s[2], s[3]), fmaxf(s[6], s[7]));
    n0 = fmaxf(n0, __shfl_xor_sync(0xffffffffu, n0, 1));
    n1 = fmaxf(n1, __shfl_xor_sync(0xffffffffu, n1, 1));
    n0 = fmaxf(m0, fmaxf(n0, __shfl_xor_sync(0xffffffffu, n0, 2)));
    n1 = fmaxf(m1, fmaxf(n1, __shfl_xor_sync(0xffffffffu, n1, 2)));
    const float al0 = ex2(m0 - n0), al1 = ex2(m1 - n1);
    m0 = n0;
    m1 = n1;
    const uint32_t p0 = pack2(ex2(s[0] - n0), ex2(s[1] - n0)), p1 = pack2(ex2(s[2] - n1), ex2(s[3] - n1));
    const uint32_t p2 = pack2(ex2(s[4] - n0), ex2(s[5] - n0)), p3 = pack2(ex2(s[6] - n1), ex2(s[7] - n1));
#pragma unroll
    for (int i = 6; i < 12; i++) asm volatile("movmatrix.sync.aligned.m8n8.trans.b16 %0, %0;" : "+r"(b[i]));
#pragma unroll
    for (int t = 0; t < 3; t++) {
      o[4 * t] *= al0; o[4 * t + 1] *= al0; o[4 * t + 2] *= al1; o[4 * t + 3] *= al1;
      mma16816(&o[4 * t], p0, p1, p2, p3, b[6 + 2 * t], b[7 + 2 * t]);
    }
  }
}
#define ATT_STEP(HQ, sq, kq, HP, op, pp, kv, sc, pc, W) do { \
  WG_FENCE(); qk_issue<HQ>(sq, q, qm[2 * HQ], qm[2 * HQ + 1], kq); WG_COMMIT(); WG_WAIT(1); pv_issue<HP>(op, pp, kv); WG_COMMIT(); \
  sm_exp(sc, pc, nk, flip); WG_WAIT(W); reg_fence(sq); } while (0)
__device__ __forceinline__ uint32_t bmul2(uint32_t a, uint32_t b) { uint32_t d; asm("mul.rn.bf16x2 %0, %1, %2;" : "=r"(d) : "r"(a), "r"(b)); return d; }
__device__ __forceinline__ uint32_t badd2(uint32_t a, uint32_t b) { uint32_t d; asm("add.rn.bf16x2 %0, %1, %2;" : "=r"(d) : "r"(a), "r"(b)); return d; }
__device__ __forceinline__ uint32_t bfma2(uint32_t a, uint32_t b, uint32_t c) { uint32_t d; asm("fma.rn.bf16x2 %0, %1, %2, %3;" : "=r"(d) : "r"(a), "r"(b), "r"(c)); return d; }

__global__ void __cluster_dims__(2, 1, 1) __launch_bounds__(384, 1) fused_block_kernel(const __grid_constant__ Params P) {
  extern __shared__ __align__(1024) uint8_t smem[];
  const uint32_t sb = s2u(smem);
  const int tid = threadIdx.x, lane = tid & 31, warp = __shfl_sync(0xffffffffu, tid >> 5, 0);
  const uint32_t bars = sb + OFF_MISC;
#define BAR(i) (bars + 8u * (uint32_t)(i))
#define TP(i)
  if (tid == 288) {
#pragma unroll
    for (int u = 0; u < 6; u++) mbar_init(BAR(u), 1);
    asm volatile("fence.mbarrier_init.release.cluster;" ::: "memory");
  }
  __syncwarp();
  asm volatile("barrier.cluster.arrive.relaxed.aligned;" ::: "memory");
  TP(0);
  const uint32_t rank = blockIdx.x & 1;
  const uint32_t mp = P.map[blockIdx.x >> 3] >> ((blockIdx.x & 6) * 4);
  const int c = mp & 7, rb = (int)(((mp >> 2) & 14) + rank);
  const int tile = rb * 8 + c;
  const int odd = c & 1;
  const int mainch = (c >> 1) * 5 + (odd ? 3 : 0), leftch = (c >> 1) * 10 + (odd ? 5 : 4);
  const int kb0 = (5 * (rb >> 1)) >> 2;
  if (lane == 0 && (warp >> 1) != 4) {
    const int j = warp < 8 ? warp + 3 : warp - 9;
    const int cnt = (int)(0x4a108208108421ull >> (5 * j)) & 31;
#pragma unroll
    for (int u = 0; u < 6; u++) mbar_init(BAR(j * 6 + u), cnt);
    asm volatile("fence.mbarrier_init.release.cluster;" ::: "memory");
  }
  __syncwarp();
  TP(1);
  if (warp >= 8) asm volatile("setmaxnreg.dec.sync.aligned.u32 56;");
  TP(2);
  if (warp > 8) {
    asm volatile("bar.arrive 1, 384;" ::: "memory");
    if (lane == 0) {
      if (warp == 9) {
        mbar_expect(BAR(B_QFULL), QST);
        tma2d(sb, &P.mX, kb0 * 64, rb * 128, BAR(B_QFULL));
      } else {
        asm volatile("prefetch.tensormap [%0];" ::"l"(warp == 10 ? &P.mWqM : &P.mWqL) : "memory");
      }
    }
    __syncwarp();
    asm volatile("bar.sync 2, 128;" ::: "memory");
  } else {
    asm volatile("bar.sync 1, 384;" ::: "memory");
  }
  TP(3);
  if (tid < 208) {
    const uint8_t* pp = tid < 192 ? reinterpret_cast<const uint8_t*>(P.wqkv) + (size_t)(kb0 * 64 + (int)rank * 32 + (tid & 31)) * 3840 + (tid >> 6) * 1280 + c * 160 + (tid & 32) * 4
                                  : reinterpret_cast<const uint8_t*>(P.x) + (size_t)(rb * 128 + c * 16 + tid - 192) * 1280 + kb0 * 128;
    l2_prefetch(pp);
  }
  if (warp == 8) {
    asm volatile("bar.arrive 2, 128;\nbarrier.cluster.wait.acquire.aligned;" ::: "memory");
    TP(4);
    if (lane == 0) {
#pragma unroll 1
      for (int kt = 0; kt < 4; kt++) {
        const uint32_t a = sb + kt * QST, fb = BAR(B_QFULL + kt);
        const int k0 = (kb0 + kt < 10 ? kb0 + kt : kb0 + kt - 10) * 64;
        if (kt) mbar_expect(fb, QST);
        tma4d_mc(a + 16384 + rank * 12288, &P.mWqM, 0, k0 + rank * 32, mainch, 0, fb);
        tma4d_mc(a + 40960 + rank * 3072, &P.mWqL, 0, k0 + rank * 32, leftch, 0, fb);
        if (kt) tma2d(a, &P.mX, k0, rb * 128, fb);
        if (kt == 0) TP(5);
      }
      mbar_expect(BAR(B_XROW), 20480);
      bulk_load(sb + OFF_XROW, reinterpret_cast<const uint8_t*>(P.x) + (size_t)(rb * 128 + c * 16) * 1280, 20480, BAR(B_XROW));
    }
    else if (lane < 4) mbar_arrive(BAR(B_XROW));
    __syncwarp();
    STAMPW(9);
  }
  const int sc = (27 * c + 3) >> 2;

  if (warp >= 8) {
    const uint32_t epoch = __shfl_sync(0xffffffffu, ldcg32(&g_epoch[tile * 32 + lane]), 0) + 1u;
    const uint32_t ep = epoch & 3u, tag = (epoch & 1u) | ((epoch & 2u) << 15);
    if (warp == 8) {
      if (lane == 0) {
#pragma unroll 1
        for (int kt = 4; kt < 10; kt++) {
          const int st = kt & 3;
          mbar_wait(BAR(B_QEMPTY + st), ((kt >> 2) - 1) & 1);
          const uint32_t a = sb + st * QST, fb = BAR(B_QFULL + st);
          const int k0 = (kb0 + kt < 10 ? kb0 + kt : kb0 + kt - 10) * 64;
          mbar_expect(fb, QST);
          tma4d_mc(a + 16384 + rank * 12288, &P.mWqM, 0, k0 + rank * 32, mainch, 0, fb);
          tma4d_mc(a + 40960 + rank * 3072, &P.mWqL, 0, k0 + rank * 32, leftch, 0, fb);
          tma2d(a, &P.mX, k0, rb * 128, fb);
        }
        l2_prefetch_bulk(reinterpret_cast<const uint8_t*>(P.wo) + tile * 6400, 6400);
        l2_prefetch_bulk(reinterpret_cast<const uint8_t*>(P.w1) + tile * 17280, 17280);
        l2_prefetch_bulk(reinterpret_cast<const uint8_t*>(P.w2) + tile * 17280, 17280);
        const CUtensorMap* mW1 = rank ? &P.mW1b : &P.mW1a;
        asm volatile("prefetch.tensormap [%0];" ::"l"(&P.mWo) : "memory");
        asm volatile("prefetch.tensormap [%0];" ::"l"(mW1) : "memory");
        asm volatile("prefetch.tensormap [%0];" ::"l"(&P.mW2) : "memory");
        mbar_wait(BAR(B_QEMPTY + 0), 0);
        mbar_wait(BAR(B_QEMPTY + 1), 0);
        if (rb) mbar_wait(BAR(B_KVFULL + 3), 0);
        mbar_expect(BAR(B_WOB), 89600);
#pragma unroll 1
        for (int i = 0; i < 4 - (int)rank; i++) {
          const int pos = rank * 4 + i;
          tma3d_mc(sb + OFF_WOB + pos * 12800, &P.mWo, 0, ((c + pos) & 7) * 80, c * 5, BAR(B_WOB));
        }
#pragma unroll 1
        for (int s = 0; s < 8; s++) {
          if (s == 0) {
            mbar_wait(BAR(B_ATT2), 0);
            mbar_expect(BAR(B_WOB7), 12800);
            if (rank) tma3d_mc(sb + OFF_WOB + 7 * 12800, &P.mWo, 0, ((c + 7) & 7) * 80, c * 5, BAR(B_WOB7));
            mbar_wait(BAR(B_OL1), 0);
          } else if (s == 1) mbar_wait(BAR(B_ATT4), 0);
          else if (s == 3 || s == 4) mbar_wait(BAR(s == 3 ? B_WODP : B_WODP2), 0);
          else if (s >= 5) mbar_wait(BAR(B_BEMPTY + s - 5), 0);
          const uint32_t fb = BAR(B_BFULL + s);
          mbar_expect(fb, 35840);
          tma3d_mc(sb + w1b_addr(s) + rank * 20480, mW1, 0, ((c + s) & 7) * 80, sc + rank * 4, fb);
        }
#pragma unroll 1
        for (int s = 0; s < 5; s++) {
          mbar_wait(s < 3 ? BAR(B_BEMPTY + 4 + s) : BAR(B_W2E + s - 3), 0);
          const uint32_t dst = sb + (s < 3 ? s : s - 3) * W2SLOT + rank * 14336, fb = BAR(B_W2FULL + s);
          const int bx0 = (c + 2 * s) % 10, bx1 = (c + 2 * s + 1) % 10;
          mbar_expect(fb, W2SLOT);
          tma2d_mc(dst, &P.mW2, bx0 * 64, sc * 32 + rank * 112, fb);
          tma2d_mc(dst + 28672, &P.mW2, bx1 * 64, sc * 32 + rank * 112, fb);
        }
      }
      __syncwarp();
    } else {
      mbar_wait(BAR(B_XROW), 0);
#pragma unroll 1
      for (int p = warp - 9; p < 8; p += 3) {
        const int row = rb * 128 + c * 16 + p * 2 + (lane >> 4);
        const uint8_t* xb = smem + OFF_XROW + (p * 2 + (lane >> 4)) * 1280 + (lane & 15) * 16;
        uint4 xv[5];
#pragma unroll
        for (int i = 0; i < 5; i++) xv[i] = *reinterpret_cast<const uint4*>(xb + i * 256);
        float s = 0.f;
#pragma unroll
        for (int i = 0; i < 5; i++)
          s += ((bf_lo(xv[i].x) + bf_hi(xv[i].x)) + (bf_lo(xv[i].y) + bf_hi(xv[i].y))) + ((bf_lo(xv[i].z) + bf_hi(xv[i].z)) + (bf_lo(xv[i].w) + bf_hi(xv[i].w)));
#pragma unroll
        for (int o = 8; o; o >>= 1) s += __shfl_xor_sync(0xffffffffu, s, o);
        const float mean = s * (1.f / 640.f);
        float m2 = 0.f;
#pragma unroll
        for (int i = 0; i < 5; i++) {
          const uint32_t u[4] = {xv[i].x, xv[i].y, xv[i].z, xv[i].w};
#pragma unroll
          for (int j = 0; j < 4; j++) {
            const float d0 = bf_lo(u[j]) - mean, d1 = bf_hi(u[j]) - mean;
            m2 += d0 * d0 + d1 * d1;
          }
        }
#pragma unroll
        for (int o = 8; o; o >>= 1) m2 += __shfl_xor_sync(0xffffffffu, m2, o);
        if ((lane & 15) == 0) g_xstat[row] = make_float2(mean, tag32(rsqrtf(m2 * (1.f / 640.f) + 1e-5f), ep));
      }
      if (warp == 9) STAMPW(17);
      if (warp == 11) {
        mbar_wait(BAR(B_PRE), 0);
        if (lane < 30) {
          float4 a = make_float4(0.f, 0.f, 0.f, 0.f);
#pragma unroll 4
          for (int i = 0; i < 16; i++) {
            const float4 v = *reinterpret_cast<const float4*>(smem + OFF_PRE + i * 512 + lane * 16);
            a.x += v.x; a.y += v.y; a.z += v.z; a.w += v.w;
          }
          *reinterpret_cast<float4*>(&g_csq[((rb >> 1) * 8 + c) * 240 + rank * 120 + lane * 4]) = make_float4(tag32(a.x, ep), tag32(a.y, ep), tag32(a.z, ep), tag32(a.w, ep));
        }
        __syncwarp();
        STAMPW(0);
      } else {
        if (warp == 10) {
          mbar_wait(BAR(B_QEMPTY + 3), 0);
          uint4 v0, v1;
          uint32_t n = 0;
          do {
            v0 = ldcg128(&g_xstat[rb * 128 + lane * 2]);
            v1 = ldcg128(&g_xstat[rb * 128 + 64 + lane * 2]);
          } while (__any_sync(0xffffffffu, (((v0.y ^ ep) | (v0.w ^ ep) | (v1.y ^ ep) | (v1.w ^ ep)) & 3u) != 0u) && ++n < SPIN_MAX);
          *reinterpret_cast<uint4*>(smem + OFF_XST + lane * 16) = v0;
          *reinterpret_cast<uint4*>(smem + OFF_XST + 512 + lane * 16) = v1;
          __syncwarp();
          if (lane < 2) mbar_arrive(BAR(B_STAT));
          STAMPW(18);
        }
        if (warp == 10 && lane == 0) {
#pragma unroll 1
          for (int i = 0; i < 1 + KVP; i++) {
            if (i < 2) mbar_wait(BAR(B_KVOWN + i), 0);
            const uint32_t off = i ? (uint32_t)(i - 1) * (KVB / KVP) + KVB : 0u;
            asm volatile("cp.async.bulk.wait_group.read 0;\ncp.async.bulk.global.shared::cta.bulk_group [%0], [%1], %2;\ncp.async.bulk.commit_group;"
                         ::"l"(g_kv + (size_t)(rb * 16 + c) * KVB + (i ? 7 * KVB + off : 0u)), "r"(sb + kv_addr(4) + off), "r"(i ? KVB / KVP : KVB) : "memory");
          }
          asm volatile("cp.async.bulk.wait_group.read 0;" ::: "memory");
          mbar_arrive_pair(BAR(B_ATT2));
          STAMPW(6);
        }
        __syncwarp();
      }
      if (warp != 10) {
        const int u = (warp - 9) * 16 + lane;
        mbar_wait(BAR(B_QEMPTY + 3), 0);
        gather8(smem + OFF_CS + u * 16, g_csq + c * 240 + min(u, 59) * 4, 1920, ep, u < 60);
        __syncwarp();
        if (lane == 0) mbar_arrive(BAR(B_STAT));
        if (warp == 9) STAMPW(16);
        mbar_wait(BAR(B_Q23), 0);
      }
#pragma unroll 1
      for (int bi = warp == 9 ? 2 : warp == 10 ? 3 : 1; bi >= 0; bi -= (warp == 9 ? 2 : 4)) {
        const int blk = 2 * rb - 4 + bi;
        if (blk < 0) continue;
        const uint8_t* src = g_kv + (size_t)(blk * 8 + c) * KVB;
        const uint32_t dst = sb + kv_addr(bi);
        uint32_t n = 0, ph = 0;
        while (!__all_sync(0xffffffffu, ((ldcg32(src + lane * 704 + 692) ^ tag) & TAGM) == 0u) && ++n < SPIN_MAX) {}
        if (warp == 9 && bi == 2) STAMPW(3);
        while (true) {
          if (lane == 0) {
            mbar_expect(BAR(B_KVLAND + bi), KVB);
            bulk_load(dst, src, KVB, BAR(B_KVLAND + bi));
          }
          mbar_wait(BAR(B_KVLAND + bi), ph);
          ph ^= 1u;
          uint32_t bad = 0;
#pragma unroll 11
          for (int i = 0; i < 44; i++) {
            uint32_t v;
            asm volatile("ld.shared.u32 %0, [%1];" : "=r"(v) : "r"(dst + (i * 32 + lane) * 16 + 4) : "memory");
            bad |= v ^ tag;
          }
          if (!__any_sync(0xffffffffu, (bad & TAGM) != 0u) || ++n >= SPIN_MAX) break;
        }
        if (lane == 0) {
          mbar_arrive(BAR(B_KVFULL + bi));
        }
        if (warp == 9 && bi == 2) STAMPW(5);
        if (warp == 10) STAMPW(7);
      }
      __syncwarp();
      asm volatile("barrier.cluster.wait.acquire.aligned;" ::: "memory");
      if (warp == 10) {
        const int l16 = lane & 15, col = sc * 32 + (int)rank * 112 + l16 * 8;
        const uint8_t* wb = reinterpret_cast<const uint8_t*>(P.w1) + (size_t)((rb >> 1) * 80 + (lane >> 4) * 40) * 3456 + (size_t)col * 2;
        float acc[8];
#pragma unroll
        for (int i = 0; i < 8; i++) acc[i] = 0.f;
        if (l16 < 14 && col < 1728) {
#pragma unroll 1
          for (int i = 0; i < 40; i += 8) {
            uint4 v[8];
#pragma unroll
            for (int u = 0; u < 8; u++) v[u] = __ldg(reinterpret_cast<const uint4*>(wb + (size_t)(i + u) * 3456));
#pragma unroll
            for (int u = 0; u < 8; u++) {
              acc[0] += bf_lo(v[u].x); acc[1] += bf_hi(v[u].x); acc[2] += bf_lo(v[u].y); acc[3] += bf_hi(v[u].y);
              acc[4] += bf_lo(v[u].z); acc[5] += bf_hi(v[u].z); acc[6] += bf_lo(v[u].w); acc[7] += bf_hi(v[u].w);
            }
          }
        }
        __syncwarp();
#pragma unroll
        for (int i = 0; i < 4; i++) {
          const float o = __shfl_xor_sync(0xffffffffu, lane < 16 ? acc[4 + i] : acc[i], 16);
          acc[i] = tag32((lane < 16 ? acc[i] : acc[4 + i]) + o, ep);
        }
        if (l16 < 14) *reinterpret_cast<float4*>(&g_cs1[((rb >> 1) * 8 + c) * 224 + rank * 112 + l16 * 8 + (lane >> 4) * 4]) = make_float4(acc[0], acc[1], acc[2], acc[3]);
        STAMPW(4);
      } else if (warp == 9) {
#pragma unroll 1
        for (int r = 1; r >= 0; r--) {
          const int cc = (c + 1 + (lane >> 2)) & 7;
          const uint32_t* hp = &g_hint[((rb * 2 + r) * 8 + cc) * HS + (lane & 3)];
          const uint32_t fb = BAR(r ? B_QFULL : B_KVFULL);
          const uint32_t dst = sb + (r ? 102400u : lane < 12 ? 179200u : 107520u) + (lane >> 2) * 10240;
          mbar_wait(BAR(r ? B_ATT2 : B_ATTL), 0);
          mbar_wait(BAR(B_ATT3), 0);
          if (lane < 4) mbar_expect(fb + lane * 8, lane < 3 ? 20480 : 10240);
          uint32_t n = 0, todo = 0x1111111u;
          while (todo) {
            uint32_t ok = __ballot_sync(0xffffffffu, ldcg32(hp) == tag || n >= SPIN_MAX);
            ok &= ok >> 1;
            ok &= (ok >> 2) & todo;
            if (r == 0 && !mbar_test(BAR(B_OL1L))) ok &= 0xfffu;
            if ((ok >> lane) & 1u) bulk_load(dst, g_o + (size_t)(rb * 16 + r * 8 + cc) * 10240, 10240, fb + (lane >> 3) * 8);
            todo &= ~ok;
            if (++n > 2 * SPIN_MAX) break;
          }
        }
      } else if (warp == 11) {
        mbar_wait(BAR(B_ATT3), 0);
#pragma unroll 1
        for (int u = lane; u < 64; u += 32) gather8(smem + OFF_XS + u * 16, g_cs1 + c * 224 + min(u, 55) * 4, 1792, ep, u < 56);
        __syncwarp();
        if (lane == 0) mbar_arrive(BAR(B_CS1));
        STAMPW(1);
      }
    }
    if (warp == 9 || warp == 10) {
      const int r = warp - 9;
      uint32_t* fl = &g_oflag[(rb * 2 + r) * 8];
      mbar_wait(BAR(B_HST + r), 0);
      if (lane == 0) {
        asm volatile("cp.async.bulk.tensor.2d.global.shared::cta.bulk_group [%0, {%2, %3}], [%1];\ncp.async.bulk.commit_group;\ncp.async.bulk.wait_group 0;"
                     ::"l"(&P.mOutH), "r"(sb + OFF_HST + r * 10240), "r"(c * 80), "r"(rb * 128 + r * 64) : "memory");
        asm volatile("fence.proxy.async.global;\nst.release.gpu.global.u32 [%0], %1;" ::"l"(fl + c), "r"(epoch) : "memory");
      }
      __syncwarp();
      uint32_t n = 0;
      while (!__all_sync(0xffffffffu, ld_flag(fl + (lane & 7)) == epoch) && ++n < SPIN_MAX) {}
      if (lane == 0) mbar_arrive(BAR(B_OUTOK + r));
      STAMPW(2);
    } else if (warp == 11) {
      st_flag(&g_epoch[tile * 32 + lane], epoch);
    }
  } else {
    const int r = warp >> 2, w = warp & 3, gq = lane >> 2, tq = lane & 3;
    asm volatile("setmaxnreg.inc.sync.aligned.u32 224;");
    STAMP(4);
    uint32_t ep = ldcg32(&g_epoch[tile * 32 + lane]);
    const int b = rb * 2 + r;
    uint32_t q[24], qm[8], tag;
    STAMP(0);
    {
      float accM[96], accL[24];
      uint32_t fa[16], fb[16];
      const uint32_t xa = sb + (uint32_t)(warp * 16 + (lane & 15)) * 128u + (uint32_t)(((lane >> 4) ^ lane) & 7) * 16u;
#define QKV_ISSUE(f, kt) do { \
        const uint32_t a = ((kt) & 3) * QST; \
        const uint64_t dm = mkdesc(sb + a + 16384, desc_hi(2048, 512, 2)); \
        const uint64_t dl = mkdesc(sb + a + 40960, desc_hi(1024, 256, 3)); \
        mbar_wait(BAR(B_QFULL + ((kt) & 3)), ((kt) >> 2) & 1); \
        _Pragma("unroll") for (int k = 0; k < 4; k++) ldsm4(&f[4 * k], (xa ^ (k * 32)) + a); \
        WG_FENCE(); \
        _Pragma("unroll") for (int k = 0; k < 4; k++) { \
          wg_rs192(accM, f[4 * k], f[4 * k + 1], f[4 * k + 2], f[4 * k + 3], dm + (k >> 1) * 768 + (k & 1) * 64, (kt) | k); \
          wg_rs48(accL, f[4 * k], f[4 * k + 1], f[4 * k + 2], f[4 * k + 3], dl + (k >> 1) * 192 + (k & 1) * 32, (kt) | k); \
        } \
        WG_COMMIT(); \
        } while (0)
#pragma unroll 1
      for (int kt = 0; kt < 10; kt += 2) {
        QKV_ISSUE(fa, kt);
        WG_WAIT(1);
        if (lane == 0) {
          if (kt == 8) mbar_arrive(BAR(B_Q23));
          else if (kt) mbar_arrive_pair(BAR(B_QEMPTY + ((kt - 1) & 3)));
        }
        QKV_ISSUE(fb, kt + 1);
        if (kt == 0) {
          const int cl = min(lane & 15, 14) + (int)rank * 15, mat = cl / 10, pc = cl - mat * 10 - odd * 2;
          const bool mn = (unsigned)pc < 8u;
          const int pitch = mn ? 64 : 32;
          const uint8_t* wp = smem + (mn ? 16384 + mat * 4096 + (pc >> 2) * 2048 + ((pc ^ (warp >> 1)) & 3) * 16 : 40960 + mat * 1024 + ((pc ^ (warp >> 2)) & 1) * 16);
          float a[8];
#pragma unroll
          for (int i = 0; i < 8; i++) a[i] = 0.f;
#pragma unroll
          for (int u = 0; u < 5; u++) {
            const int kr = (rb >> 1) * 80 - kb0 * 64 + u * 16;
            const uint4 v = *reinterpret_cast<const uint4*>(wp + (kr >> 6) * QST + ((kr & 16) + (lane >> 4) * 8 + warp + (kr & 32) * (mn ? 6 : 3)) * pitch);
            a[0] += bf_lo(v.x); a[1] += bf_hi(v.x); a[2] += bf_lo(v.y); a[3] += bf_hi(v.y);
            a[4] += bf_lo(v.z); a[5] += bf_hi(v.z); a[6] += bf_lo(v.w); a[7] += bf_hi(v.w);
          }
          float4* dst = reinterpret_cast<float4*>(smem + OFF_PRE + warp * 1024 + lane * 32);
          dst[0] = make_float4(a[0], a[1], a[2], a[3]);
          dst[1] = make_float4(a[4], a[5], a[6], a[7]);
          __syncwarp();
          if (lane == 0) mbar_arrive(BAR(B_PRE));
          STAMP(5);
        } else if (kt == 4) {
          asm volatile("barrier.cluster.wait.acquire.aligned;" ::: "memory");
        }
        WG_WAIT(1);
        if (lane == 0 && kt != 6) mbar_arrive_pair(BAR(B_QEMPTY + (kt & 3)));
      }
      ep = (__shfl_sync(0xffffffffu, ep, 0) + 1u) & 3u;
      tag = (ep & 1u) | ((ep & 2u) << 15);
      mbar_wait(BAR(B_STAT), 0);
      const float2 s0 = lds64f(sb + OFF_XST + (warp * 16 + gq) * 8), s1 = lds64f(sb + OFF_XST + (warp * 16 + gq + 8) * 8);
      mbar_wait(BAR(B_Q23), 0);
      WG_WAIT(0);
      reg_fence(accM); reg_fence(accL);
      if (lane == 0) mbar_arrive_pair(BAR(B_QEMPTY + 1));
      STAMP(2);
      const uint32_t km = tq == 1 ? ~TAGM : 0xffffffffu, kt1 = tq == 1 ? tag : 0u;
      const uint32_t csM = sb + OFF_CS + (odd ? 64 : 0) + tq * 8, csL = sb + OFF_CS + (odd ? 0 : 256) + tq * 8;
      const uint32_t kvo = sb + kv_addr(4 + r) + (uint32_t)(w * 16 + ((lane >> 3) & 1) * 8 + (lane & 7)) * 16u + (uint32_t)(lane >> 4) * 1024u;
      const float qs = 0.22360679774997896f * 1.4426950408889634f;
      const bool lo = tq < 2;
      uint32_t qj[20], kj[20];
#pragma unroll
      for (int mm = 0; mm < 3; mm++) {
        const int mat = (mm + 1) % 3;
        const float r0 = mat == 0 ? s0.y * qs : s0.y, r1 = mat == 0 ? s1.y * qs : s1.y;
        const float n0 = -s0.x * r0, n1 = -s1.x * r1;
        uint32_t pk[20];
#pragma unroll
        for (int t = 0; t < 10; t++) {
          const float* a = t < 8 ? &accM[(mat * 8 + t) * 4] : &accL[(mat * 2 + t - 8) * 4];
          const float2 cs = lds64f(t < 8 ? csM + mat * 320 + t * 32 : csL + mat * 320 + (t - 8) * 32);
          pk[2 * t] = pack2(fmaf(a[0], r0, cs.x * n0), fmaf(a[1], r0, cs.y * n0));
          pk[2 * t + 1] = pack2(fmaf(a[2], r1, cs.x * n1), fmaf(a[3], r1, cs.y * n1));
        }
#pragma unroll
        for (int i = 0; i < 20; i++) qj[i] = odd ? pk[(i + 16) % 20] : pk[i];
        if (mat == 1) {
#pragma unroll
          for (int i = 0; i < 20; i++) kj[i] = (qj[i] & km) | kt1;
#pragma unroll
          for (int t = 0; t < 10; t += 2) stsm4(kvo + t * 1024, kj[2 * t], kj[2 * t + 1], kj[2 * t + 2], kj[2 * t + 3]);
        }
        if (mat == 2) {
          const uint32_t one = (tq & 1) ? 0u : 0x3f80u;
          uint32_t vv[24];
#pragma unroll
          for (int hp = 0; hp < 2; hp++) {
            const int j = hp * 10;
#pragma unroll
            for (int i = 0; i < 4; i++) { vv[hp * 12 + i] = qj[j + i]; vv[hp * 12 + 8 + i] = qj[j + 6 + i]; }
            vv[hp * 12 + 4] = lo ? qj[j + 4] : one; vv[hp * 12 + 5] = lo ? qj[j + 5] : one;
            vv[hp * 12 + 6] = lo ? one : qj[j + 4]; vv[hp * 12 + 7] = lo ? one : qj[j + 5];
          }
#pragma unroll
          for (int i = 0; i < 24; i++) vv[i] = (vv[i] & km) | kt1;
#pragma unroll
          for (int t = 0; t < 6; t++) stsm4(kvo + 10240 + t * 2048, vv[4 * t], vv[4 * t + 1], vv[4 * t + 2], vv[4 * t + 3]);
          fence_async_smem();
          __syncwarp();
          if (lane == 0) mbar_arrive(BAR(B_KVOWN + r));
        }
      }
#pragma unroll
      for (int hp = 0; hp < 2; hp++) {
        const int j = hp * 10;
        q[hp * 12 + 0] = qj[j + 0]; q[hp * 12 + 1] = qj[j + 1]; q[hp * 12 + 2] = qj[j + 2]; q[hp * 12 + 3] = qj[j + 3];
        q[hp * 12 + 4] = lo ? qj[j + 4] : 0u; q[hp * 12 + 5] = lo ? qj[j + 5] : 0u;
        q[hp * 12 + 6] = lo ? 0u : qj[j + 4]; q[hp * 12 + 7] = lo ? 0u : qj[j + 5];
        q[hp * 12 + 8] = qj[j + 6]; q[hp * 12 + 9] = qj[j + 7]; q[hp * 12 + 10] = qj[j + 8]; q[hp * 12 + 11] = qj[j + 9];
      }
#pragma unroll
      for (int h = 0; h < 4; h++) {
        const int j = (h >> 1) * 10 + (h & 1) * 4;
        const uint32_t d0 = bfma2(q[6 * h + 4], kj[j + 4], bfma2(q[6 * h + 2], kj[j + 2], bmul2(q[6 * h], kj[j])));
        const uint32_t d1 = bfma2(q[6 * h + 5], kj[j + 5], bfma2(q[6 * h + 3], kj[j + 3], bmul2(q[6 * h + 1], kj[j + 1])));
        uint32_t u = badd2(__byte_perm(d0, d1, 0x5410), __byte_perm(d0, d1, 0x7632));
        u = badd2(u, __shfl_xor_sync(0xffffffffu, u, 1));
        u = badd2(u, __shfl_xor_sync(0xffffffffu, u, 2));
        u = tq == 2 ? u ^ 0x80008000u : 0u;
        qm[2 * h] = u & 0xffffu;
        qm[2 * h + 1] = u >> 16;
        asm volatile("" : "+r"(qm[2 * h]), "+r"(qm[2 * h + 1]));
      }
    }
    STAMP(3);
    uint32_t x0[20], xr[20];
    {
      float o0[12], o1[12], o2[12], o3[12];
#pragma unroll
      for (int i = 0; i < 12; i++) { o0[i] = 0.f; o1[i] = 0.f; o2[i] = 0.f; o3[i] = 0.f; }
      float s0[32], s1[32];
      uint32_t p0[16], p1[16];
      const int dthr = w * 16 + gq - 2 * tq;
      const uint32_t seq = r ? 0x13245u : rb == 1 ? 0x324u : 0x13024u;
      const int anti = r ? 4 : rb == 1 ? 7 : 2;
      const int nit = rb >= 2 ? 5 : 2 * rb + 1 + r;
      mbar_wait(BAR(B_KVOWN + r), 0);
      uint32_t kb = ((sb + kv_addr(4 + r)) & 0x3FFFF) >> 4, kp = kb;
      WG_FENCE();
      qk_issue<0>(s0, q, qm[0], qm[1], kb);
      WG_COMMIT();
#pragma unroll
      for (int i = 0; i < 16; i++) p1[i] = 0u;
      WG_WAIT(0);
      reg_fence(s0);
#pragma unroll 1
      for (int it = 0; it < nit; it++) {
        const int nb = (it && it != anti) ? 4096 : dthr * 16 + 144;
        const uint32_t flip = it == anti ? 0xffffffffu : 0u;
        if (r == 0 && it == GOW) mbar_wait(BAR(B_GO), 0);
        if (r == 1 && it == GOIT && lane < 2) mbar_arrive(BAR(B_GO));
        uint32_t nk[9];
#pragma unroll
        for (int t = 0; t < 9; t++) asm("shl.b32 %0, %1, %2;" : "=r"(nk[t]) : "r"(0xffffffffu), "r"(max(nb - 128 * t, 0)));
        ATT_STEP(1, s1, kb, 3, o3, p1, kp, s0, p0, 1);
        ATT_STEP(2, s0, kb, 0, o0, p0, kb, s1, p1, 1);
        if (it == 2 && lane == 0) mbar_arrive_pair(BAR(B_ATT2));
        if (it == 3 && lane < 2) mbar_arrive(BAR(B_ATT3));
        ATT_STEP(3, s1, kb, 1, o1, p1, kb, s0, p0, 1);
        kp = kb;
        if (it + 1 < nit) {
          const int bi = (seq >> (4 * it + 4)) & 15;
          mbar_wait(bi == 4 ? BAR(B_KVOWN) : BAR(B_KVFULL + bi), 0);
          kb = ((sb + kv_addr(bi)) & 0x3FFFF) >> 4;
        }
        ATT_STEP(0, s0, kb, 2, o2, p0, kp, s1, p1, LASTW);
      }
      WG_FENCE();
      pv_issue<3>(o3, p1, kp);
      WG_COMMIT();
      WG_WAIT(0);
      reg_fence(o0); reg_fence(o1); reg_fence(o2); reg_fence(o3);
      if (nit < 3 && lane == 0) mbar_arrive_pair(BAR(B_ATT2));
      if (nit < 4 && lane < 2) mbar_arrive(BAR(B_ATT3));
      if (lane == 0) mbar_arrive(BAR(B_ATTL));
      if (r == 1 && nit <= GOIT && lane < 2) mbar_arrive(BAR(B_GO));
      {
        const uint32_t e0 = 63u << 23;
        const uint32_t ba = (__float_as_uint(o0[8]) - e0) | (__float_as_uint(o0[10]) - e0) | (__float_as_uint(o2[8]) - e0) | (__float_as_uint(o2[10]) - e0);
        const uint32_t bb = (__float_as_uint(o1[0]) - e0) | (__float_as_uint(o1[2]) - e0) | (__float_as_uint(o3[0]) - e0) | (__float_as_uint(o3[2]) - e0);
        if (__builtin_expect(__any_sync(0xffffffffu, ((tq == 2 ? ba : tq == 0 ? bb : 0u) >> 30) != FORCE_SAFE), 0)) {
          const uint8_t* kv = g_kv + (ptrdiff_t)((2 * rb - 4) * 8 + c) * KVB + lane * 4;
          safe_head<0>(o0, q, kv, seq, nit, anti, dthr, tq, tag);
          safe_head<1>(o1, q, kv, seq, nit, anti, dthr, tq, tag);
          safe_head<2>(o2, q, kv, seq, nit, anti, dthr, tq, tag);
          safe_head<3>(o3, q, kv, seq, nit, anti, dthr, tq, tag);
          __syncwarp();
        }
      }
      {
        const uint8_t* xp = reinterpret_cast<const uint8_t*>(P.x) + (size_t)(b * 64 + w * 16 + gq) * 1280 + c * 160 + tq * 4;
#pragma unroll
        for (int t = 0; t < 10; t++) {
          xr[2 * t] = ldnc32(xp + t * 16);
          xr[2 * t + 1] = ldnc32(xp + 8 * 1280 + t * 16);
        }
      }
      float inv[4][2];
      inv[0][0] = rcp(__shfl_sync(0xffffffffu, o0[8], (lane & 28) + 2));
      inv[0][1] = rcp(__shfl_sync(0xffffffffu, o0[10], (lane & 28) + 2));
      inv[1][0] = rcp(__shfl_sync(0xffffffffu, o1[0], lane & 28));
      inv[1][1] = rcp(__shfl_sync(0xffffffffu, o1[2], lane & 28));
      inv[2][0] = rcp(__shfl_sync(0xffffffffu, o2[8], (lane & 28) + 2));
      inv[2][1] = rcp(__shfl_sync(0xffffffffu, o2[10], (lane & 28) + 2));
      inv[3][0] = rcp(__shfl_sync(0xffffffffu, o3[0], lane & 28));
      inv[3][1] = rcp(__shfl_sync(0xffffffffu, o3[2], lane & 28));
      const bool lo = tq < 2;
#define OPK(dst, o, t, h) do { x0[dst] = pack2(o[4 * (t)] * inv[h][0], o[4 * (t) + 1] * inv[h][0]); x0[dst + 1] = pack2(o[4 * (t) + 2] * inv[h][1], o[4 * (t) + 3] * inv[h][1]); } while (0)
#define OPK2(dst, oa, ha, ob, hb) do { \
        const float i0 = lo ? inv[ha][0] : inv[hb][0], i1 = lo ? inv[ha][1] : inv[hb][1]; \
        x0[dst] = pack2((lo ? oa[8] : ob[0]) * i0, (lo ? oa[9] : ob[1]) * i0); \
        x0[dst + 1] = pack2((lo ? oa[10] : ob[2]) * i1, (lo ? oa[11] : ob[3]) * i1); } while (0)
      OPK(0, o0, 0, 0); OPK(2, o0, 1, 0); OPK2(4, o0, 0, o1, 1); OPK(6, o1, 1, 1); OPK(8, o1, 2, 1);
      OPK(10, o2, 0, 2); OPK(12, o2, 1, 2); OPK2(14, o2, 2, o3, 3); OPK(16, o3, 1, 3); OPK(18, o3, 2, 3);
    }
    const int bw = b * 4 + w;
    const size_t tile_off = (size_t)b * 81920 + w * 2560 + lane * 16;
    uint32_t* hint = &g_hint[b * 8 * HS + w];
    {
#pragma unroll
      for (int k = 0; k < 5; k++) {
        x0[4 * k] = tag16(x0[4 * k], tag);
        stg128(g_o + tile_off + c * 10240 + k * 512, x0[4 * k], x0[4 * k + 1], x0[4 * k + 2], x0[4 * k + 3]);
      }
      if (lane == 0) st_flag(hint + c * HS, tag);
      STAMP(6);
      float acc[40];
      constexpr uint64_t HI = desc_hi(2560, 256, 3);
      const uint64_t db = mkdesc(sb + OFF_WOB, HI);
      mbar_wait(BAR(B_WOB), 0);
#pragma unroll
      for (int t = 0; t < 10; t++) {
        acc[4 * t] = bf_lo(xr[2 * t]); acc[4 * t + 1] = bf_hi(xr[2 * t]);
        acc[4 * t + 2] = bf_lo(xr[2 * t + 1]); acc[4 * t + 3] = bf_hi(xr[2 * t + 1]);
      }
      WG_FENCE();
#pragma unroll
      for (int k = 0; k < 5; k++) wg_rs80(acc, x0[4 * k], x0[4 * k + 1], x0[4 * k + 2], x0[4 * k + 3], db + k * 32, 1);
      WG_COMMIT();
      mbar_wait(BAR(B_WOB7), 0);
      STAMP(7);
      WG_WAIT(0);
      uint32_t xa[7][20];
      const uint32_t ol = sb + w * 2560 + lane * 16;
#pragma unroll
      for (int i = 0; i < 7; i++) {
        if (!(i & 1)) mbar_wait(BAR((r ? B_QFULL : B_KVFULL) + (i >> 1)), r ? i < 4 : 4 * rb + i >= 8);
#pragma unroll
        for (int k = 0; k < 5; k++)
          asm volatile("ld.shared.v4.u32 {%0,%1,%2,%3}, [%4];" : "=r"(xa[i][4 * k]), "=r"(xa[i][4 * k + 1]), "=r"(xa[i][4 * k + 2]), "=r"(xa[i][4 * k + 3])
                       : "r"(ol + (r ? 102400u : i < 3 ? 179200u : 107520u) + i * 10240 + k * 512) : "memory");
      }
      {
        uint32_t bad = 0;
#pragma unroll
        for (int i = 0; i < 7; i++)
#pragma unroll
          for (int k = 0; k < 5; k++) bad |= xa[i][4 * k] ^ tag;
        bad = __any_sync(0xffffffffu, (bad & TAGM) != 0u);
        if (lane < 2 - r) mbar_arrive_pair(BAR(r ? B_OL1 : B_ATT4));
        if (r && lane < 2) mbar_arrive(BAR(B_OL1L));
        if (__builtin_expect(bad, 0)) {
#pragma unroll
          for (int i = 0; i < 7; i++) fix_tile(xa[i], g_o + tile_off, c, i + 1, tag);
        }
      }
      WG_FENCE();
#pragma unroll
      for (int i = 0; i < 7; i++) {
#pragma unroll
        for (int k = 0; k < 5; k++) wg_rs80(acc, xa[i][4 * k], xa[i][4 * k + 1], xa[i][4 * k + 2], xa[i][4 * k + 3], db + (i + 1) * 800 + k * 32, 1);
        if (i == 1 || i == 2 || i >= 4) WG_COMMIT();
        if (i == 2 || i == 5) {
          WG_WAIT(1);
          if (lane == 0) mbar_arrive_pair(BAR(i == 2 ? B_WODP : B_WODP2));
        }
      }
      WG_WAIT(0);
      reg_fence(acc);
      STAMP(8);
#pragma unroll
      for (int t = 0; t < 10; t++) {
        x0[2 * t] = pack2(acc[4 * t], acc[4 * t + 1]);
        x0[2 * t + 1] = pack2(acc[4 * t + 2], acc[4 * t + 3]);
      }
#pragma unroll
      for (int k = 0; k < 5; k++) {
        x0[4 * k] = tag16(x0[4 * k], tag);
        stg128(g_h + tile_off + c * 10240 + k * 512, x0[4 * k], x0[4 * k + 1], x0[4 * k + 2], x0[4 * k + 3]);
      }
      if (lane == 0) st_flag(hint + 256 * HS + c * HS, tag);
      mbar_wait(BAR(B_BFULL), 0);
      float sum0 = 0.f, sum1 = 0.f;
#pragma unroll
      for (int t = 0; t < 10; t++) {
        sum0 += acc[4 * t] + acc[4 * t + 1];
        sum1 += acc[4 * t + 2] + acc[4 * t + 3];
      }
      sum0 += __shfl_xor_sync(0xffffffffu, sum0, 1);
      sum1 += __shfl_xor_sync(0xffffffffu, sum1, 1);
      sum0 += __shfl_xor_sync(0xffffffffu, sum0, 2);
      sum1 += __shfl_xor_sync(0xffffffffu, sum1, 2);
      const float mu0 = sum0 * (1.f / 80.f), mu1 = sum1 * (1.f / 80.f);
      float v0 = 0.f, v1 = 0.f;
#pragma unroll
      for (int t = 0; t < 10; t++) {
        const float d0 = acc[4 * t] - mu0, d1 = acc[4 * t + 1] - mu0, d2 = acc[4 * t + 2] - mu1, d3 = acc[4 * t + 3] - mu1;
        v0 += d0 * d0 + d1 * d1;
        v1 += d2 * d2 + d3 * d3;
      }
      v0 += __shfl_xor_sync(0xffffffffu, v0, 1);
      v1 += __shfl_xor_sync(0xffffffffu, v1, 1);
      v0 += __shfl_xor_sync(0xffffffffu, v0, 2);
      v1 += __shfl_xor_sync(0xffffffffu, v1, 2);
      if (tq < 2) g_hstat[(bw * 8 + c) * 16 + gq + tq * 8] = make_float2(tq ? mu1 : mu0, tag32(tq ? v1 : v0, ep));
    }
    uint32_t ha[56];
    {
      float acc[112];
      constexpr uint64_t HI = desc_hi(5120, 512, 2);
#define ST4(i)
#define ST5(i)
#define W1_ISSUE(xx, i) do { \
        const uint64_t db = mkdesc(sb + w1b_addr(i), HI); \
        mbar_wait(BAR(B_BFULL + (i)), 0); \
        WG_FENCE(); \
        _Pragma("unroll") for (int k = 0; k < 5; k++) wg_rs224(acc, xx[4 * k], xx[4 * k + 1], xx[4 * k + 2], xx[4 * k + 3], db + k * 64, (i) | k); \
        WG_COMMIT(); } while (0)
#define W1_STEP(xx, i) do { \
        ST4(i); \
        W1_ISSUE(xx, i); \
        WG_WAIT(1); \
        ST5(i); \
        if ((i) != 4 && (i) != 1 && lane == 0) mbar_arrive_pair(BAR(B_BEMPTY - 1 + (i))); } while (0)
#define HT(i) ht, c, i
      const uint8_t* ht = g_h + tile_off;
      uint32_t x1[20], x2[20], x3[20];
      uint32_t ready = 0;
      probe_wait(ready, 1, hint + 256 * HS + ((c + lane) & 7) * HS, tag);
      ld_tile(x1, HT(1));
      probe_wait(ready, 2, hint + 256 * HS + ((c + lane) & 7) * HS, tag);
      ld_tile(x2, HT(2));
      probe_wait(ready, 3, hint + 256 * HS + ((c + lane) & 7) * HS, tag);
      ld_tile(x3, HT(3));
      STAMP(9);
      W1_ISSUE(x0, 0);
      {
        const uint32_t hs = sb + OFF_HST + (uint32_t)(warp * 16 + (lane & 15)) * 160u + (uint32_t)(lane >> 4) * 16u;
        mbar_wait(BAR(B_ATTL), 0);
#pragma unroll
        for (int k = 0; k < 5; k++) stsm4(hs + k * 32, x0[4 * k], x0[4 * k + 1], x0[4 * k + 2], x0[4 * k + 3]);
        fence_async_smem();
        __syncwarp();
        if (lane == 0) mbar_arrive(BAR(B_HST + r));
      }
      WG_WAIT(0);
      if (lane == 0) mbar_arrive_pair(BAR(B_BEMPTY));
      fix_tile(x1, HT(1), tag);
      fix_tile(x2, HT(2), tag);
      fix_tile(x3, HT(3), tag);
      STAMP(10);
      W1_STEP(x1, 1);
      ld_tile(x0, HT(4));
      W1_STEP(x2, 2);
      ld_tile(x1, HT(5));
      W1_STEP(x3, 3);
      fix_tile(x0, HT(4), tag);
      fix_tile(x1, HT(5), tag);
      ld_tile(x2, HT(6));
      W1_STEP(x0, 4);
      ld_tile(x3, HT(7));
      uint2 hs[4];
      const float2* hp = &g_hstat[(bw * 8 + tq * 2) * 16 + gq];
      hs[0] = ldcg64(hp); hs[1] = ldcg64(hp + 16); hs[2] = ldcg64(hp + 8); hs[3] = ldcg64(hp + 24);
      W1_STEP(x1, 5);
      fix_tile(x2, HT(6), tag);
      fix_tile(x3, HT(7), tag);
      W1_STEP(x2, 6);
      W1_STEP(x3, 7);
      {
        uint32_t n = 0;
        while (__any_sync(0xffffffffu, (((hs[0].y ^ ep) | (hs[1].y ^ ep) | (hs[2].y ^ ep) | (hs[3].y ^ ep)) & 3u) != 0u) && ++n < SPIN_MAX) {
          hs[0] = ldcg64(hp); hs[1] = ldcg64(hp + 16); hs[2] = ldcg64(hp + 8); hs[3] = ldcg64(hp + 24);
        }
      }
      float mean0, mean1, rs0, rs1;
      {
        const float a0 = __uint_as_float(hs[0].x), a1 = __uint_as_float(hs[1].x), b0 = __uint_as_float(hs[2].x), b1 = __uint_as_float(hs[3].x);
        float t0 = a0 + a1, t1 = b0 + b1;
        t0 += __shfl_xor_sync(0xffffffffu, t0, 1);
        t1 += __shfl_xor_sync(0xffffffffu, t1, 1);
        t0 += __shfl_xor_sync(0xffffffffu, t0, 2);
        t1 += __shfl_xor_sync(0xffffffffu, t1, 2);
        mean0 = t0 * 0.125f;
        mean1 = t1 * 0.125f;
        float u0 = __uint_as_float(hs[0].y) + __uint_as_float(hs[1].y) + 80.f * ((a0 - mean0) * (a0 - mean0) + (a1 - mean0) * (a1 - mean0));
        float u1 = __uint_as_float(hs[2].y) + __uint_as_float(hs[3].y) + 80.f * ((b0 - mean1) * (b0 - mean1) + (b1 - mean1) * (b1 - mean1));
        u0 += __shfl_xor_sync(0xffffffffu, u0, 1);
        u1 += __shfl_xor_sync(0xffffffffu, u1, 1);
        u0 += __shfl_xor_sync(0xffffffffu, u0, 2);
        u1 += __shfl_xor_sync(0xffffffffu, u1, 2);
        rs0 = 0.5f * rsqrtf(u0 * (1.f / 640.f) + 1e-5f);
        rs1 = 0.5f * rsqrtf(u1 * (1.f / 640.f) + 1e-5f);
      }
      mbar_wait(BAR(B_CS1), 0);
      WG_WAIT(0);
      reg_fence(acc);
      if (lane == 0) mbar_arrive_pair(BAR(B_BEMPTY + 7));
      STAMP(11);
      const float n0 = -mean0 * rs0, n1 = -mean1 * rs1;
#pragma unroll
      for (int t = 0; t < 28; t++) {
        const float2 cs = lds64f(sb + OFF_XS + t * 32 + tq * 8);
        const float h0 = fmaf(acc[4 * t], rs0, cs.x * n0), h1 = fmaf(acc[4 * t + 1], rs0, cs.y * n0);
        const float h2 = fmaf(acc[4 * t + 2], rs1, cs.x * n1), h3 = fmaf(acc[4 * t + 3], rs1, cs.y * n1);
        ha[2 * t] = pack2(fmaf(h0, tanh_fast(h0), h0), fmaf(h1, tanh_fast(h1), h1));
        ha[2 * t + 1] = pack2(fmaf(h2, tanh_fast(h2), h2), fmaf(h3, tanh_fast(h3), h3));
      }
      if ((c & 3) == 3) {
#pragma unroll
        for (int t = 48; t < 56; t++) ha[t] = 0u;
      }
    }
    STAMP(12);
    {
      float accA[64], accB[64];
      constexpr uint64_t HI = desc_hi(28672, 1024, 1);
      const uint32_t ost = sb + OFF_OST + (uint32_t)warp * 6144u;
      const uint32_t osw = ost + (uint32_t)(lane & 15) * 128u + (uint32_t)(((lane >> 4) ^ lane) & 7) * 16u;
#define W2_ISSUE(acc, s) do { \
        const uint64_t db = mkdesc(sb + ((s) % 3) * W2SLOT + mbar_wait0(BAR(B_W2FULL + (s))), HI); \
        WG_FENCE(); \
        _Pragma("unroll") for (int k = 0; k < 14; k++) wg_rs128(acc, ha[4 * k], ha[4 * k + 1], ha[4 * k + 2], ha[4 * k + 3], db + k * 128, k); \
        WG_COMMIT(); } while (0)
#define W2_OUT(acc, s) do { \
        reg_fence(acc); \
        if ((s) < 2 && lane == 0) mbar_arrive_pair(BAR(B_W2E + (s))); \
        _Pragma("unroll") for (int u = 2 * (s); u < 2 * (s) + 2; u++) { \
          const float* a = &acc[(u & 1) * 32]; \
          if (u >= 3) { if (lane == 0) asm volatile("cp.async.bulk.wait_group.read 2;" ::: "memory"); __syncwarp(); } \
          _Pragma("unroll") for (int t = 0; t < 8; t += 2) \
            stsm4((osw ^ (t * 16)) + (u % 3) * 2048, pack2(a[4 * t], a[4 * t + 1]), pack2(a[4 * t + 2], a[4 * t + 3]), pack2(a[4 * t + 4], a[4 * t + 5]), pack2(a[4 * t + 6], a[4 * t + 7])); \
          fence_async_smem(); \
          __syncwarp(); \
          if (lane == 0) \
            asm volatile("cp.reduce.async.bulk.tensor.2d.global.shared::cta.add.bulk_group [%0, {%2, %3}], [%1];\ncp.async.bulk.commit_group;" \
                         ::"l"(&P.mOut), "r"(ost + (u % 3) * 2048), "r"(min((uint32_t)c * 64u + u * 64u, (uint32_t)c * 64u + u * 64u - 640u)), "r"(rb * 128 + warp * 16) : "memory"); \
        } } while (0)
      W2_ISSUE(accA, 0);
      W2_ISSUE(accB, 1);
      mbar_wait(BAR(B_BEMPTY + 7), 0);
      mbar_wait(BAR(B_OUTOK + r), 0);
      fence_async_glob();
      WG_WAIT(1);
      W2_OUT(accA, 0);
      STAMP(13);
      W2_ISSUE(accA, 2);
      WG_WAIT(1);
      W2_OUT(accB, 1);
      W2_ISSUE(accB, 3);
      WG_WAIT(1);
      W2_OUT(accA, 2);
      W2_ISSUE(accA, 4);
      WG_WAIT(1);
      W2_OUT(accB, 3);
      STAMP(14);
      WG_WAIT(0);
      W2_OUT(accA, 4);
      STAMP(15);
      if (lane == 0) asm volatile("cp.async.bulk.wait_group.read 0;" ::: "memory");
      STAMP(17);
    }
  }
}

typedef CUresult (*EncodeFn)(CUtensorMap*, CUtensorMapDataType, cuuint32_t, void*, const cuuint64_t*, const cuuint64_t*, const cuuint32_t*,
                             const cuuint32_t*, CUtensorMapInterleave, CUtensorMapSwizzle, CUtensorMapL2promotion, CUtensorMapFloatOOBfill);

static void make_map(EncodeFn enc, CUtensorMap* m, const void* p, int nd, const cuuint64_t* dims, const cuuint64_t* strides, const cuuint32_t* box,
                     CUtensorMapSwizzle sw) {
  const cuuint32_t es[5] = {1, 1, 1, 1, 1};
  enc(m, CU_TENSOR_MAP_DATA_TYPE_BFLOAT16, (cuuint32_t)nd, const_cast<void*>(p), dims, strides, box, es, CU_TENSOR_MAP_INTERLEAVE_NONE, sw,
      CU_TENSOR_MAP_L2_PROMOTION_L2_128B, CU_TENSOR_MAP_FLOAT_OOB_FILL_NONE);
}

extern "C" void kernel_launch(void* const* d_in, const int* in_sizes, int n_in, void* d_out, int out_size) {
  (void)in_sizes; (void)n_in; (void)out_size;
  static EncodeFn enc = nullptr;
  if (!enc) {
    void* f = nullptr;
    cudaDriverEntryPointQueryResult qr;
    cudaGetDriverEntryPoint("cuTensorMapEncodeTiled", &f, cudaEnableDefault, &qr);
    enc = (EncodeFn)f;
    cudaFuncSetAttribute(fused_block_kernel, cudaFuncAttributeMaxDynamicSharedMemorySize, (int)SMEM_BYTES);
  }
  Params P;
  P.x = (const __nv_bfloat16*)d_in[0];
  P.wqkv = (const __nv_bfloat16*)d_in[1];
  P.wo = (const __nv_bfloat16*)d_in[2];
  P.w1 = (const __nv_bfloat16*)d_in[4];
  P.w2 = (const __nv_bfloat16*)d_in[5];
  P.out = (__nv_bfloat16*)d_out;
  for (int k = 0; k < 64; k++) {
    const int c = k < 4 ? k + 4 : k < 36 ? (k - 4) >> 3 : (k * 37 - 308) >> 8;
    const int g = k < 4 ? 0 : k < 36 ? (k - 1) & 7 : k - 33 - 7 * ((k * 37 - 1258) >> 8);
    reinterpret_cast<uint8_t*>(P.map)[k] = (uint8_t)(c + 8 * g);
  }
  { const cuuint64_t d[2] = {640, 2048}, s[1] = {1280}; const cuuint32_t b[2] = {64, 128}; make_map(enc, &P.mX, P.x, 2, d, s, b, CU_TENSOR_MAP_SWIZZLE_128B); }
  { const cuuint64_t d[4] = {32, 640, 20, 3}, s[3] = {3840, 64, 1280}; const cuuint32_t b[4] = {32, 32, 2, 3}; make_map(enc, &P.mWqM, P.wqkv, 4, d, s, b, CU_TENSOR_MAP_SWIZZLE_64B); }
  { const cuuint64_t d[4] = {16, 640, 40, 3}, s[3] = {3840, 32, 1280}; const cuuint32_t b[4] = {16, 32, 1, 3}; make_map(enc, &P.mWqL, P.wqkv, 4, d, s, b, CU_TENSOR_MAP_SWIZZLE_32B); }
  { const cuuint64_t d[3] = {16, 640, 40}, s[2] = {1280, 32}; const cuuint32_t b[3] = {16, 80, 5}; make_map(enc, &P.mWo, P.wo, 3, d, s, b, CU_TENSOR_MAP_SWIZZLE_32B); }
  { const cuuint64_t d[3] = {32, 640, 54}, s[2] = {3456, 64}; const cuuint32_t b[3] = {32, 80, 4}; make_map(enc, &P.mW1a, P.w1, 3, d, s, b, CU_TENSOR_MAP_SWIZZLE_64B); }
  { const cuuint64_t d[3] = {32, 640, 54}, s[2] = {3456, 64}; const cuuint32_t b[3] = {32, 80, 3}; make_map(enc, &P.mW1b, P.w1, 3, d, s, b, CU_TENSOR_MAP_SWIZZLE_64B); }
  { const cuuint64_t d[2] = {640, 1728}, s[1] = {1280}; const cuuint32_t b[2] = {64, 112}; make_map(enc, &P.mW2, P.w2, 2, d, s, b, CU_TENSOR_MAP_SWIZZLE_128B); }
  { const cuuint64_t d[2] = {640, 2048}, s[1] = {1280}; const cuuint32_t b[2] = {80, 64}; make_map(enc, &P.mOutH, P.out, 2, d, s, b, CU_TENSOR_MAP_SWIZZLE_NONE); }
  { const cuuint64_t d[2] = {640, 2048}, s[1] = {1280}; const cuuint32_t b[2] = {64, 16}; make_map(enc, &P.mOut, P.out, 2, d, s, b, CU_TENSOR_MAP_SWIZZLE_128B); }
  fused_block_kernel<<<128, 384, SMEM_BYTES, cudaStreamPerThread>>>(P);
}
```

```cpp
#include <cuda_runtime.h>
#include <cuda.h>
#include <cuda_bf16.h>
#include <stdint.h>

#define PROF 0
#define PF0 1
#define LASTW 1
#define LW0 1
#define LWX 0
#define QORD 2
#define LEAD0 1
#define KVP 8
#define GOIT 3
#define GOW 1
#define HPROBE 1
#define HS 4
#define HMODE 0
#define FORCE_SAFE 0u

__device__ __align__(1024) uint8_t g_kv[32 * 8 * 22528];
__device__ __align__(1024) uint8_t g_o[32 * 4 * 8 * 2560];
__device__ __align__(1024) uint8_t g_h[32 * 4 * 8 * 2560];
__device__ __align__(1024) float2 g_hstat[32 * 4 * 8 * 16];
__device__ __align__(128) uint32_t g_hint[2 * 32 * 8 * HS];
__device__ __align__(128) uint32_t g_oflag[32 * 8];
__device__ __align__(128) float2 g_xstat[2048];
__device__ __align__(128) float g_csq[8 * 8 * 240];
__device__ __align__(128) float g_cs1[8 * 8 * 224];
__device__ __align__(128) uint32_t g_epoch[128 * 32];
#define STAMP(slot)
#define STAMPW(slot)

struct Params {
  const __nv_bfloat16 *x, *wqkv, *wo, *w1, *w2;
  __nv_bfloat16* out;
  uint32_t map[16];
  CUtensorMap mX, mWqM, mWqL, mWo, mW1a, mW1b, mW2, mOutH, mOut[4];
};

constexpr uint32_t QST = 47104;
constexpr uint32_t KVB = 22528;
constexpr uint32_t OFF_WOB = 0;
constexpr uint32_t OFF_PRE = 188416;
constexpr uint32_t OFF_XROW = 196608;
constexpr uint32_t W2SLOT = 57344;
constexpr uint32_t OFF_OST = 174080;
constexpr uint32_t OFF_HST = 209920;
constexpr uint32_t OFF_CS = 229376;
constexpr uint32_t OFF_XST = 230336;
constexpr uint32_t OFF_XS = 230912;
constexpr uint32_t OFF_MISC = 231808;
constexpr uint32_t SMEM_BYTES = 232448;

enum {
  B_QFULL = 0, B_KVFULL = 4, B_KVLAND = 8, B_WOB = 12, B_WOB7 = 13, B_BFULL = 14, B_W2FULL = 22, B_CS1 = 27, B_OUTOK = 28,
  B_KVOWN = 30, B_HST = 32, B_STAT = 34, B_XROW = 35,
  B_Q23 = 36, B_PRE = 37, B_ATTL = 38, B_GO = 39, B_OL1 = 40, B_OL1L = 41,
  B_QEMPTY = 42, B_W2E = 46, B_WODP = 48, B_BEMPTY = 49, B_WODP2 = 57, B_ATT4 = 58, B_ATT3 = 59,
  B_ATT2 = 60
};
constexpr uint32_t TAGM = 0x00010001u;
constexpr uint32_t SPIN_MAX = 1u << 18;

__device__ __forceinline__ uint32_t s2u(const void* p) { return (uint32_t)__cvta_generic_to_shared(p); }
__device__ __forceinline__ void mbar_init(uint32_t b, int c) { asm volatile("mbarrier.init.shared::cta.b64 [%0], %1;" ::"r"(b), "r"(c)); }
__device__ __forceinline__ void mbar_expect(uint32_t b, int bytes) { asm volatile("mbarrier.arrive.expect_tx.shared::cta.b64 _, [%0], %1;" ::"r"(b), "r"(bytes) : "memory"); }
__device__ __forceinline__ void mbar_arrive(uint32_t b) { asm volatile("mbarrier.arrive.shared::cta.b64 _, [%0];" ::"r"(b) : "memory"); }
__device__ __forceinline__ void mbar_arrive_pair(uint32_t b) {
  asm volatile("{\n.reg .b32 r;\nmapa.shared::cluster.u32 r, %0, 0;\nmbarrier.arrive.shared::cluster.b64 _, [r];\n"
               "mapa.shared::cluster.u32 r, %0, 1;\nmbarrier.arrive.shared::cluster.b64 _, [r];\n}" ::"r"(b) : "memory");
}
__device__ __forceinline__ void mbar_wait(uint32_t b, uint32_t ph) {
  asm volatile("{\n.reg .pred p;\n.reg .u32 n;\nmov.u32 n, 0;\nW%=:\nmbarrier.try_wait.parity.shared::cta.b64 p, [%0], %1;\n"
               "add.u32 n, n, 1;\nsetp.lt.and.u32 p, n, 0x100000, !p;\n@p bra W%=;\n}" ::"r"(b), "r"(ph) : "memory");
}
__device__ __forceinline__ uint32_t mbar_wait0(uint32_t b) {
  uint32_t n;
  asm volatile("{\n.reg .pred p;\nmov.u32 %0, 0;\nW%=:\nmbarrier.try_wait.parity.shared::cta.b64 p, [%1], 0;\n"
               "add.u32 %0, %0, 1;\nsetp.lt.and.u32 p, %0, 0x100000, !p;\n@p bra W%=;\n}" : "=r"(n) : "r"(b) : "memory");
  return n >> 21;
}
__device__ __forceinline__ bool mbar_test(uint32_t b) {
  uint32_t v;
  asm volatile("{\n.reg .pred p;\nmbarrier.test_wait.parity.shared::cta.b64 p, [%1], 0;\nselp.u32 %0, 1, 0, p;\n}" : "=r"(v) : "r"(b) : "memory");
  return v != 0u;
}
__device__ __forceinline__ void tma2d(uint32_t dst, const CUtensorMap* m, int c0, int c1, uint32_t bar) {
  asm volatile("cp.async.bulk.tensor.2d.shared::cluster.global.mbarrier::complete_tx::bytes [%0], [%1, {%3, %4}], [%2];" ::"r"(dst), "l"(m), "r"(bar), "r"(c0), "r"(c1) : "memory");
}
__device__ __forceinline__ void tma2d_mc(uint32_t dst, const CUtensorMap* m, int c0, int c1, uint32_t bar) {
  asm volatile("cp.async.bulk.tensor.2d.shared::cluster.global.mbarrier::complete_tx::bytes.multicast::cluster [%0], [%1, {%3, %4}], [%2], %5;" ::"r"(dst), "l"(m), "r"(bar), "r"(c0), "r"(c1), "h"((uint16_t)3) : "memory");
}
__device__ __forceinline__ void tma3d_mc(uint32_t dst, const CUtensorMap* m, int c0, int c1, int c2, uint32_t bar) {
  asm volatile("cp.async.bulk.tensor.3d.shared::cluster.global.mbarrier::complete_tx::bytes.multicast::cluster [%0], [%1, {%3, %4, %5}], [%2], %6;" ::"r"(dst), "l"(m), "r"(bar), "r"(c0), "r"(c1), "r"(c2), "h"((uint16_t)3) : "memory");
}
__device__ __forceinline__ void tma4d_mc(uint32_t dst, const CUtensorMap* m, int c0, int c1, int c2, int c3, uint32_t bar) {
  asm volatile("cp.async.bulk.tensor.4d.shared::cluster.global.mbarrier::complete_tx::bytes.multicast::cluster [%0], [%1, {%3, %4, %5, %6}], [%2], %7;" ::"r"(dst), "l"(m), "r"(bar), "r"(c0), "r"(c1), "r"(c2), "r"(c3), "h"((uint16_t)3) : "memory");
}
__device__ __forceinline__ void bulk_load(uint32_t dst, const void* src, int bytes, uint32_t bar) {
  asm volatile("cp.async.bulk.shared::cluster.global.mbarrier::complete_tx::bytes [%0], [%1], %2, [%3];" ::"r"(dst), "l"(src), "r"(bytes), "r"(bar) : "memory");
}
__device__ __forceinline__ void tma4d_pf(const CUtensorMap* m, int c0, int c1, int c2, int c3) {
  asm volatile("cp.async.bulk.prefetch.tensor.4d.L2.global [%0, {%1, %2, %3, %4}];" ::"l"(m), "r"(c0), "r"(c1), "r"(c2), "r"(c3) : "memory");
}
__device__ __forceinline__ void l2_prefetch_bulk(const void* p, int bytes) { asm volatile("cp.async.bulk.prefetch.L2.global [%0], %1;" ::"l"(p), "r"(bytes) : "memory"); }
__device__ __forceinline__ void l2_prefetch(const void* p) { asm volatile("prefetch.global.L2 [%0];" ::"l"(p)); }
__device__ __forceinline__ uint32_t ld_flag(const uint32_t* p) { uint32_t v; asm volatile("ld.acquire.gpu.global.u32 %0, [%1];" : "=r"(v) : "l"(p) : "memory"); return v; }
__device__ __forceinline__ void st_flag(uint32_t* p, uint32_t v) { asm volatile("st.relaxed.gpu.global.u32 [%0], %1;" ::"l"(p), "r"(v) : "memory"); }
__device__ __forceinline__ void fence_gpu() { asm volatile("fence.acq_rel.gpu;" ::: "memory"); }
__device__ __forceinline__ void fence_async_smem() { asm volatile("fence.proxy.async.shared::cta;" ::: "memory"); }
__device__ __forceinline__ void fence_async_glob() { asm volatile("fence.proxy.async.global;" ::: "memory"); }
__device__ __forceinline__ uint4 ldcg128(const void* p) { uint4 v; asm volatile("ld.relaxed.gpu.global.v4.u32 {%0,%1,%2,%3}, [%4];" : "=r"(v.x), "=r"(v.y), "=r"(v.z), "=r"(v.w) : "l"(p) : "memory"); return v; }
__device__ __forceinline__ uint4 ldnc128(const void* p) { uint4 v; asm volatile("ld.global.nc.v4.u32 {%0,%1,%2,%3}, [%4];" : "=r"(v.x), "=r"(v.y), "=r"(v.z), "=r"(v.w) : "l"(p)); return v; }
__device__ __forceinline__ uint32_t ldnc32(const void* p) { uint32_t v; asm volatile("ld.global.nc.u32 %0, [%1];" : "=r"(v) : "l"(p)); return v; }
__device__ __forceinline__ uint2 ldcg64(const void* p) { uint2 v; asm volatile("ld.relaxed.gpu.global.v2.u32 {%0,%1}, [%2];" : "=r"(v.x), "=r"(v.y) : "l"(p) : "memory"); return v; }
__device__ __forceinline__ uint32_t ldcg32(const void* p) { uint32_t v; asm volatile("ld.relaxed.gpu.global.u32 %0, [%1];" : "=r"(v) : "l"(p) : "memory"); return v; }
__device__ __forceinline__ uint32_t pack2(float lo, float hi) { uint32_t r; asm("cvt.rn.bf16x2.f32 %0, %1, %2;" : "=r"(r) : "f"(hi), "f"(lo)); return r; }
__device__ __forceinline__ float bf_lo(uint32_t v) { return __uint_as_float(v << 16); }
__device__ __forceinline__ float bf_hi(uint32_t v) { return __uint_as_float(v & 0xffff0000u); }
__device__ __forceinline__ float ex2(float x) { float y; asm("ex2.approx.ftz.f32 %0, %1;" : "=f"(y) : "f"(x)); return y; }
__device__ __forceinline__ float rcp(float x) { float y; asm("rcp.approx.ftz.f32 %0, %1;" : "=f"(y) : "f"(x)); return y; }
__device__ __forceinline__ float tanh_fast(float x) { float y; asm("tanh.approx.f32 %0, %1;" : "=f"(y) : "f"(x)); return y; }
__device__ __forceinline__ void stsm4(uint32_t a, uint32_t r0, uint32_t r1, uint32_t r2, uint32_t r3) {
  asm volatile("stmatrix.sync.aligned.m8n8.x4.shared.b16 [%0], {%1,%2,%3,%4};" ::"r"(a), "r"(r0), "r"(r1), "r"(r2), "r"(r3) : "memory");
}
__device__ __forceinline__ void ldsm4(uint32_t* r, uint32_t a) {
  asm volatile("ldmatrix.sync.aligned.m8n8.x4.shared.b16 {%0,%1,%2,%3}, [%4];" : "=r"(r[0]), "=r"(r[1]), "=r"(r[2]), "=r"(r[3]) : "r"(a) : "memory");
}
__device__ __forceinline__ float2 lds64f(uint32_t a) { float2 v; asm volatile("ld.shared.v2.f32 {%0,%1}, [%2];" : "=f"(v.x), "=f"(v.y) : "r"(a)); return v; }
__device__ __forceinline__ constexpr uint64_t desc_hi(uint32_t lbo, uint32_t sbo, uint32_t sw) {
  return ((uint64_t)(lbo >> 4) << 16) | ((uint64_t)(sbo >> 4) << 32) | ((uint64_t)sw << 62);
}
__device__ __forceinline__ uint64_t mkdesc(uint32_t addr, uint64_t hi) { return hi | (uint64_t)((addr & 0x3FFFF) >> 4); }
#define WG_FENCE() asm volatile("wgmma.fence.sync.aligned;" ::: "memory")
#define WG_COMMIT() asm volatile("wgmma.commit_group.sync.aligned;" ::: "memory")
#define WG_WAIT_(n) asm volatile("wgmma.wait_group.sync.aligned " #n ";" ::: "memory")
#define WG_WAIT(n) WG_WAIT_(n)
template <int N> __device__ __forceinline__ void reg_fence(float (&a)[N]) {
#pragma unroll
  for (int i = 0; i < N; i++) asm volatile("" : "+f"(a[i])::"memory");
}

__device__ __forceinline__ void wg_rs48(float (&d)[24], uint32_t a0, uint32_t a1, uint32_t a2, uint32_t a3, uint64_t db, int sd) {
  asm volatile("{\n.reg .pred p;\nsetp.ne.b32 p, %29, 0;\n"
  "wgmma.mma_async.sync.aligned.m64n48k16.f32.bf16.bf16 {%0, %1, %2, %3, %4, %5, %6, %7, %8, %9, %10, %11, %12, %13, %14, %15, %16, %17, %18, %19, %20, %21, %22, %23}, {%24, %25, %26, %27}, %28, p, 1, 1, 1;\n}\n"
  : "+f"(d[0]), "+f"(d[1]), "+f"(d[2]), "+f"(d[3]), "+f"(d[4]), "+f"(d[5]), "+f"(d[6]), "+f"(d[7]), "+f"(d[8]), "+f"(d[9]), "+f"(d[10]), "+f"(d[11]), "+f"(d[12]), "+f"(d[13]), "+f"(d[14]), "+f"(d[15]), "+f"(d[16]), "+f"(d[17]), "+f"(d[18]), "+f"(d[19]), "+f"(d[20]), "+f"(d[21]), "+f"(d[22]), "+f"(d[23]) : "r"(a0), "r"(a1), "r"(a2), "r"(a3), "l"(db), "r"(sd));
}
__device__ __forceinline__ void wg_rs80(float (&d)[40], uint32_t a0, uint32_t a1, uint32_t a2, uint32_t a3, uint64_t db, int sd) {
  asm volatile("{\n.reg .pred p;\nsetp.ne.b32 p, %45, 0;\n"
  "wgmma.mma_async.sync.aligned.m64n80k16.f32.bf16.bf16 {%0, %1, %2, %3, %4, %5, %6, %7, %8, %9, %10, %11, %12, %13, %14, %15, %16, %17, %18, %19, %20, %21, %22, %23, %24, %25, %26, %27, %28, %29, %30, %31, %32, %33, %34, %35, %36, %37, %38, %39}, {%40, %41, %42, %43}, %44, p, 1, 1, 1;\n}\n"
  : "+f"(d[0]), "+f"(d[1]), "+f"(d[2]), "+f"(d[3]), "+f"(d[4]), "+f"(d[5]), "+f"(d[6]), "+f"(d[7]), "+f"(d[8]), "+f"(d[9]), "+f"(d[10]), "+f"(d[11]), "+f"(d[12]), "+f"(d[13]), "+f"(d[14]), "+f"(d[15]), "+f"(d[16]), "+f"(d[17]), "+f"(d[18]), "+f"(d[19]), "+f"(d[20]), "+f"(d[21]), "+f"(d[22]), "+f"(d[23]), "+f"(d[24]), "+f"(d[25]), "+f"(d[26]), "+f"(d[27]), "+f"(d[28]), "+f"(d[29]), "+f"(d[30]), "+f"(d[31]), "+f"(d[32]), "+f"(d[33]), "+f"(d[34]), "+f"(d[35]), "+f"(d[36]), "+f"(d[37]), "+f"(d[38]), "+f"(d[39]) : "r"(a0), "r"(a1), "r"(a2), "r"(a3), "l"(db), "r"(sd));
}
__device__ __forceinline__ void wg_rs224(float (&d)[112], uint32_t a0, uint32_t a1, uint32_t a2, uint32_t a3, uint64_t db, int sd) {
  asm volatile("{\n.reg .pred p;\nsetp.ne.b32 p, %117, 0;\n"
  "wgmma.mma_async.sync.aligned.m64n224k16.f32.bf16.bf16 {%0, %1, %2, %3, %4, %5, %6, %7, %8, %9, %10, %11, %12, %13, %14, %15, %16, %17, %18, %19, %20, %21, %22, %23, %24, %25, %26, %27, %28, %29, %30, %31, %32, %33, %34, %35, %36, %37, %38, %39, %40, %41, %42, %43, %44, %45, %46, %47, %48, %49, %50, %51, %52, %53, %54, %55, %56, %57, %58, %59, %60, %61, %62, %63, %64, %65, %66, %67, %68, %69, %70, %71, %72, %73, %74, %75, %76, %77, %78, %79, %80, %81, %82, %83, %84, %85, %86, %87, %88, %89, %90, %91, %92, %93, %94, %95, %96, %97, %98, %99, %100, %101, %102, %103, %104, %105, %106, %107, %108, %109, %110, %111}, {%112, %113, %114, %115}, %116, p, 1, 1, 1;\n}\n"
  : "+f"(d[0]), "+f"(d[1]), "+f"(d[2]), "+f"(d[3]), "+f"(d[4]), "+f"(d[5]), "+f"(d[6]), "+f"(d[7]), "+f"(d[8]), "+f"(d[9]), "+f"(d[10]), "+f"(d[11]), "+f"(d[12]), "+f"(d[13]), "+f"(d[14]), "+f"(d[15]), "+f"(d[16]), "+f"(d[17]), "+f"(d[18]), "+f"(d[19]), "+f"(d[20]), "+f"(d[21]), "+f"(d[22]), "+f"(d[23]), "+f"(d[24]), "+f"(d[25]), "+f"(d[26]), "+f"(d[27]), "+f"(d[28]), "+f"(d[29]), "+f"(d[30]), "+f"(d[31]), "+f"(d[32]), "+f"(d[33]), "+f"(d[34]), "+f"(d[35]), "+f"(d[36]), "+f"(d[37]), "+f"(d[38]), "+f"(d[39]), "+f"(d[40]), "+f"(d[41]), "+f"(d[42]), "+f"(d[43]), "+f"(d[44]), "+f"(d[45]), "+f"(d[46]), "+f"(d[47]), "+f"(d[48]), "+f"(d[49]), "+f"(d[50]), "+f"(d[51]), "+f"(d[52]), "+f"(d[53]), "+f"(d[54]), "+f"(d[55]), "+f"(d[56]), "+f"(d[57]), "+f"(d[58]), "+f"(d[59]), "+f"(d[60]), "+f"(d[61]), "+f"(d[62]), "+f"(d[63]), "+f"(d[64]), "+f"(d[65]), "+f"(d[66]), "+f"(d[67]), "+f"(d[68]), "+f"(d[69]), "+f"(d[70]), "+f"(d[71]), "+f"(d[72]), "+f"(d[73]), "+f"(d[74]), "+f"(d[75]), "+f"(d[76]), "+f"(d[77]), "+f"(d[78]), "+f"(d[79]), "+f"(d[80]), "+f"(d[81]), "+f"(d[82]), "+f"(d[83]), "+f"(d[84]), "+f"(d[85]), "+f"(d[86]), "+f"(d[87]), "+f"(d[88]), "+f"(d[89]), "+f"(d[90]), "+f"(d[91]), "+f"(d[92]), "+f"(d[93]), "+f"(d[94]), "+f"(d[95]), "+f"(d[96]), "+f"(d[97]), "+f"(d[98]), "+f"(d[99]), "+f"(d[100]), "+f"(d[101]), "+f"(d[102]), "+f"(d[103]), "+f"(d[104]), "+f"(d[105]), "+f"(d[106]), "+f"(d[107]), "+f"(d[108]), "+f"(d[109]), "+f"(d[110]), "+f"(d[111]) : "r"(a0), "r"(a1), "r"(a2), "r"(a3), "l"(db), "r"(sd));
}
__device__ __forceinline__ void wg_rs64k(float (&d)[32], uint32_t a0, uint32_t a1, uint32_t a2, uint32_t a3, uint64_t db, int sd) {
  asm volatile("{\n.reg .pred p;\nsetp.ne.b32 p, %37, 0;\n"
  "wgmma.mma_async.sync.aligned.m64n64k16.f32.bf16.bf16 {%0, %1, %2, %3, %4, %5, %6, %7, %8, %9, %10, %11, %12, %13, %14, %15, %16, %17, %18, %19, %20, %21, %22, %23, %24, %25, %26, %27, %28, %29, %30, %31}, {%32, %33, %34, %35}, %36, p, 1, 1, 0;\n}\n"
  : "+f"(d[0]), "+f"(d[1]), "+f"(d[2]), "+f"(d[3]), "+f"(d[4]), "+f"(d[5]), "+f"(d[6]), "+f"(d[7]), "+f"(d[8]), "+f"(d[9]), "+f"(d[10]), "+f"(d[11]), "+f"(d[12]), "+f"(d[13]), "+f"(d[14]), "+f"(d[15]), "+f"(d[16]), "+f"(d[17]), "+f"(d[18]), "+f"(d[19]), "+f"(d[20]), "+f"(d[21]), "+f"(d[22]), "+f"(d[23]), "+f"(d[24]), "+f"(d[25]), "+f"(d[26]), "+f"(d[27]), "+f"(d[28]), "+f"(d[29]), "+f"(d[30]), "+f"(d[31]) : "r"(a0), "r"(a1), "r"(a2), "r"(a3), "l"(db), "r"(sd));
}
__device__ __forceinline__ void wg_rs24(float (&d)[12], uint32_t a0, uint32_t a1, uint32_t a2, uint32_t a3, uint64_t db, int sd) {
  asm volatile("{\n.reg .pred p;\nsetp.ne.b32 p, %17, 0;\n"
  "wgmma.mma_async.sync.aligned.m64n24k16.f32.bf16.bf16 {%0, %1, %2, %3, %4, %5, %6, %7, %8, %9, %10, %11}, {%12, %13, %14, %15}, %16, p, 1, 1, 1;\n}\n"
  : "+f"(d[0]), "+f"(d[1]), "+f"(d[2]), "+f"(d[3]), "+f"(d[4]), "+f"(d[5]), "+f"(d[6]), "+f"(d[7]), "+f"(d[8]), "+f"(d[9]), "+f"(d[10]), "+f"(d[11]) : "r"(a0), "r"(a1), "r"(a2), "r"(a3), "l"(db), "r"(sd));
}
__device__ __forceinline__ void wg_rs128(float (&d)[64], uint32_t a0, uint32_t a1, uint32_t a2, uint32_t a3, uint64_t db, int sd) {
  asm volatile("{\n.reg .pred p;\nsetp.ne.b32 p, %69, 0;\n"
  "wgmma.mma_async.sync.aligned.m64n128k16.f32.bf16.bf16 {%0, %1, %2, %3, %4, %5, %6, %7, %8, %9, %10, %11, %12, %13, %14, %15, %16, %17, %18, %19, %20, %21, %22, %23, %24, %25, %26, %27, %28, %29, %30, %31, %32, %33, %34, %35, %36, %37, %38, %39, %40, %41, %42, %43, %44, %45, %46, %47, %48, %49, %50, %51, %52, %53, %54, %55, %56, %57, %58, %59, %60, %61, %62, %63}, {%64, %65, %66, %67}, %68, p, 1, 1, 1;\n}\n"
  : "+f"(d[0]), "+f"(d[1]), "+f"(d[2]), "+f"(d[3]), "+f"(d[4]), "+f"(d[5]), "+f"(d[6]), "+f"(d[7]), "+f"(d[8]), "+f"(d[9]), "+f"(d[10]), "+f"(d[11]), "+f"(d[12]), "+f"(d[13]), "+f"(d[14]), "+f"(d[15]), "+f"(d[16]), "+f"(d[17]), "+f"(d[18]), "+f"(d[19]), "+f"(d[20]), "+f"(d[21]), "+f"(d[22]), "+f"(d[23]), "+f"(d[24]), "+f"(d[25]), "+f"(d[26]), "+f"(d[27]), "+f"(d[28]), "+f"(d[29]), "+f"(d[30]), "+f"(d[31]), "+f"(d[32]), "+f"(d[33]), "+f"(d[34]), "+f"(d[35]), "+f"(d[36]), "+f"(d[37]), "+f"(d[38]), "+f"(d[39]), "+f"(d[40]), "+f"(d[41]), "+f"(d[42]), "+f"(d[43]), "+f"(d[44]), "+f"(d[45]), "+f"(d[46]), "+f"(d[47]), "+f"(d[48]), "+f"(d[49]), "+f"(d[50]), "+f"(d[51]), "+f"(d[52]), "+f"(d[53]), "+f"(d[54]), "+f"(d[55]), "+f"(d[56]), "+f"(d[57]), "+f"(d[58]), "+f"(d[59]), "+f"(d[60]), "+f"(d[61]), "+f"(d[62]), "+f"(d[63]) : "r"(a0), "r"(a1), "r"(a2), "r"(a3), "l"(db), "r"(sd));
}
__device__ __forceinline__ void wg_rs64(float (&d)[32], uint32_t a0, uint32_t a1, uint32_t a2, uint32_t a3, uint64_t db, int sd) {
  asm volatile("{\n.reg .pred p;\nsetp.ne.b32 p, %37, 0;\n"
  "wgmma.mma_async.sync.aligned.m64n64k16.f32.bf16.bf16 {%0, %1, %2, %3, %4, %5, %6, %7, %8, %9, %10, %11, %12, %13, %14, %15, %16, %17, %18, %19, %20, %21, %22, %23, %24, %25, %26, %27, %28, %29, %30, %31}, {%32, %33, %34, %35}, %36, p, 1, 1, 1;\n}\n"
  : "+f"(d[0]), "+f"(d[1]), "+f"(d[2]), "+f"(d[3]), "+f"(d[4]), "+f"(d[5]), "+f"(d[6]), "+f"(d[7]), "+f"(d[8]), "+f"(d[9]), "+f"(d[10]), "+f"(d[11]), "+f"(d[12]), "+f"(d[13]), "+f"(d[14]), "+f"(d[15]), "+f"(d[16]), "+f"(d[17]), "+f"(d[18]), "+f"(d[19]), "+f"(d[20]), "+f"(d[21]), "+f"(d[22]), "+f"(d[23]), "+f"(d[24]), "+f"(d[25]), "+f"(d[26]), "+f"(d[27]), "+f"(d[28]), "+f"(d[29]), "+f"(d[30]), "+f"(d[31]) : "r"(a0), "r"(a1), "r"(a2), "r"(a3), "l"(db), "r"(sd));
}

__device__ __forceinline__ uint32_t kv_addr(int i) {
  return 94208u + KVB * (uint32_t)((0x103254u >> (4 * i)) & 15u);
}
__device__ __forceinline__ uint32_t w1b_addr(int s) {
  return (s == 3 || s == 4) ? (uint32_t)(s - 3) * 35840u : 102400u + (uint32_t)(s >= 5 ? s - 5 : s) * 35840u;
}
__device__ __forceinline__ void stg128(void* p, uint32_t a, uint32_t b, uint32_t c, uint32_t d) {
  asm volatile("st.relaxed.gpu.global.v4.u32 [%0], {%1,%2,%3,%4};" ::"l"(p), "r"(a), "r"(b), "r"(c), "r"(d) : "memory");
}
__device__ __forceinline__ void stg32(void* p, uint32_t a) { asm volatile("st.global.u32 [%0], %1;" ::"l"(p), "r"(a) : "memory"); }
__device__ __forceinline__ void ld_tile(uint32_t (&a)[20], const uint8_t* p, int c, int i) {
  p += ((c + i) & 7) * 10240;
#pragma unroll
  for (int k = 0; k < 5; k++)
    asm volatile("ld.relaxed.gpu.global.v4.u32 {%0,%1,%2,%3}, [%4];" : "=r"(a[4 * k]), "=r"(a[4 * k + 1]), "=r"(a[4 * k + 2]), "=r"(a[4 * k + 3]) : "l"(p + k * 512) : "memory");
}
__device__ __forceinline__ uint32_t tag16(uint32_t v, uint32_t tag) { return (v & ~TAGM) | tag; }
__device__ __forceinline__ float tag32(float v, uint32_t ep) { return __uint_as_float((__float_as_uint(v) & ~3u) | ep); }
__device__ __forceinline__ void fix_tile(uint32_t (&a)[20], const uint8_t* p, int c, int i, uint32_t tag) {
  uint32_t n = 0;
  while (__any_sync(0xffffffffu, (((a[0] ^ tag) | (a[4] ^ tag) | (a[8] ^ tag) | (a[12] ^ tag) | (a[16] ^ tag)) & TAGM) != 0u) && ++n < SPIN_MAX) ld_tile(a, p, c, i);
}
__device__ __forceinline__ void probe_wait(uint32_t& ready, int i, const void* p, uint32_t tag) {
  uint32_t n = 0;
  while (!((ready >> i) & 1u) && ++n < SPIN_MAX) ready = __ballot_sync(0xffffffffu, ldcg32(p) == tag);
}
__device__ __forceinline__ void gather8(uint8_t* dst, const float* p, int stride, uint32_t ep, bool on) {
  uint4 v[8];
  uint32_t n = 0, bad;
  do {
    bad = 0;
#pragma unroll
    for (int i = 0; i < 8; i++) v[i] = ldcg128(p + i * stride);
#pragma unroll
    for (int i = 0; i < 8; i++) bad |= (v[i].x ^ ep) | (v[i].w ^ ep);
  } while (__any_sync(0xffffffffu, (bad & 3u) != 0u) && ++n < SPIN_MAX);
  float4 s = make_float4(0.f, 0.f, 0.f, 0.f);
#pragma unroll
  for (int i = 0; i < 8; i++) { s.x += __uint_as_float(v[i].x); s.y += __uint_as_float(v[i].y); s.z += __uint_as_float(v[i].z); s.w += __uint_as_float(v[i].w); }
  if (on) *reinterpret_cast<float4*>(dst) = s;
}

__device__ __forceinline__ uint64_t desc2(uint32_t lo, uint32_t hi) { uint64_t d; asm("mov.b64 %0, {%1, %2};" : "=l"(d) : "r"(lo), "r"(hi)); return d; }
template <int H>
__device__ __forceinline__ void qk_issue(float (&s)[32], const uint32_t (&q)[24], uint32_t m0, uint32_t m1, uint32_t kd) {
  constexpr int J0 = (H == 0) ? 0 : (H == 1) ? 2 : (H == 2) ? 5 : 7;
  wg_rs64k(s, q[H * 6 + 0], q[H * 6 + 1], q[H * 6 + 2], q[H * 6 + 3], desc2(kd + (0x400000u + J0 * 64), 8u), 0);
  wg_rs64k(s, q[H * 6 + 4], q[H * 6 + 5], m0, m1, desc2(kd + (((10 - J0) * 64u << 16) + (J0 + 2) * 64), 8u), 1);
}
template <int H, int FIRST>
__device__ __forceinline__ void pv_issue(float (&o)[12], const uint32_t (&p)[16], uint32_t kd) {
  if (FIRST && H == 3) return;
#pragma unroll
  for (int i = 0; i < 4; i++)
    wg_rs24(o, p[4 * i], p[4 * i + 1], p[4 * i + 2], p[4 * i + 3], desc2(kd + (0x80000u + 640 + 3 * H * 64 + i * 16), 64u), i || !FIRST);
}
template <int KIND>
__device__ __forceinline__ void sm_exp(const float (&s)[32], uint32_t (&p)[16], const uint32_t (&nk)[8], int w) {
#define EXU(i) pack2(ex2(s[2 * (i)]), ex2(s[2 * (i) + 1]))
  if (KIND == 0) {
#pragma unroll
    for (int i = 0; i < 16; i++) p[i] = EXU(i);
  } else {
#pragma unroll
    for (int u = 1; u < 4; u++) {
      const int i0 = KIND == 1 ? 2 * u : 15 - 2 * u, i1 = KIND == 1 ? 17 - 2 * u : 2 * u - 2;
      const uint32_t e = pack2(ex2(w >= u ? s[2 * i0] : s[2 * i1]), ex2(w >= u ? s[2 * i0 + 1] : s[2 * i1 + 1]));
      p[i0] = e & (KIND == 1 ? ~nk[i0 >> 1] : nk[i0 >> 1]);
      p[i1] = e & (KIND == 1 ? ~nk[i1 >> 1] : nk[i1 >> 1]);
    }
    if (KIND == 1) {
      p[0] = EXU(0) & ~nk[0];
      p[9] = EXU(9) & ~nk[4];
    } else {
      p[6] = EXU(6) & nk[3];
      p[15] = EXU(15) & nk[7];
    }
#pragma unroll
    for (int t = 0; t < 4; t++) {
      p[2 * t + (KIND == 1 ? 1 : 8)] = EXU(2 * t + (KIND == 1 ? 1 : 8));
      p[2 * t + (KIND == 1 ? 8 : 1)] = 0u;
    }
  }
#pragma unroll
  for (int i = 0; i < 16; i++) asm volatile("" : "+r"(p[i])::"memory");
}
__device__ __forceinline__ void mma16816(float* d, uint32_t a0, uint32_t a1, uint32_t a2, uint32_t a3, uint32_t b0, uint32_t b1) {
  asm volatile("mma.sync.aligned.m16n8k16.row.col.f32.bf16.bf16.f32 {%0,%1,%2,%3}, {%4,%5,%6,%7}, {%8,%9}, {%0,%1,%2,%3};"
               : "+f"(d[0]), "+f"(d[1]), "+f"(d[2]), "+f"(d[3]) : "r"(a0), "r"(a1), "r"(a2), "r"(a3), "r"(b0), "r"(b1));
}
template <int H>
__device__ __forceinline__ void safe_head(float (&o)[12], const uint32_t (&q)[24], const uint8_t* kv, uint32_t seq, int nit, int d0, int d1, int tq, uint32_t tag) {
  constexpr int J0 = (H == 0) ? 0 : (H == 1) ? 2 : (H == 2) ? 5 : 7;
  float m0 = -INFINITY, m1 = -INFINITY;
#pragma unroll
  for (int i = 0; i < 12; i++) o[i] = 0.f;
#pragma unroll 1
  for (int st = 0; st < 4 * nit; st++) {
    const uint8_t* a = kv + (size_t)((seq >> (st & 28)) & 15) * (8 * KVB) + (st & 3) * 256;
    uint32_t b[12], bad, n = 0;
    do {
      bad = 0;
#pragma unroll
      for (int i = 0; i < 12; i++) {
        b[i] = ldcg32(a + ((i < 6 ? J0 : 7 + 3 * H) + (i >> 1)) * 1024 + (i & 1) * 128);
        bad |= b[i] ^ tag;
      }
    } while (__any_sync(0xffffffffu, tq == 1 && (bad & TAGM) != 0u) && ++n < SPIN_MAX);
    float s[8];
#pragma unroll
    for (int i = 0; i < 8; i++) s[i] = 0.f;
#pragma unroll
    for (int t = 0; t < 2; t++) {
      mma16816(&s[4 * t], q[6 * H], q[6 * H + 1], q[6 * H + 2], q[6 * H + 3], b[t], b[2 + t]);
      mma16816(&s[4 * t], q[6 * H + 4], q[6 * H + 5], 0u, 0u, b[4 + t], 0u);
    }
    if (st < 4 || st >= 16) {
#pragma unroll
      for (int i = 0; i < 8; i++)
        if (((st & 3) * 16 + (i >> 2) * 8 + (i & 1) <= ((i & 2) ? d1 : d0)) != (st < 4)) s[i] = -INFINITY;
    }
    float n0 = fmaxf(fmaxf(s[0], s[1]), fmaxf(s[4], s[5])), n1 = fmaxf(fmaxf(s[2], s[3]), fmaxf(s[6], s[7]));
    n0 = fmaxf(n0, __shfl_xor_sync(0xffffffffu, n0, 1));
    n1 = fmaxf(n1, __shfl_xor_sync(0xffffffffu, n1, 1));
    n0 = fmaxf(m0, fmaxf(n0, __shfl_xor_sync(0xffffffffu, n0, 2)));
    n1 = fmaxf(m1, fmaxf(n1, __shfl_xor_sync(0xffffffffu, n1, 2)));
    const float al0 = ex2(m0 - n0), al1 = ex2(m1 - n1);
    m0 = n0;
    m1 = n1;
    const uint32_t p0 = pack2(ex2(s[0] - n0), ex2(s[1] - n0)), p1 = pack2(ex2(s[2] - n1), ex2(s[3] - n1));
    const uint32_t p2 = pack2(ex2(s[4] - n0), ex2(s[5] - n0)), p3 = pack2(ex2(s[6] - n1), ex2(s[7] - n1));
#pragma unroll
    for (int i = 6; i < 12; i++) asm volatile("movmatrix.sync.aligned.m8n8.trans.b16 %0, %0;" : "+r"(b[i]));
#pragma unroll
    for (int t = 0; t < 3; t++) {
      o[4 * t] *= al0; o[4 * t + 1] *= al0; o[4 * t + 2] *= al1; o[4 * t + 3] *= al1;
      mma16816(&o[4 * t], p0, p1, p2, p3, b[6 + 2 * t], b[7 + 2 * t]);
    }
  }
}
#define ATT_STEP(KIND, HQ, sq, kq, HP, op, pp, kv, sc, pc, W) do { \
  WG_FENCE(); qk_issue<HQ>(sq, q, qm[2 * HQ], qm[2 * HQ + 1], kq); WG_COMMIT(); WG_WAIT(1); pv_issue<HP, KIND == 1>(op, pp, kv); WG_COMMIT(); \
  sm_exp<KIND>(sc, pc, nk, w); WG_WAIT(W); reg_fence(sq); } while (0)
__device__ __forceinline__ uint32_t bmul2(uint32_t a, uint32_t b) { uint32_t d; asm("mul.rn.bf16x2 %0, %1, %2;" : "=r"(d) : "r"(a), "r"(b)); return d; }
__device__ __forceinline__ uint32_t badd2(uint32_t a, uint32_t b) { uint32_t d; asm("add.rn.bf16x2 %0, %1, %2;" : "=r"(d) : "r"(a), "r"(b)); return d; }
__device__ __forceinline__ uint32_t bfma2(uint32_t a, uint32_t b, uint32_t c) { uint32_t d; asm("fma.rn.bf16x2 %0, %1, %2, %3;" : "=r"(d) : "r"(a), "r"(b), "r"(c)); return d; }

__global__ void __cluster_dims__(2, 1, 1) __launch_bounds__(384, 1) fused_block_kernel(const __grid_constant__ Params P) {
  extern __shared__ __align__(1024) uint8_t smem[];
  const uint32_t sb = s2u(smem);
  const int tid = threadIdx.x, lane = tid & 31, warp = __shfl_sync(0xffffffffu, tid >> 5, 0);
  const uint32_t bars = sb + OFF_MISC;
#define BAR(i) (bars + 8u * (uint32_t)(i))
#define TP(i)
  if (tid == 288) {
#pragma unroll
    for (int u = 0; u < 6; u++) mbar_init(BAR(u), 1);
    asm volatile("fence.mbarrier_init.release.cluster;" ::: "memory");
  }
  __syncwarp();
  asm volatile("barrier.cluster.arrive.relaxed.aligned;" ::: "memory");
  TP(0);
  const uint32_t rank = blockIdx.x & 1;
  const uint32_t mp = P.map[blockIdx.x >> 3] >> ((blockIdx.x & 6) * 4);
  const int c = mp & 7, rb = (int)(((mp >> 2) & 14) + rank);
  const int tile = rb * 8 + c;
  const int odd = c & 1;
  const int mainch = (c >> 1) * 5 + (odd ? 3 : 0), leftch = (c >> 1) * 10 + (odd ? 5 : 4);
  const int kb0 = (5 * (rb >> 1)) >> 2;
  if (lane == 0 && (warp >> 1) != 4) {
    const int j = warp < 8 ? warp + 3 : warp - 9;
    const int cnt = (int)(0x4a108208108421ull >> (5 * j)) & 31;
#pragma unroll
    for (int u = 0; u < 6; u++) mbar_init(BAR(j * 6 + u), cnt);
    asm volatile("fence.mbarrier_init.release.cluster;" ::: "memory");
  }
  __syncwarp();
  TP(1);
  if (warp >= 8) asm volatile("setmaxnreg.dec.sync.aligned.u32 56;");
  TP(2);
  if (warp > 8) {
    asm volatile("bar.arrive 1, 384;" ::: "memory");
    if (lane == 0) {
      if (warp == 9) {
        mbar_expect(BAR(B_QFULL), QST);
        tma2d(sb, &P.mX, kb0 * 64, rb * 128, BAR(B_QFULL));
      } else {
        asm volatile("prefetch.tensormap [%0];" ::"l"(warp == 10 ? &P.mWqM : &P.mWqL) : "memory");
      }
    }
    __syncwarp();
    asm volatile("bar.sync 2, 128;" ::: "memory");
  } else {
    asm volatile("bar.sync 1, 384;" ::: "memory");
  }
  TP(3);
  if (tid < 208) {
    const uint8_t* pp = tid < 192 ? reinterpret_cast<const uint8_t*>(P.wqkv) + (size_t)(kb0 * 64 + (int)rank * 32 + (tid & 31)) * 3840 + (tid >> 6) * 1280 + c * 160 + (tid & 32) * 4
                                  : reinterpret_cast<const uint8_t*>(P.x) + (size_t)(rb * 128 + c * 16 + tid - 192) * 1280 + kb0 * 128;
    l2_prefetch(pp);
  }
  if (warp == 8) {
    asm volatile("bar.arrive 2, 128;\nbarrier.cluster.wait.acquire.aligned;" ::: "memory");
    TP(4);
    if (lane == 0) {
#pragma unroll 1
      for (int kt = 0; kt < 4; kt++) {
        const uint32_t a = sb + kt * QST, fb = BAR(B_QFULL + kt);
        const int k0 = (kb0 + kt < 10 ? kb0 + kt : kb0 + kt - 10) * 64;
        if (kt) mbar_expect(fb, QST);
        tma4d_mc(a + 16384 + rank * 12288, &P.mWqM, 0, k0 + rank * 32, mainch, 0, fb);
        tma4d_mc(a + 40960 + rank * 3072, &P.mWqL, 0, k0 + rank * 32, leftch, 0, fb);
        if (kt) tma2d(a, &P.mX, k0, rb * 128, fb);
        if (kt == 0) TP(5);
      }
      mbar_expect(BAR(B_XROW), 20480);
      bulk_load(sb + OFF_XROW, reinterpret_cast<const uint8_t*>(P.x) + (size_t)(rb * 128 + c * 16) * 1280, 20480, BAR(B_XROW));
    } else if (lane < 4) mbar_arrive(BAR(B_XROW));
    __syncwarp();
    STAMPW(9);
  }
  const int sc = (27 * c + 3) >> 2;

  if (warp >= 8) {
    const uint32_t epoch = __shfl_sync(0xffffffffu, ldcg32(&g_epoch[tile * 32 + lane]), 0) + 1u;
    const uint32_t ep = epoch & 3u, tag = (epoch & 1u) | ((epoch & 2u) << 15);
    if (warp == 8) {
      if (lane == 0) {
#pragma unroll 1
        for (int kt = 4; kt < 10; kt++) {
          const int st = kt & 3;
          mbar_wait(BAR(B_QEMPTY + st), ((kt >> 2) - 1) & 1);
          const uint32_t a = sb + st * QST, fb = BAR(B_QFULL + st);
          const int k0 = (kb0 + kt < 10 ? kb0 + kt : kb0 + kt - 10) * 64;
          mbar_expect(fb, QST);
          tma4d_mc(a + 16384 + rank * 12288, &P.mWqM, 0, k0 + rank * 32, mainch, 0, fb);
          tma4d_mc(a + 40960 + rank * 3072, &P.mWqL, 0, k0 + rank * 32, leftch, 0, fb);
          tma2d(a, &P.mX, k0, rb * 128, fb);
        }
        l2_prefetch_bulk(reinterpret_cast<const uint8_t*>(P.wo) + tile * 6400, 6400);
        l2_prefetch_bulk(reinterpret_cast<const uint8_t*>(P.w1) + tile * 17280, 17280);
        l2_prefetch_bulk(reinterpret_cast<const uint8_t*>(P.w2) + tile * 17280, 17280);
        const CUtensorMap* mW1 = rank ? &P.mW1b : &P.mW1a;
        asm volatile("prefetch.tensormap [%0];" ::"l"(&P.mWo) : "memory");
        asm volatile("prefetch.tensormap [%0];" ::"l"(mW1) : "memory");
        asm volatile("prefetch.tensormap [%0];" ::"l"(&P.mW2) : "memory");
        mbar_wait(BAR(B_QEMPTY + 1), 0);
        if (rb) mbar_wait(BAR(B_KVFULL + 3), 0);
        mbar_expect(BAR(B_WOB), 89600);
#pragma unroll 1
        for (int i = 0; i < 4 - (int)rank; i++) {
          const int pos = rank * 4 + i;
          tma3d_mc(sb + OFF_WOB + pos * 12800, &P.mWo, 0, ((c + pos) & 7) * 80, c * 5, BAR(B_WOB));
        }
#pragma unroll 1
        for (int s = 0; s < 8; s++) {
          if (s == 0) {
            mbar_wait(BAR(B_ATT2), 0);
            mbar_expect(BAR(B_WOB7), 12800);
            if (rank) tma3d_mc(sb + OFF_WOB + 7 * 12800, &P.mWo, 0, ((c + 7) & 7) * 80, c * 5, BAR(B_WOB7));
            mbar_wait(BAR(B_OL1), 0);
          } else if (s == 1) mbar_wait(BAR(B_ATT4), 0);
          else if (s == 3 || s == 4) mbar_wait(BAR(s == 3 ? B_WODP : B_WODP2), 0);
          else if (s >= 5) mbar_wait(BAR(B_BEMPTY + s - 5), 0);
          const uint32_t fb = BAR(B_BFULL + s);
          mbar_expect(fb, 35840);
          tma3d_mc(sb + w1b_addr(s) + rank * 20480, mW1, 0, ((c + s) & 7) * 80, sc + rank * 4, fb);
        }
#pragma unroll 1
        for (int s = 0; s < 5; s++) {
          mbar_wait(s < 3 ? BAR(B_BEMPTY + 4 + s) : BAR(B_W2E + s - 3), 0);
          const uint32_t dst = sb + (s < 3 ? s : s - 3) * W2SLOT + rank * 14336, fb = BAR(B_W2FULL + s);
          const int bx0 = (c + 2 * s) % 10, bx1 = (c + 2 * s + 1) % 10;
          mbar_expect(fb, W2SLOT);
          tma2d_mc(dst, &P.mW2, bx0 * 64, sc * 32 + rank * 112, fb);
          tma2d_mc(dst + 28672, &P.mW2, bx1 * 64, sc * 32 + rank * 112, fb);
        }
      }
      __syncwarp();
    } else {
      if (warp == 11) {
        mbar_wait(BAR(B_PRE), 0);
        if (lane < 30) {
          float4 a = make_float4(0.f, 0.f, 0.f, 0.f);
#pragma unroll 4
          for (int i = 0; i < 16; i++) {
            const float4 v = *reinterpret_cast<const float4*>(smem + OFF_PRE + i * 512 + lane * 16);
            a.x += v.x; a.y += v.y; a.z += v.z; a.w += v.w;
          }
          *reinterpret_cast<float4*>(&g_csq[((rb >> 1) * 8 + c) * 240 + rank * 120 + lane * 4]) = make_float4(tag32(a.x, ep), tag32(a.y, ep), tag32(a.z, ep), tag32(a.w, ep));
        }
        __syncwarp();
        STAMPW(0);
      }
      mbar_wait(BAR(B_XROW), 0);
      if (warp == 9) STAMPW(8);
      {
        float s3[3] = {0.f, 0.f, 0.f}, m3[3] = {0.f, 0.f, 0.f}, sh3 = 0.f;
#pragma unroll 1
        for (int p = 0; p < 3 - (warp == 11); p++) {
          const uint32_t xb = sb + OFF_XROW + ((warp - 9 + p * 3) * 2 + (lane >> 4)) * 1280;
          uint32_t u[20], u0;
          asm volatile("ld.shared.u32 %0, [%1];" : "=r"(u0) : "r"(xb) : "memory");
#pragma unroll
          for (int i = 0; i < 5; i++)
            asm volatile("ld.shared.v4.u32 {%0,%1,%2,%3}, [%4];" : "=r"(u[4 * i]), "=r"(u[4 * i + 1]), "=r"(u[4 * i + 2]), "=r"(u[4 * i + 3]) : "r"(xb + (lane & 15) * 16 + i * 256) : "memory");
          const float sh = bf_lo(u0);
          float su[2] = {0.f, 0.f}, sq[2] = {0.f, 0.f};
#pragma unroll
          for (int j = 0; j < 20; j++) {
            const float d0 = bf_lo(u[j]) - sh, d1 = bf_hi(u[j]) - sh;
            su[j & 1] += d0 + d1;
            sq[j & 1] = fmaf(d1, d1, fmaf(d0, d0, sq[j & 1]));
          }
#pragma unroll
          for (int i = 0; i < 3; i++)
            if (p == i) { s3[i] = su[0] + su[1]; m3[i] = sq[0] + sq[1]; }
          if (p == (lane & 15)) sh3 = sh;
        }
#pragma unroll
        for (int o = 8; o; o >>= 1)
#pragma unroll
          for (int i = 0; i < 3; i++) {
            s3[i] += __shfl_xor_sync(0xffffffffu, s3[i], o);
            m3[i] += __shfl_xor_sync(0xffffffffu, m3[i], o);
          }
        const int p = lane & 15;
        const float s = (p == 0 ? s3[0] : p == 1 ? s3[1] : s3[2]) * (1.f / 640.f), m2 = (p == 0 ? m3[0] : p == 1 ? m3[1] : m3[2]) * (1.f / 640.f);
        if (p < 3 - (warp == 11))
          g_xstat[rb * 128 + c * 16 + (warp - 9 + p * 3) * 2 + (lane >> 4)] = make_float2(sh3 + s, tag32(rsqrtf(fmaxf(fmaf(-s, s, m2), 0.f) + 1e-5f), ep));
      }
      if (warp == 9) STAMPW(17);
      if (warp != 11) {
        if (warp == 10) {
          mbar_wait(BAR(B_QEMPTY + 3), 0);
          uint4 v0, v1;
          uint32_t n = 0;
          do {
            v0 = ldcg128(&g_xstat[rb * 128 + lane * 2]);
            v1 = ldcg128(&g_xstat[rb * 128 + 64 + lane * 2]);
          } while (__any_sync(0xffffffffu, (((v0.y ^ ep) | (v0.w ^ ep) | (v1.y ^ ep) | (v1.w ^ ep)) & 3u) != 0u) && ++n < SPIN_MAX);
          *reinterpret_cast<uint4*>(smem + OFF_XST + lane * 16) = v0;
          *reinterpret_cast<uint4*>(smem + OFF_XST + 512 + lane * 16) = v1;
          __syncwarp();
          if (lane < 2) mbar_arrive(BAR(B_STAT));
          STAMPW(18);
        }
        if (warp == 10 && lane == 0) {
#pragma unroll 1
          for (int i = 0; i < 1 + KVP; i++) {
            if (i < 2) mbar_wait(BAR(B_KVOWN + i), 0);
            const uint32_t off = i ? (uint32_t)(i - 1) * (KVB / KVP) + KVB : 0u;
            asm volatile("cp.async.bulk.wait_group.read 0;\ncp.async.bulk.global.shared::cta.bulk_group [%0], [%1], %2;\ncp.async.bulk.commit_group;"
                         ::"l"(g_kv + (size_t)(rb * 16 + c) * KVB + (i ? 7 * KVB + off : 0u)), "r"(sb + kv_addr(4) + off), "r"(i ? KVB / KVP : KVB) : "memory");
          }
          asm volatile("cp.async.bulk.wait_group.read 0;" ::: "memory");
          mbar_arrive_pair(BAR(B_ATT2));
          STAMPW(6);
        }
        __syncwarp();
      }
      if (warp != 10) {
        const int u = (warp - 9) * 16 + lane;
        mbar_wait(BAR(B_QEMPTY + 3), 0);
        gather8(smem + OFF_CS + u * 16, g_csq + c * 240 + min(u, 59) * 4, 1920, ep, u < 60);
        __syncwarp();
        if (lane == 0) mbar_arrive(BAR(B_STAT));
        if (warp == 9) STAMPW(16);
        mbar_wait(BAR(B_QEMPTY + 1), 1);
      }
      if (warp == 9) STAMPW(19);
#pragma unroll 1
      for (int bi = warp == 9 ? 2 : warp == 10 ? 3 : 1; bi >= 0; bi -= (warp == 9 ? 2 : 4)) {
        const int blk = 2 * rb - 4 + bi;
        if (blk < 0) continue;
        const uint8_t* src = g_kv + (size_t)(blk * 8 + c) * KVB;
        const uint32_t dst = sb + kv_addr(bi);
        uint32_t n = 0, ph = 0;
        while (!__all_sync(0xffffffffu, ((ldcg32(src + lane * 704 + 692) ^ tag) & TAGM) == 0u) && ++n < SPIN_MAX) {}
        if (warp == 9 && bi == 2) STAMPW(3);
        mbar_wait(BAR(B_QEMPTY + 1), 0);
        while (true) {
          if (lane == 0) {
            mbar_expect(BAR(B_KVLAND + bi), KVB);
            bulk_load(dst, src, KVB, BAR(B_KVLAND + bi));
          }
          mbar_wait(BAR(B_KVLAND + bi), ph);
          ph ^= 1u;
          uint32_t bad = 0;
#pragma unroll 11
          for (int i = 0; i < 44; i++) {
            uint32_t v;
            asm volatile("ld.shared.u32 %0, [%1];" : "=r"(v) : "r"(dst + (i * 32 + lane) * 16 + 4) : "memory");
            bad |= v ^ tag;
          }
          if (!__any_sync(0xffffffffu, (bad & TAGM) != 0u) || ++n >= SPIN_MAX) break;
        }
        if (lane == 0) {
          mbar_arrive(BAR(B_KVFULL + bi));
        }
        if (warp == 9 && bi == 2) STAMPW(5);
        if (warp == 10) STAMPW(7);
      }
      __syncwarp();
      asm volatile("barrier.cluster.wait.acquire.aligned;" ::: "memory");
      if (warp == 10) {
        const int l16 = lane & 15, col = sc * 32 + (int)rank * 112 + l16 * 8;
        const uint8_t* wb = reinterpret_cast<const uint8_t*>(P.w1) + (size_t)((rb >> 1) * 80 + (lane >> 4) * 40) * 3456 + (size_t)col * 2;
        float acc[8];
#pragma unroll
        for (int i = 0; i < 8; i++) acc[i] = 0.f;
        if (l16 < 14 && col < 1728) {
#pragma unroll 1
          for (int i = 0; i < 40; i += 8) {
            uint4 v[8];
#pragma unroll
            for (int u = 0; u < 8; u++) v[u] = __ldg(reinterpret_cast<const uint4*>(wb + (size_t)(i + u) * 3456));
#pragma unroll
            for (int u = 0; u < 8; u++) {
              acc[0] += bf_lo(v[u].x); acc[1] += bf_hi(v[u].x); acc[2] += bf_lo(v[u].y); acc[3] += bf_hi(v[u].y);
              acc[4] += bf_lo(v[u].z); acc[5] += bf_hi(v[u].z); acc[6] += bf_lo(v[u].w); acc[7] += bf_hi(v[u].w);
            }
          }
        }
        __syncwarp();
#pragma unroll
        for (int i = 0; i < 4; i++) {
          const float o = __shfl_xor_sync(0xffffffffu, lane < 16 ? acc[4 + i] : acc[i], 16);
          acc[i] = tag32((lane < 16 ? acc[i] : acc[4 + i]) + o, ep);
        }
        if (l16 < 14) *reinterpret_cast<float4*>(&g_cs1[((rb >> 1) * 8 + c) * 224 + rank * 112 + l16 * 8 + (lane >> 4) * 4]) = make_float4(acc[0], acc[1], acc[2], acc[3]);
        STAMPW(4);
      } else if (warp == 9) {
#pragma unroll 1
        for (int r = 1; r >= 0; r--) {
          const int cc = (c + 1 + (lane >> 2)) & 7;
          const uint32_t* hp = &g_hint[((rb * 2 + r) * 8 + cc) * HS + (lane & 3)];
          const uint32_t fb = BAR(r ? B_QFULL : B_KVFULL);
          const uint32_t dst = sb + (r ? 102400u : lane < 12 ? 179200u : 107520u) + (lane >> 2) * 10240;
          mbar_wait(BAR(r ? B_ATT2 : B_ATTL), 0);
          mbar_wait(BAR(B_ATT3), 0);
          if (lane < 4) mbar_expect(fb + lane * 8, lane < 3 ? 20480 : 10240);
          uint32_t n = 0, todo = 0x1111111u;
          while (todo) {
            uint32_t ok = __ballot_sync(0xffffffffu, ldcg32(hp) == tag || n >= SPIN_MAX);
            ok &= ok >> 1;
            ok &= (ok >> 2) & todo;
            if (r == 0 && !mbar_test(BAR(B_OL1L))) ok &= 0xfffu;
            if ((ok >> lane) & 1u) bulk_load(dst, g_o + (size_t)(rb * 16 + r * 8 + cc) * 10240, 10240, fb + (lane >> 3) * 8);
            todo &= ~ok;
            if (++n > 2 * SPIN_MAX) break;
          }
        }
      } else if (warp == 11) {
        mbar_wait(BAR(B_ATT3), 0);
#pragma unroll 1
        for (int u = lane; u < 64; u += 32) gather8(smem + OFF_XS + u * 16, g_cs1 + c * 224 + min(u, 55) * 4, 1792, ep, u < 56);
        __syncwarp();
        if (lane == 0) mbar_arrive(BAR(B_CS1));
        STAMPW(1);
      }
    }
    if (warp == 9 || warp == 10) {
      const int r = warp - 9;
      uint32_t* fl = &g_oflag[(rb * 2 + r) * 8];
      mbar_wait(BAR(B_HST + r), 0);
      if (lane == 0) {
        asm volatile("cp.async.bulk.tensor.2d.global.shared::cta.bulk_group [%0, {%2, %3}], [%1];\ncp.async.bulk.commit_group;\ncp.async.bulk.wait_group 0;"
                     ::"l"(&P.mOutH), "r"(sb + OFF_HST + r * 10240), "r"(c * 80), "r"(rb * 128 + r * 64) : "memory");
        asm volatile("fence.proxy.async.global;\nst.release.gpu.global.u32 [%0], %1;" ::"l"(fl + c), "r"(epoch) : "memory");
      }
      __syncwarp();
      uint32_t n = 0;
      while (!__all_sync(0xffffffffu, ld_flag(fl + (lane & 7)) == epoch) && ++n < SPIN_MAX) {}
      if (lane == 0) mbar_arrive(BAR(B_OUTOK + r));
      STAMPW(2);
    } else if (warp == 11) {
      st_flag(&g_epoch[tile * 32 + lane], epoch);
    }
  } else {
    const int r = warp >> 2, w = warp & 3, gq = lane >> 2, tq = lane & 3;
    asm volatile("setmaxnreg.inc.sync.aligned.u32 224;");
    STAMP(4);
    uint32_t ep = ldcg32(&g_epoch[tile * 32 + lane]);
    const int b = rb * 2 + r;
    const int row0 = w * 8 + gq, row1 = 56 - w * 8 + gq;
    const int rowm = ((lane & 8) ? 56 - w * 8 : w * 8) + (lane & 7);
    uint32_t q[24], qm[8], tag;
    STAMP(0);
    {
      float accQ[32], accK[64], accL[24];
      uint32_t fa[16], fb[16];
      const uint32_t xa = sb + (uint32_t)(r * 64 + rowm) * 128u + (uint32_t)(((lane >> 4) ^ lane) & 7) * 16u;
#define QKV_DM(kt, k) (mkdesc(sb + ((kt) & 3) * QST + 16384, desc_hi(2048, 512, 2)) + ((k) >> 1) * 768 + ((k) & 1) * 64)
#define QKV_DL(kt, k) (mkdesc(sb + ((kt) & 3) * QST + 40960, desc_hi(1024, 256, 3)) + ((k) >> 1) * 192 + ((k) & 1) * 32)
#define QKV_STEP(f, kt, WQ, REL) do { \
        mbar_wait(BAR(B_QFULL + ((kt) & 3)), ((kt) >> 2) & 1); \
        _Pragma("unroll") for (int k = 0; k < 4; k++) ldsm4(&f[4 * k], (xa ^ (k * 32)) + ((kt) & 3) * QST); \
        WG_FENCE(); \
        _Pragma("unroll") for (int k = 0; k < 4; k++) { \
          wg_rs48(accL, f[4 * k], f[4 * k + 1], f[4 * k + 2], f[4 * k + 3], QKV_DL(kt, k), (kt) | k); \
          if (WQ) wg_rs64(accQ, f[4 * k], f[4 * k + 1], f[4 * k + 2], f[4 * k + 3], QKV_DM(kt, k), (kt) | k); \
          wg_rs128(accK, f[4 * k], f[4 * k + 1], f[4 * k + 2], f[4 * k + 3], QKV_DM(kt, k) + 256, (kt) | k); \
          if (k == 0 || k == 3) WG_COMMIT(); \
          if (k == 0) { WG_WAIT(1); REL; } \
        } } while (0)
#define Q_STEP(f, kt) do { \
        _Pragma("unroll") for (int k = 0; k < 4; k++) wg_rs64(accQ, f[4 * k], f[4 * k + 1], f[4 * k + 2], f[4 * k + 3], QKV_DM(kt, k), 1); \
        WG_COMMIT(); } while (0)
#pragma unroll 1
      for (int kt = 0; kt < 6; kt += 2) {
        QKV_STEP(fa, kt, 1, if (kt && lane == 0) mbar_arrive_pair(BAR(B_QEMPTY + ((kt - 1) & 3))));
        QKV_STEP(fb, kt + 1, 1, if (kt && lane == 0) mbar_arrive_pair(BAR(B_QEMPTY + (kt & 3))));
        if (kt == 0) {
          const int cl = min(lane & 15, 14) + (int)rank * 15, mat = cl / 10, pc = cl - mat * 10 - odd * 2;
          const bool mn = (unsigned)pc < 8u;
          const int pitch = mn ? 64 : 32;
          const uint8_t* wp = smem + (mn ? 16384 + mat * 4096 + (pc >> 2) * 2048 + ((pc ^ (warp >> 1)) & 3) * 16 : 40960 + mat * 1024 + ((pc ^ (warp >> 2)) & 1) * 16);
          float a[8];
#pragma unroll
          for (int i = 0; i < 8; i++) a[i] = 0.f;
#pragma unroll
          for (int u = 0; u < 5; u++) {
            const int kr = (rb >> 1) * 80 - kb0 * 64 + u * 16;
            const uint4 v = *reinterpret_cast<const uint4*>(wp + (kr >> 6) * QST + ((kr & 16) + (lane >> 4) * 8 + warp + (kr & 32) * (mn ? 6 : 3)) * pitch);
            a[0] += bf_lo(v.x); a[1] += bf_hi(v.x); a[2] += bf_lo(v.y); a[3] += bf_hi(v.y);
            a[4] += bf_lo(v.z); a[5] += bf_hi(v.z); a[6] += bf_lo(v.w); a[7] += bf_hi(v.w);
          }
          float4* dst = reinterpret_cast<float4*>(smem + OFF_PRE + warp * 1024 + lane * 32);
          dst[0] = make_float4(a[0], a[1], a[2], a[3]);
          dst[1] = make_float4(a[4], a[5], a[6], a[7]);
          __syncwarp();
          if (lane == 0) {
            mbar_arrive(BAR(B_PRE));
            mbar_arrive_pair(BAR(B_QEMPTY));
          }
          STAMP(5);
        } else if (kt == 4) {
          asm volatile("barrier.cluster.wait.acquire.aligned;" ::: "memory");
        }
      }
      uint32_t fc[16];
      QKV_STEP(fa, 6, 1, if (lane == 0) mbar_arrive_pair(BAR(B_QEMPTY + 1)));
      QKV_STEP(fb, 7, 0, if (lane == 0) mbar_arrive(BAR(B_Q23)));
      if (r) mbar_wait(BAR(B_XROW), 1);
      QKV_STEP(fa, 8, 0, );
      QKV_STEP(fc, 9, 0, if (!r && lane == 0) mbar_arrive(BAR(B_XROW)));
      ep = (__shfl_sync(0xffffffffu, ep, 0) + 1u) & 3u;
      tag = (ep & 1u) | ((ep & 2u) << 15);
      mbar_wait(BAR(B_STAT), 0);
      const float2 s0 = lds64f(sb + OFF_XST + (r * 64 + row0) * 8), s1 = lds64f(sb + OFF_XST + (r * 64 + row1) * 8);
      mbar_wait(BAR(B_Q23), 0);
      WG_WAIT(0);
      reg_fence(accK); reg_fence(accL);
      STAMP(2);
      const uint32_t km = tq == 1 ? ~TAGM : 0xffffffffu, kt1 = tq == 1 ? tag : 0u;
      const uint32_t csb = sb + OFF_CS + tq * 8;
      const uint32_t kvo = sb + kv_addr(4 + r) + (uint32_t)rowm * 16u + (uint32_t)(lane >> 4) * 1024u;
      const float qs = 0.22360679774997896f * 1.4426950408889634f;
      const bool lo = tq < 2;
      uint32_t qj[20], kj[20];
#define QKV_OUT(mat, ODD) do { \
        const float r0 = mat == 0 ? s0.y * qs : s0.y, r1 = mat == 0 ? s1.y * qs : s1.y; \
        const float n0 = -s0.x * r0, n1 = -s1.x * r1; \
        _Pragma("unroll") for (int t = 0; t < 10; t++) { \
          const float* a = t >= 8 ? &accL[(mat * 2 + t - 8) * 4] : mat ? &accK[(mat * 8 - 8 + t) * 4] : &accQ[t * 4]; \
          const int u = (t + 2 * ODD) % 10; \
          const float2 cs = lds64f(csb + mat * 320 + u * 32); \
          qj[2 * u] = pack2(fmaf(a[0], r0, cs.x * n0), fmaf(a[1], r0, cs.y * n0)); \
          qj[2 * u + 1] = pack2(fmaf(a[2], r1, cs.x * n1), fmaf(a[3], r1, cs.y * n1)); \
        } } while (0)
#define KV_OUT(ODD) do { \
        QKV_OUT(1, ODD); \
        _Pragma("unroll") for (int i = 0; i < 20; i++) kj[i] = (qj[i] & km) | kt1; \
        _Pragma("unroll") for (int t = 0; t < 10; t += 2) stsm4(kvo + t * 1024, kj[2 * t], kj[2 * t + 1], kj[2 * t + 2], kj[2 * t + 3]); \
        QKV_OUT(2, ODD); \
          \
        const uint32_t one = (tq & 1) ? 0u : 0x3f80u; \
        uint32_t vv[24]; \
        _Pragma("unroll") for (int hp = 0; hp < 2; hp++) { \
          const int j = hp * 10; \
          _Pragma("unroll") for (int i = 0; i < 4; i++) { vv[hp * 12 + i] = qj[j + i]; vv[hp * 12 + 8 + i] = qj[j + 6 + i]; } \
          vv[hp * 12 + 4] = lo ? qj[j + 4] : one; vv[hp * 12 + 5] = lo ? qj[j + 5] : one; \
          vv[hp * 12 + 6] = lo ? one : qj[j + 4]; vv[hp * 12 + 7] = lo ? one : qj[j + 5]; \
        } \
        _Pragma("unroll") for (int i = 0; i < 24; i++) vv[i] = (vv[i] & km) | kt1; \
        _Pragma("unroll") for (int t = 0; t < 6; t++) stsm4(kvo + 10240 + t * 2048, vv[4 * t], vv[4 * t + 1], vv[4 * t + 2], vv[4 * t + 3]); \
      } while (0)
      if (odd) KV_OUT(1);
      else KV_OUT(0);
      fence_async_smem();
      __syncwarp();
      if (lane == 0) mbar_arrive(BAR(B_KVOWN + r));
      mbar_wait(BAR(B_STAT), 0);
      WG_FENCE();
      Q_STEP(fb, 7);
      Q_STEP(fa, 8);
      Q_STEP(fc, 9);
      WG_WAIT(0);
      reg_fence(accQ);
      if (lane == 0) mbar_arrive_pair(BAR(B_QEMPTY + 1));
      STAMP(1);
      if (odd) QKV_OUT(0, 1);
      else QKV_OUT(0, 0);
#pragma unroll
      for (int hp = 0; hp < 2; hp++) {
        const int j = hp * 10;
        q[hp * 12 + 0] = qj[j + 0]; q[hp * 12 + 1] = qj[j + 1]; q[hp * 12 + 2] = qj[j + 2]; q[hp * 12 + 3] = qj[j + 3];
        q[hp * 12 + 4] = lo ? qj[j + 4] : 0u; q[hp * 12 + 5] = lo ? qj[j + 5] : 0u;
        q[hp * 12 + 6] = lo ? 0u : qj[j + 4]; q[hp * 12 + 7] = lo ? 0u : qj[j + 5];
        q[hp * 12 + 8] = qj[j + 6]; q[hp * 12 + 9] = qj[j + 7]; q[hp * 12 + 10] = qj[j + 8]; q[hp * 12 + 11] = qj[j + 9];
      }
#pragma unroll
      for (int h = 0; h < 4; h++) {
        const int j = (h >> 1) * 10 + (h & 1) * 4;
        const uint32_t d0 = bfma2(q[6 * h + 4], kj[j + 4], bfma2(q[6 * h + 2], kj[j + 2], bmul2(q[6 * h], kj[j])));
        const uint32_t d1 = bfma2(q[6 * h + 5], kj[j + 5], bfma2(q[6 * h + 3], kj[j + 3], bmul2(q[6 * h + 1], kj[j + 1])));
        uint32_t u = badd2(__byte_perm(d0, d1, 0x5410), __byte_perm(d0, d1, 0x7632));
        u = badd2(u, __shfl_xor_sync(0xffffffffu, u, 1));
        u = badd2(u, __shfl_xor_sync(0xffffffffu, u, 2));
        u = tq == 2 ? u ^ 0x80008000u : 0u;
        qm[2 * h] = u & 0xffffu;
        qm[2 * h + 1] = u >> 16;
        asm volatile("" : "+r"(qm[2 * h]), "+r"(qm[2 * h + 1]));
      }
    }
    STAMP(3);
    uint32_t x0[20], xr[20];
    {
      float o0[12], o1[12], o2[12], o3[12];
#pragma unroll
      for (int i = 0; i < 12; i++) o3[i] = 0.f;
      reg_fence(o3);
      float s0[32], s1[32];
      uint32_t p0[16], p1[16];
      uint32_t nk[8];
#pragma unroll
      for (int t = 0; t < 8; t++) asm("shl.b32 %0, %1, %2;" : "=r"(nk[t]) : "r"(0xffffffffu), "r"(max(((t < 4 ? row0 : row1) - 2 * tq - 8 * t + 1) * 16, 0)));
      const uint32_t seq = r ? 0x13245u : 0x01324u;
      const int nit = rb >= 2 ? 5 : 2 * rb + 1 + r;
      mbar_wait(BAR(B_KVOWN + r), 0);
      uint32_t kb = ((sb + kv_addr(4 + r)) & 0x3FFFF) >> 4, kp = kb;
      WG_FENCE();
      qk_issue<0>(s0, q, qm[0], qm[1], kb);
      WG_COMMIT();
      WG_WAIT(0);
      reg_fence(s0);
#define ATT_ITER(KIND) do { \
        ATT_STEP(KIND, 1, s1, kb, 3, o3, p1, kp, s0, p0, 1);     \
        ATT_STEP(KIND, 2, s0, kb, 0, o0, p0, kb, s1, p1, 1); \
        if (it == 2 && lane == 0) mbar_arrive_pair(BAR(B_ATT2));     \
        if (it == 3 + r && lane < 2) mbar_arrive(BAR(B_ATT3)); \
        ATT_STEP(KIND, 3, s1, kb, 1, o1, p1, kb, s0, p0, 1); \
        kp = kb; \
        if (KIND == 2) { \
          WG_FENCE(); pv_issue<2, 0>(o2, p0, kp); WG_COMMIT(); sm_exp<KIND>(s1, p1, nk, w); \
        } else { \
          if (it + 1 < nit) { \
            const int bi = (seq >> (4 * it + 4)) & 15; \
            mbar_wait(bi == 4 ? BAR(B_KVOWN) : BAR(B_KVFULL + bi), 0); \
            kb = ((sb + kv_addr(bi)) & 0x3FFFF) >> 4; \
          } \
          if (KIND == 1) ATT_STEP(KIND, 0, s0, kb, 2, o2, p0, kp, s1, p1, LW0); \
          else ATT_STEP(KIND, 0, s0, kb, 2, o2, p0, kp, s1, p1, LASTW); \
        } } while (0)
      {
        const int it = 0;
        ATT_ITER(1);
      }
#pragma unroll 1
      for (int it = 1; it < min(nit, 4); it++) {
        if (r == 0 && it == GOW) mbar_wait(BAR(B_GO), 0);
        if (r == 1 && it == GOIT && lane < 2) mbar_arrive(BAR(B_GO));
        ATT_ITER(0);
      }
      if (nit == 5) {
        const int it = 4;
        if (r == 1 && it == GOIT && lane < 2) mbar_arrive(BAR(B_GO));
        ATT_ITER(2);
        WG_FENCE();
        pv_issue<3, 0>(o3, p1, kp);
        WG_COMMIT();
        WG_WAIT(0);
        reg_fence(o0); reg_fence(o1); reg_fence(o2); reg_fence(o3);
      } else {
        WG_FENCE();
        pv_issue<3, 0>(o3, p1, kp);
        WG_COMMIT();
        WG_WAIT(0);
        reg_fence(o0); reg_fence(o1); reg_fence(o2); reg_fence(o3);
      }
      if (nit < 3 && lane == 0) mbar_arrive_pair(BAR(B_ATT2));
      if (nit < 4 + r && lane < 2) mbar_arrive(BAR(B_ATT3));
      if (lane == 0) mbar_arrive(BAR(B_ATTL));
      if (r == 1 && nit <= GOIT && lane < 2) mbar_arrive(BAR(B_GO));
      {
        const uint32_t e0 = 63u << 23;
        const uint32_t ba = (__float_as_uint(o0[8]) - e0) | (__float_as_uint(o0[10]) - e0) | (__float_as_uint(o2[8]) - e0) | (__float_as_uint(o2[10]) - e0);
        const uint32_t bb = (__float_as_uint(o1[0]) - e0) | (__float_as_uint(o1[2]) - e0) | (__float_as_uint(o3[0]) - e0) | (__float_as_uint(o3[2]) - e0);
        if (__builtin_expect(__any_sync(0xffffffffu, ((tq == 2 ? ba : tq == 0 ? bb : 0u) >> 30) != FORCE_SAFE), 0)) {
          const uint8_t* kv = g_kv + (ptrdiff_t)((2 * rb - 4) * 8 + c) * KVB + lane * 4;
          safe_head<0>(o0, q, kv, seq, nit, row0 - 2 * tq, row1 - 2 * tq, tq, tag);
          safe_head<1>(o1, q, kv, seq, nit, row0 - 2 * tq, row1 - 2 * tq, tq, tag);
          safe_head<2>(o2, q, kv, seq, nit, row0 - 2 * tq, row1 - 2 * tq, tq, tag);
          safe_head<3>(o3, q, kv, seq, nit, row0 - 2 * tq, row1 - 2 * tq, tq, tag);
          __syncwarp();
        }
      }
      {
        const uint8_t* xp = reinterpret_cast<const uint8_t*>(P.x) + (size_t)(b * 64 + row0) * 1280 + c * 160 + tq * 4;
        const uint8_t* xq = xp + (56 - w * 16) * 1280;
#pragma unroll
        for (int t = 0; t < 10; t++) {
          xr[2 * t] = ldnc32(xp + t * 16);
          xr[2 * t + 1] = ldnc32(xq + t * 16);
        }
      }
      float inv[4][2];
      inv[0][0] = rcp(__shfl_sync(0xffffffffu, o0[8], (lane & 28) + 2));
      inv[0][1] = rcp(__shfl_sync(0xffffffffu, o0[10], (lane & 28) + 2));
      inv[1][0] = rcp(__shfl_sync(0xffffffffu, o1[0], lane & 28));
      inv[1][1] = rcp(__shfl_sync(0xffffffffu, o1[2], lane & 28));
      inv[2][0] = rcp(__shfl_sync(0xffffffffu, o2[8], (lane & 28) + 2));
      inv[2][1] = rcp(__shfl_sync(0xffffffffu, o2[10], (lane & 28) + 2));
      inv[3][0] = rcp(__shfl_sync(0xffffffffu, o3[0], lane & 28));
      inv[3][1] = rcp(__shfl_sync(0xffffffffu, o3[2], lane & 28));
      const bool lo = tq < 2;
#define OPK(dst, o, t, h) do { x0[dst] = pack2(o[4 * (t)] * inv[h][0], o[4 * (t) + 1] * inv[h][0]); x0[dst + 1] = pack2(o[4 * (t) + 2] * inv[h][1], o[4 * (t) + 3] * inv[h][1]); } while (0)
#define OPK2(dst, oa, ha, ob, hb) do { \
        const float i0 = lo ? inv[ha][0] : inv[hb][0], i1 = lo ? inv[ha][1] : inv[hb][1]; \
        x0[dst] = pack2((lo ? oa[8] : ob[0]) * i0, (lo ? oa[9] : ob[1]) * i0); \
        x0[dst + 1] = pack2((lo ? oa[10] : ob[2]) * i1, (lo ? oa[11] : ob[3]) * i1); } while (0)
      OPK(0, o0, 0, 0); OPK(2, o0, 1, 0); OPK2(4, o0, 0, o1, 1); OPK(6, o1, 1, 1); OPK(8, o1, 2, 1);
      OPK(10, o2, 0, 2); OPK(12, o2, 1, 2); OPK2(14, o2, 2, o3, 3); OPK(16, o3, 1, 3); OPK(18, o3, 2, 3);
    }
    const int bw = b * 4 + w;
    const size_t tile_off = (size_t)b * 81920 + w * 2560 + lane * 16;
    uint32_t* hint = &g_hint[b * 8 * HS + w];
    {
#pragma unroll
      for (int k = 0; k < 5; k++) {
        x0[4 * k] = tag16(x0[4 * k], tag);
        stg128(g_o + tile_off + c * 10240 + k * 512, x0[4 * k], x0[4 * k + 1], x0[4 * k + 2], x0[4 * k + 3]);
      }
      if (lane == 0) st_flag(hint + c * HS, tag);
      STAMP(6);
      float acc[40];
      constexpr uint64_t HI = desc_hi(2560, 256, 3);
      const uint64_t db = mkdesc(sb + OFF_WOB, HI);
      mbar_wait(BAR(B_WOB), 0);
#pragma unroll
      for (int t = 0; t < 10; t++) {
        acc[4 * t] = bf_lo(xr[2 * t]); acc[4 * t + 1] = bf_hi(xr[2 * t]);
        acc[4 * t + 2] = bf_lo(xr[2 * t + 1]); acc[4 * t + 3] = bf_hi(xr[2 * t + 1]);
      }
      WG_FENCE();
#pragma unroll
      for (int k = 0; k < 5; k++) wg_rs80(acc, x0[4 * k], x0[4 * k + 1], x0[4 * k + 2], x0[4 * k + 3], db + k * 32, 1);
      WG_COMMIT();
      mbar_wait(BAR(B_WOB7), 0);
      STAMP(7);
      WG_WAIT(0);
      uint32_t xa[7][20];
      const uint32_t ol = sb + w * 2560 + lane * 16;
#pragma unroll
      for (int i = 0; i < 7; i++) {
        if (!(i & 1)) mbar_wait(BAR((r ? B_QFULL : B_KVFULL) + (i >> 1)), r ? i < 4 : 4 * rb + i >= 8);
#pragma unroll
        for (int k = 0; k < 5; k++)
          asm volatile("ld.shared.v4.u32 {%0,%1,%2,%3}, [%4];" : "=r"(xa[i][4 * k]), "=r"(xa[i][4 * k + 1]), "=r"(xa[i][4 * k + 2]), "=r"(xa[i][4 * k + 3])
                       : "r"(ol + (r ? 102400u : i < 3 ? 179200u : 107520u) + i * 10240 + k * 512) : "memory");
      }
      {
        uint32_t bad = 0;
#pragma unroll
        for (int i = 0; i < 7; i++)
#pragma unroll
          for (int k = 0; k < 5; k++) bad |= xa[i][4 * k] ^ tag;
        bad = __any_sync(0xffffffffu, (bad & TAGM) != 0u);
        if (lane < 2 - r) mbar_arrive_pair(BAR(r ? B_OL1 : B_ATT4));
        if (r && lane < 2) mbar_arrive(BAR(B_OL1L));
        if (__builtin_expect(bad, 0)) {
#pragma unroll
          for (int i = 0; i < 7; i++) fix_tile(xa[i], g_o + tile_off, c, i + 1, tag);
        }
      }
      WG_FENCE();
#pragma unroll
      for (int i = 0; i < 7; i++) {
#pragma unroll
        for (int k = 0; k < 5; k++) wg_rs80(acc, xa[i][4 * k], xa[i][4 * k + 1], xa[i][4 * k + 2], xa[i][4 * k + 3], db + (i + 1) * 800 + k * 32, 1);
        if (i == 1 || i == 2 || i >= 4) WG_COMMIT();
        if (i == 2 || i == 5) {
          WG_WAIT(1);
          if (lane == 0) mbar_arrive_pair(BAR(i == 2 ? B_WODP : B_WODP2));
        }
      }
      WG_WAIT(0);
      reg_fence(acc);
      STAMP(8);
#pragma unroll
      for (int t = 0; t < 10; t++) {
        x0[2 * t] = pack2(acc[4 * t], acc[4 * t + 1]);
        x0[2 * t + 1] = pack2(acc[4 * t + 2], acc[4 * t + 3]);
      }
#pragma unroll
      for (int k = 0; k < 5; k++) {
        x0[4 * k] = tag16(x0[4 * k], tag);
        stg128(g_h + tile_off + c * 10240 + k * 512, x0[4 * k], x0[4 * k + 1], x0[4 * k + 2], x0[4 * k + 3]);
      }
      if (lane == 0) st_flag(hint + 256 * HS + c * HS, tag);
      mbar_wait(BAR(B_BFULL), 0);
      float sum0 = 0.f, sum1 = 0.f;
#pragma unroll
      for (int t = 0; t < 10; t++) {
        sum0 += acc[4 * t] + acc[4 * t + 1];
        sum1 += acc[4 * t + 2] + acc[4 * t + 3];
      }
      sum0 += __shfl_xor_sync(0xffffffffu, sum0, 1);
      sum1 += __shfl_xor_sync(0xffffffffu, sum1, 1);
      sum0 += __shfl_xor_sync(0xffffffffu, sum0, 2);
      sum1 += __shfl_xor_sync(0xffffffffu, sum1, 2);
      const float mu0 = sum0 * (1.f / 80.f), mu1 = sum1 * (1.f / 80.f);
      float v0 = 0.f, v1 = 0.f;
#pragma unroll
      for (int t = 0; t < 10; t++) {
        const float d0 = acc[4 * t] - mu0, d1 = acc[4 * t + 1] - mu0, d2 = acc[4 * t + 2] - mu1, d3 = acc[4 * t + 3] - mu1;
        v0 += d0 * d0 + d1 * d1;
        v1 += d2 * d2 + d3 * d3;
      }
      v0 += __shfl_xor_sync(0xffffffffu, v0, 1);
      v1 += __shfl_xor_sync(0xffffffffu, v1, 1);
      v0 += __shfl_xor_sync(0xffffffffu, v0, 2);
      v1 += __shfl_xor_sync(0xffffffffu, v1, 2);
      if (tq < 2) g_hstat[(bw * 8 + c) * 16 + gq + tq * 8] = make_float2(tq ? mu1 : mu0, tag32(tq ? v1 : v0, ep));
    }
    uint32_t ha[56];
    {
      float acc[112];
      constexpr uint64_t HI = desc_hi(5120, 512, 2);
#define ST4(i)
#define ST5(i)
#define W1_ISSUE(xx, i) do { \
        const uint64_t db = mkdesc(sb + w1b_addr(i), HI); \
        mbar_wait(BAR(B_BFULL + (i)), 0); \
        WG_FENCE(); \
        _Pragma("unroll") for (int k = 0; k < 5; k++) wg_rs224(acc, xx[4 * k], xx[4 * k + 1], xx[4 * k + 2], xx[4 * k + 3], db + k * 64, (i) | k); \
        WG_COMMIT(); } while (0)
#define W1_STEP(xx, i) do { \
        ST4(i); \
        W1_ISSUE(xx, i); \
        WG_WAIT(1); \
        ST5(i); \
        if ((i) != 4 && (i) != 1 && lane == 0) mbar_arrive_pair(BAR(B_BEMPTY - 1 + (i))); } while (0)
#define HT(i) ht, c, i
      const uint8_t* ht = g_h + tile_off;
      uint32_t x1[20], x2[20], x3[20];
      uint32_t ready = 0;
      probe_wait(ready, 1, hint + 256 * HS + ((c + lane) & 7) * HS, tag);
      ld_tile(x1, HT(1));
      probe_wait(ready, 2, hint + 256 * HS + ((c + lane) & 7) * HS, tag);
      ld_tile(x2, HT(2));
      probe_wait(ready, 3, hint + 256 * HS + ((c + lane) & 7) * HS, tag);
      ld_tile(x3, HT(3));
      STAMP(9);
      W1_ISSUE(x0, 0);
      {
        const uint32_t hs = sb + OFF_HST + (uint32_t)(r * 64 + rowm) * 160u + (uint32_t)(lane >> 4) * 16u;
        mbar_wait(BAR(B_ATTL), 0);
#pragma unroll
        for (int k = 0; k < 5; k++) stsm4(hs + k * 32, x0[4 * k], x0[4 * k + 1], x0[4 * k + 2], x0[4 * k + 3]);
        fence_async_smem();
        __syncwarp();
        if (lane == 0) mbar_arrive(BAR(B_HST + r));
      }
      WG_WAIT(0);
      if (lane == 0) mbar_arrive_pair(BAR(B_BEMPTY));
      fix_tile(x1, HT(1), tag);
      fix_tile(x2, HT(2), tag);
      fix_tile(x3, HT(3), tag);
      STAMP(10);
      W1_STEP(x1, 1);
      ld_tile(x0, HT(4));
      W1_STEP(x2, 2);
      ld_tile(x1, HT(5));
      W1_STEP(x3, 3);
      fix_tile(x0, HT(4), tag);
      fix_tile(x1, HT(5), tag);
      ld_tile(x2, HT(6));
      W1_STEP(x0, 4);
      ld_tile(x3, HT(7));
      uint2 hs[4];
      const float2* hp = &g_hstat[(bw * 8 + tq * 2) * 16 + gq];
      hs[0] = ldcg64(hp); hs[1] = ldcg64(hp + 16); hs[2] = ldcg64(hp + 8); hs[3] = ldcg64(hp + 24);
      W1_STEP(x1, 5);
      fix_tile(x2, HT(6), tag);
      fix_tile(x3, HT(7), tag);
      W1_STEP(x2, 6);
      W1_STEP(x3, 7);
      {
        uint32_t n = 0;
        while (__any_sync(0xffffffffu, (((hs[0].y ^ ep) | (hs[1].y ^ ep) | (hs[2].y ^ ep) | (hs[3].y ^ ep)) & 3u) != 0u) && ++n < SPIN_MAX) {
          hs[0] = ldcg64(hp); hs[1] = ldcg64(hp + 16); hs[2] = ldcg64(hp + 8); hs[3] = ldcg64(hp + 24);
        }
      }
      float mean0, mean1, rs0, rs1;
      {
        const float a0 = __uint_as_float(hs[0].x), a1 = __uint_as_float(hs[1].x), b0 = __uint_as_float(hs[2].x), b1 = __uint_as_float(hs[3].x);
        float t0 = a0 + a1, t1 = b0 + b1;
        t0 += __shfl_xor_sync(0xffffffffu, t0, 1);
        t1 += __shfl_xor_sync(0xffffffffu, t1, 1);
        t0 += __shfl_xor_sync(0xffffffffu, t0, 2);
        t1 += __shfl_xor_sync(0xffffffffu, t1, 2);
        mean0 = t0 * 0.125f;
        mean1 = t1 * 0.125f;
        float u0 = __uint_as_float(hs[0].y) + __uint_as_float(hs[1].y) + 80.f * ((a0 - mean0) * (a0 - mean0) + (a1 - mean0) * (a1 - mean0));
        float u1 = __uint_as_float(hs[2].y) + __uint_as_float(hs[3].y) + 80.f * ((b0 - mean1) * (b0 - mean1) + (b1 - mean1) * (b1 - mean1));
        u0 += __shfl_xor_sync(0xffffffffu, u0, 1);
        u1 += __shfl_xor_sync(0xffffffffu, u1, 1);
        u0 += __shfl_xor_sync(0xffffffffu, u0, 2);
        u1 += __shfl_xor_sync(0xffffffffu, u1, 2);
        rs0 = 0.5f * rsqrtf(u0 * (1.f / 640.f) + 1e-5f);
        rs1 = 0.5f * rsqrtf(u1 * (1.f / 640.f) + 1e-5f);
      }
      mbar_wait(BAR(B_CS1), 0);
      WG_WAIT(0);
      reg_fence(acc);
      if (lane == 0) mbar_arrive_pair(BAR(B_BEMPTY + 7));
      STAMP(11);
      const float n0 = -mean0 * rs0, n1 = -mean1 * rs1;
#pragma unroll
      for (int t = 0; t < 28; t++) {
        const float2 cs = lds64f(sb + OFF_XS + t * 32 + tq * 8);
        const float h0 = fmaf(acc[4 * t], rs0, cs.x * n0), h1 = fmaf(acc[4 * t + 1], rs0, cs.y * n0);
        const float h2 = fmaf(acc[4 * t + 2], rs1, cs.x * n1), h3 = fmaf(acc[4 * t + 3], rs1, cs.y * n1);
        ha[2 * t] = pack2(fmaf(h0, tanh_fast(h0), h0), fmaf(h1, tanh_fast(h1), h1));
        ha[2 * t + 1] = pack2(fmaf(h2, tanh_fast(h2), h2), fmaf(h3, tanh_fast(h3), h3));
      }
      if ((c & 3) == 3) {
#pragma unroll
        for (int t = 48; t < 56; t++) ha[t] = 0u;
      }
    }
    STAMP(12);
    {
      float accA[64], accB[64];
      constexpr uint64_t HI = desc_hi(28672, 1024, 1);
      const uint32_t ost = sb + OFF_OST + (uint32_t)warp * 6144u;
      const uint32_t osw = ost + (uint32_t)(lane & 15) * 128u + (uint32_t)(((lane >> 4) ^ lane) & 7) * 16u;
#define W2_ISSUE(acc, s) do { \
        const uint64_t db = mkdesc(sb + ((s) % 3) * W2SLOT + mbar_wait0(BAR(B_W2FULL + (s))), HI); \
        WG_FENCE(); \
        _Pragma("unroll") for (int k = 0; k < 14; k++) wg_rs128(acc, ha[4 * k], ha[4 * k + 1], ha[4 * k + 2], ha[4 * k + 3], db + k * 128, k); \
        WG_COMMIT(); } while (0)
#define W2_OUT(acc, s) do { \
        reg_fence(acc); \
        if ((s) < 2 && lane == 0) mbar_arrive_pair(BAR(B_W2E + (s))); \
        _Pragma("unroll") for (int u = 2 * (s); u < 2 * (s) + 2; u++) { \
          const float* a = &acc[(u & 1) * 32]; \
          if (u >= 3) { if (lane == 0) asm volatile("cp.async.bulk.wait_group.read 2;" ::: "memory"); __syncwarp(); } \
          _Pragma("unroll") for (int t = 0; t < 8; t += 2) \
            stsm4((osw ^ (t * 16)) + (u % 3) * 2048, pack2(a[4 * t], a[4 * t + 1]), pack2(a[4 * t + 2], a[4 * t + 3]), pack2(a[4 * t + 4], a[4 * t + 5]), pack2(a[4 * t + 6], a[4 * t + 7])); \
          fence_async_smem(); \
          __syncwarp(); \
          if (lane == 0) \
            asm volatile("cp.reduce.async.bulk.tensor.3d.global.shared::cta.add.bulk_group [%0, {%2, %3, %4}], [%1];\ncp.async.bulk.commit_group;" \
                         ::"l"(&P.mOut[w]), "r"(ost + (u % 3) * 2048), "r"(min((uint32_t)c * 64u + u * 64u, (uint32_t)c * 64u + u * 64u - 640u)), "r"(b * 64 + w * 8), "r"(0) : "memory"); \
        } } while (0)
      W2_ISSUE(accA, 0);
      W2_ISSUE(accB, 1);
      mbar_wait(BAR(B_BEMPTY + 7), 0);
      mbar_wait(BAR(B_OUTOK + r), 0);
      fence_async_glob();
      WG_WAIT(1);
      W2_OUT(accA, 0);
      STAMP(13);
      W2_ISSUE(accA, 2);
      WG_WAIT(1);
      W2_OUT(accB, 1);
      W2_ISSUE(accB, 3);
      WG_WAIT(1);
      W2_OUT(accA, 2);
      W2_ISSUE(accA, 4);
      WG_WAIT(1);
      W2_OUT(accB, 3);
      STAMP(14);
      WG_WAIT(0);
      W2_OUT(accA, 4);
      STAMP(15);
      if (lane == 0) asm volatile("cp.async.bulk.wait_group.read 0;" ::: "memory");
      STAMP(17);
    }
  }
}

typedef CUresult (*EncodeFn)(CUtensorMap*, CUtensorMapDataType, cuuint32_t, void*, const cuuint64_t*, const cuuint64_t*, const cuuint32_t*,
                             const cuuint32_t*, CUtensorMapInterleave, CUtensorMapSwizzle, CUtensorMapL2promotion, CUtensorMapFloatOOBfill);

static void make_map(EncodeFn enc, CUtensorMap* m, const void* p, int nd, const cuuint64_t* dims, const cuuint64_t* strides, const cuuint32_t* box,
                     CUtensorMapSwizzle sw) {
  const cuuint32_t es[5] = {1, 1, 1, 1, 1};
  enc(m, CU_TENSOR_MAP_DATA_TYPE_BFLOAT16, (cuuint32_t)nd, const_cast<void*>(p), dims, strides, box, es, CU_TENSOR_MAP_INTERLEAVE_NONE, sw,
      CU_TENSOR_MAP_L2_PROMOTION_L2_128B, CU_TENSOR_MAP_FLOAT_OOB_FILL_NONE);
}

extern "C" void kernel_launch(void* const* d_in, const int* in_sizes, int n_in, void* d_out, int out_size) {
  (void)in_sizes; (void)n_in; (void)out_size;
  static EncodeFn enc = nullptr;
  if (!enc) {
    void* f = nullptr;
    cudaDriverEntryPointQueryResult qr;
    cudaGetDriverEntryPoint("cuTensorMapEncodeTiled", &f, cudaEnableDefault, &qr);
    enc = (EncodeFn)f;
    cudaFuncSetAttribute(fused_block_kernel, cudaFuncAttributeMaxDynamicSharedMemorySize, (int)SMEM_BYTES);
  }
  Params P;
  P.x = (const __nv_bfloat16*)d_in[0];
  P.wqkv = (const __nv_bfloat16*)d_in[1];
  P.wo = (const __nv_bfloat16*)d_in[2];
  P.w1 = (const __nv_bfloat16*)d_in[4];
  P.w2 = (const __nv_bfloat16*)d_in[5];
  P.out = (__nv_bfloat16*)d_out;
  for (int k = 0; k < 64; k++) {
    const int c = k < 4 ? k + 4 : k < 36 ? (k - 4) >> 3 : (k * 37 - 308) >> 8;
    const int g = k < 4 ? 0 : k < 36 ? (k - 1) & 7 : k - 33 - 7 * ((k * 37 - 1258) >> 8);
    reinterpret_cast<uint8_t*>(P.map)[k] = (uint8_t)(c + 8 * g);
  }
  { const cuuint64_t d[2] = {640, 2048}, s[1] = {1280}; const cuuint32_t b[2] = {64, 128}; make_map(enc, &P.mX, P.x, 2, d, s, b, CU_TENSOR_MAP_SWIZZLE_128B); }
  { const cuuint64_t d[4] = {32, 640, 20, 3}, s[3] = {3840, 64, 1280}; const cuuint32_t b[4] = {32, 32, 2, 3}; make_map(enc, &P.mWqM, P.wqkv, 4, d, s, b, CU_TENSOR_MAP_SWIZZLE_64B); }
  { const cuuint64_t d[4] = {16, 640, 40, 3}, s[3] = {3840, 32, 1280}; const cuuint32_t b[4] = {16, 32, 1, 3}; make_map(enc, &P.mWqL, P.wqkv, 4, d, s, b, CU_TENSOR_MAP_SWIZZLE_32B); }
  { const cuuint64_t d[3] = {16, 640, 40}, s[2] = {1280, 32}; const cuuint32_t b[3] = {16, 80, 5}; make_map(enc, &P.mWo, P.wo, 3, d, s, b, CU_TENSOR_MAP_SWIZZLE_32B); }
  { const cuuint64_t d[3] = {32, 640, 54}, s[2] = {3456, 64}; const cuuint32_t b[3] = {32, 80, 4}; make_map(enc, &P.mW1a, P.w1, 3, d, s, b, CU_TENSOR_MAP_SWIZZLE_64B); }
  { const cuuint64_t d[3] = {32, 640, 54}, s[2] = {3456, 64}; const cuuint32_t b[3] = {32, 80, 3}; make_map(enc, &P.mW1b, P.w1, 3, d, s, b, CU_TENSOR_MAP_SWIZZLE_64B); }
  { const cuuint64_t d[2] = {640, 1728}, s[1] = {1280}; const cuuint32_t b[2] = {64, 112}; make_map(enc, &P.mW2, P.w2, 2, d, s, b, CU_TENSOR_MAP_SWIZZLE_128B); }
  { const cuuint64_t d[2] = {640, 2048}, s[1] = {1280}; const cuuint32_t b[2] = {80, 64}; make_map(enc, &P.mOutH, P.out, 2, d, s, b, CU_TENSOR_MAP_SWIZZLE_NONE); }
  for (int w = 0; w < 4; w++) {
    const cuuint64_t d[3] = {640, 2048, 2}, s[2] = {1280, (cuuint64_t)(56 - 16 * w) * 1280};
    const cuuint32_t b[3] = {64, 8, 2};
    make_map(enc, &P.mOut[w], P.out, 3, d, s, b, CU_TENSOR_MAP_SWIZZLE_128B);
  }
  fused_block_kernel<<<128, 384, SMEM_BYTES, cudaStreamPerThread>>>(P);
}
```

```cpp
#include <cuda_runtime.h>
#include <cuda.h>
#include <cuda_bf16.h>
#include <stdint.h>

#define PROF 0
#define PF0 1
#define LASTW 1
#define LW0 1
#define LWX 0
#define QORD 2
#define LEAD0 1
#define KVP 8
#define GOIT 3
#define GOW 1
#define HPROBE 1
#define HS 8
#define HMODE 0
#define XRB 1
#define WOPH 3
#define HNEW 2
#define DLY 9
#define HP 9
#define HRST 1
#define APR 4
#define EARL 0
#define X4E 0
#define ORD7 0
#define CSU 4
#define NOFIX 0
#define XRST 1
#define W2N 1
#define PP 1
#define UNI 0
#define FORCE_SAFE 0u

__device__ __align__(1024) uint8_t g_kv[32 * 8 * 22528];
__device__ __align__(1024) uint8_t g_o[32 * 4 * 8 * 2560];
__device__ __align__(1024) uint8_t g_h[32 * 4 * 8 * 2560];
__device__ __align__(1024) float2 g_hstat[32 * 4 * 8 * 16];
__device__ __align__(128) uint32_t g_hint[2 * 32 * 8 * HS];
__device__ __align__(128) uint32_t g_oflag[32 * 8];
__device__ __align__(128) float2 g_xstat[128 * 24];
__device__ __align__(128) float g_csq[8 * 8 * 240];
__device__ __align__(128) float g_cs1[8 * 8 * 224];
__device__ __align__(128) uint32_t g_epoch[128 * 32];
#define STAMP(slot)
#define STAMPW(slot)

struct Params {
  const __nv_bfloat16 *x, *wqkv, *wo, *w1, *w2;
  __nv_bfloat16* out;
  uint32_t map[16];
  CUtensorMap mX, mWqM[2], mWqL, mWo, mW1a, mW1b, mW2, mOutH, mOut[4];
};

constexpr uint32_t QST = 47104;
constexpr uint32_t KVB = 22528;
constexpr uint32_t OFF_WOB = 0;
constexpr uint32_t OFF_PRE = 188416;
constexpr uint32_t OFF_XROW = 196608;
constexpr uint32_t W2SLOT = 57344;
constexpr uint32_t OFF_OST = 174080;
constexpr uint32_t OFF_HST = 209920;
constexpr uint32_t OFF_CS = 229376;
constexpr uint32_t OFF_XST = 230336;
constexpr uint32_t OFF_HINT = 230400;
constexpr uint32_t OFF_XS = 230912;
constexpr uint32_t OFF_MISC = 231808;
constexpr uint32_t SMEM_BYTES = 232448;

enum {
  B_QFULL = 0, B_KVFULL = 4, B_KVLAND = 8, B_WOB = 12, B_WOB7 = 13, B_BFULL = 14, B_W2FULL = 22, B_CS1 = 27, B_OUTOK = 28,
  B_KVOWN = 30, B_HST = 32, B_STAT = 34, B_XROW = 35,
  B_Q23 = 36, B_PRE = 37, B_ATTL = 38, B_GO = 39, B_OL1 = 40, B_OL1L = 41,
  B_QEMPTY = 42, B_W2E = 46, B_WODP = 48, B_BEMPTY = 49, B_WODP2 = 57, B_ATT4 = 58, B_ATT3 = 59,
  B_ATT2 = 60
};
constexpr uint32_t TAGM = 0x00010001u;
constexpr uint32_t SPIN_MAX = 1u << 18;

__device__ __forceinline__ uint32_t s2u(const void* p) { return (uint32_t)__cvta_generic_to_shared(p); }
__device__ __forceinline__ void mbar_init(uint32_t b, int c) { asm volatile("mbarrier.init.shared::cta.b64 [%0], %1;" ::"r"(b), "r"(c)); }
__device__ __forceinline__ void mbar_expect(uint32_t b, int bytes) { asm volatile("mbarrier.arrive.expect_tx.shared::cta.b64 _, [%0], %1;" ::"r"(b), "r"(bytes) : "memory"); }
__device__ __forceinline__ void mbar_arrive(uint32_t b) { asm volatile("mbarrier.arrive.shared::cta.b64 _, [%0];" ::"r"(b) : "memory"); }
__device__ __forceinline__ void mbar_arrive_pair(uint32_t b) {
  asm volatile("{\n.reg .b32 r;\nmapa.shared::cluster.u32 r, %0, 0;\nmbarrier.arrive.shared::cluster.b64 _, [r];\n"
               "mapa.shared::cluster.u32 r, %0, 1;\nmbarrier.arrive.shared::cluster.b64 _, [r];\n}" ::"r"(b) : "memory");
}
__device__ __forceinline__ void mbar_wait(uint32_t b, uint32_t ph) {
  asm volatile("{\n.reg .pred p;\n.reg .u32 n;\nmov.u32 n, 0;\nW%=:\nmbarrier.try_wait.parity.shared::cta.b64 p, [%0], %1;\n"
               "add.u32 n, n, 1;\nsetp.lt.and.u32 p, n, 0x100000, !p;\n@p bra W%=;\n}" ::"r"(b), "r"(ph) : "memory");
}
__device__ __forceinline__ uint32_t mbar_wait0(uint32_t b) {
  uint32_t n;
  asm volatile("{\n.reg .pred p;\nmov.u32 %0, 0;\nW%=:\nmbarrier.try_wait.parity.shared::cta.b64 p, [%1], 0;\n"
               "add.u32 %0, %0, 1;\nsetp.lt.and.u32 p, %0, 0x100000, !p;\n@p bra W%=;\n}" : "=r"(n) : "r"(b) : "memory");
  return n >> 21;
}
__device__ __forceinline__ bool mbar_test(uint32_t b) {
  uint32_t v;
  asm volatile("{\n.reg .pred p;\nmbarrier.test_wait.parity.shared::cta.b64 p, [%1], 0;\nselp.u32 %0, 1, 0, p;\n}" : "=r"(v) : "r"(b) : "memory");
  return v != 0u;
}
__device__ __forceinline__ void tma2d(uint32_t dst, const CUtensorMap* m, int c0, int c1, uint32_t bar) {
  asm volatile("cp.async.bulk.tensor.2d.shared::cluster.global.mbarrier::complete_tx::bytes [%0], [%1, {%3, %4}], [%2];" ::"r"(dst), "l"(m), "r"(bar), "r"(c0), "r"(c1) : "memory");
}
__device__ __forceinline__ void tma2d_mc(uint32_t dst, const CUtensorMap* m, int c0, int c1, uint32_t bar) {
  asm volatile("cp.async.bulk.tensor.2d.shared::cluster.global.mbarrier::complete_tx::bytes.multicast::cluster [%0], [%1, {%3, %4}], [%2], %5;" ::"r"(dst), "l"(m), "r"(bar), "r"(c0), "r"(c1), "h"((uint16_t)3) : "memory");
}
__device__ __forceinline__ void tma3d(uint32_t dst, const CUtensorMap* m, int c0, int c1, int c2, uint32_t bar) {
  asm volatile("cp.async.bulk.tensor.3d.shared::cluster.global.mbarrier::complete_tx::bytes [%0], [%1, {%3, %4, %5}], [%2];" ::"r"(dst), "l"(m), "r"(bar), "r"(c0), "r"(c1), "r"(c2) : "memory");
}
__device__ __forceinline__ void tma3d_mc(uint32_t dst, const CUtensorMap* m, int c0, int c1, int c2, uint32_t bar) {
  asm volatile("cp.async.bulk.tensor.3d.shared::cluster.global.mbarrier::complete_tx::bytes.multicast::cluster [%0], [%1, {%3, %4, %5}], [%2], %6;" ::"r"(dst), "l"(m), "r"(bar), "r"(c0), "r"(c1), "r"(c2), "h"((uint16_t)3) : "memory");
}
__device__ __forceinline__ void tma4d_mc(uint32_t dst, const CUtensorMap* m, int c0, int c1, int c2, int c3, uint32_t bar) {
  asm volatile("cp.async.bulk.tensor.4d.shared::cluster.global.mbarrier::complete_tx::bytes.multicast::cluster [%0], [%1, {%3, %4, %5, %6}], [%2], %7;" ::"r"(dst), "l"(m), "r"(bar), "r"(c0), "r"(c1), "r"(c2), "r"(c3), "h"((uint16_t)3) : "memory");
}
__device__ __forceinline__ void bulk_load(uint32_t dst, const void* src, int bytes, uint32_t bar) {
  asm volatile("cp.async.bulk.shared::cluster.global.mbarrier::complete_tx::bytes [%0], [%1], %2, [%3];" ::"r"(dst), "l"(src), "r"(bytes), "r"(bar) : "memory");
}
__device__ __forceinline__ void tma4d_pf(const CUtensorMap* m, int c0, int c1, int c2, int c3) {
  asm volatile("cp.async.bulk.prefetch.tensor.4d.L2.global [%0, {%1, %2, %3, %4}];" ::"l"(m), "r"(c0), "r"(c1), "r"(c2), "r"(c3) : "memory");
}
__device__ __forceinline__ void l2_prefetch_bulk(const void* p, int bytes) { asm volatile("cp.async.bulk.prefetch.L2.global [%0], %1;" ::"l"(p), "r"(bytes) : "memory"); }
__device__ __forceinline__ void l2_prefetch(const void* p) { asm volatile("prefetch.global.L2 [%0];" ::"l"(p)); }
__device__ __forceinline__ uint32_t ld_flag(const uint32_t* p) { uint32_t v; asm volatile("ld.acquire.gpu.global.u32 %0, [%1];" : "=r"(v) : "l"(p) : "memory"); return v; }
__device__ __forceinline__ void st_flag(uint32_t* p, uint32_t v) { asm volatile("st.relaxed.gpu.global.u32 [%0], %1;" ::"l"(p), "r"(v) : "memory"); }
__device__ __forceinline__ void fence_gpu() { asm volatile("fence.acq_rel.gpu;" ::: "memory"); }
__device__ __forceinline__ void fence_async_smem() { asm volatile("fence.proxy.async.shared::cta;" ::: "memory"); }
__device__ __forceinline__ void fence_async_glob() { asm volatile("fence.proxy.async.global;" ::: "memory"); }
__device__ __forceinline__ uint4 ldcg128(const void* p) { uint4 v; asm volatile("ld.relaxed.gpu.global.v4.u32 {%0,%1,%2,%3}, [%4];" : "=r"(v.x), "=r"(v.y), "=r"(v.z), "=r"(v.w) : "l"(p) : "memory"); return v; }
__device__ __forceinline__ uint4 ldnc128(const void* p) { uint4 v; asm volatile("ld.global.nc.v4.u32 {%0,%1,%2,%3}, [%4];" : "=r"(v.x), "=r"(v.y), "=r"(v.z), "=r"(v.w) : "l"(p)); return v; }
__device__ __forceinline__ uint32_t ldnc32(const void* p) { uint32_t v; asm volatile("ld.global.nc.u32 %0, [%1];" : "=r"(v) : "l"(p)); return v; }
__device__ __forceinline__ uint2 ldcg64(const void* p) { uint2 v; asm volatile("ld.relaxed.gpu.global.v2.u32 {%0,%1}, [%2];" : "=r"(v.x), "=r"(v.y) : "l"(p) : "memory"); return v; }
__device__ __forceinline__ uint32_t ldcg32(const void* p) { uint32_t v; asm volatile("ld.relaxed.gpu.global.u32 %0, [%1];" : "=r"(v) : "l"(p) : "memory"); return v; }
__device__ __forceinline__ uint32_t pack2(float lo, float hi) { uint32_t r; asm("cvt.rn.bf16x2.f32 %0, %1, %2;" : "=r"(r) : "f"(hi), "f"(lo)); return r; }
__device__ __forceinline__ float bf_lo(uint32_t v) { return __uint_as_float(v << 16); }
__device__ __forceinline__ float bf_hi(uint32_t v) { return __uint_as_float(v & 0xffff0000u); }
__device__ __forceinline__ float ex2(float x) { float y; asm("ex2.approx.ftz.f32 %0, %1;" : "=f"(y) : "f"(x)); return y; }
__device__ __forceinline__ float rcp(float x) { float y; asm("rcp.approx.ftz.f32 %0, %1;" : "=f"(y) : "f"(x)); return y; }
__device__ __forceinline__ float tanh_fast(float x) { float y; asm("tanh.approx.f32 %0, %1;" : "=f"(y) : "f"(x)); return y; }
__device__ __forceinline__ void stsm4(uint32_t a, uint32_t r0, uint32_t r1, uint32_t r2, uint32_t r3) {
  asm volatile("stmatrix.sync.aligned.m8n8.x4.shared.b16 [%0], {%1,%2,%3,%4};" ::"r"(a), "r"(r0), "r"(r1), "r"(r2), "r"(r3) : "memory");
}
__device__ __forceinline__ void ldsm4(uint32_t* r, uint32_t a) {
  asm volatile("ldmatrix.sync.aligned.m8n8.x4.shared.b16 {%0,%1,%2,%3}, [%4];" : "=r"(r[0]), "=r"(r[1]), "=r"(r[2]), "=r"(r[3]) : "r"(a) : "memory");
}
__device__ __forceinline__ float2 lds64f(uint32_t a) { float2 v; asm volatile("ld.shared.v2.f32 {%0,%1}, [%2];" : "=f"(v.x), "=f"(v.y) : "r"(a)); return v; }
__device__ __forceinline__ constexpr uint64_t desc_hi(uint32_t lbo, uint32_t sbo, uint32_t sw) {
  return ((uint64_t)(lbo >> 4) << 16) | ((uint64_t)(sbo >> 4) << 32) | ((uint64_t)sw << 62);
}
__device__ __forceinline__ uint64_t mkdesc(uint32_t addr, uint64_t hi) { return hi | (uint64_t)((addr & 0x3FFFF) >> 4); }
#define WG_FENCE() asm volatile("wgmma.fence.sync.aligned;" ::: "memory")
#define WG_COMMIT() asm volatile("wgmma.commit_group.sync.aligned;" ::: "memory")
#define WG_WAIT_(n) asm volatile("wgmma.wait_group.sync.aligned " #n ";" ::: "memory")
#define WG_WAIT(n) WG_WAIT_(n)
template <int N> __device__ __forceinline__ void reg_fence(float (&a)[N]) {
#pragma unroll
  for (int i = 0; i < N; i++) asm volatile("" : "+f"(a[i])::"memory");
}

__device__ __forceinline__ void wg_rs48(float (&d)[24], uint32_t a0, uint32_t a1, uint32_t a2, uint32_t a3, uint64_t db, int sd) {
  asm volatile("{\n.reg .pred p;\nsetp.ne.b32 p, %29, 0;\n"
  "wgmma.mma_async.sync.aligned.m64n48k16.f32.bf16.bf16 {%0, %1, %2, %3, %4, %5, %6, %7, %8, %9, %10, %11, %12, %13, %14, %15, %16, %17, %18, %19, %20, %21, %22, %23}, {%24, %25, %26, %27}, %28, p, 1, 1, 1;\n}\n"
  : "+f"(d[0]), "+f"(d[1]), "+f"(d[2]), "+f"(d[3]), "+f"(d[4]), "+f"(d[5]), "+f"(d[6]), "+f"(d[7]), "+f"(d[8]), "+f"(d[9]), "+f"(d[10]), "+f"(d[11]), "+f"(d[12]), "+f"(d[13]), "+f"(d[14]), "+f"(d[15]), "+f"(d[16]), "+f"(d[17]), "+f"(d[18]), "+f"(d[19]), "+f"(d[20]), "+f"(d[21]), "+f"(d[22]), "+f"(d[23]) : "r"(a0), "r"(a1), "r"(a2), "r"(a3), "l"(db), "r"(sd));
}
__device__ __forceinline__ void wg_rs80(float (&d)[40], uint32_t a0, uint32_t a1, uint32_t a2, uint32_t a3, uint64_t db, int sd) {
  asm volatile("{\n.reg .pred p;\nsetp.ne.b32 p, %45, 0;\n"
  "wgmma.mma_async.sync.aligned.m64n80k16.f32.bf16.bf16 {%0, %1, %2, %3, %4, %5, %6, %7, %8, %9, %10, %11, %12, %13, %14, %15, %16, %17, %18, %19, %20, %21, %22, %23, %24, %25, %26, %27, %28, %29, %30, %31, %32, %33, %34, %35, %36, %37, %38, %39}, {%40, %41, %42, %43}, %44, p, 1, 1, 1;\n}\n"
  : "+f"(d[0]), "+f"(d[1]), "+f"(d[2]), "+f"(d[3]), "+f"(d[4]), "+f"(d[5]), "+f"(d[6]), "+f"(d[7]), "+f"(d[8]), "+f"(d[9]), "+f"(d[10]), "+f"(d[11]), "+f"(d[12]), "+f"(d[13]), "+f"(d[14]), "+f"(d[15]), "+f"(d[16]), "+f"(d[17]), "+f"(d[18]), "+f"(d[19]), "+f"(d[20]), "+f"(d[21]), "+f"(d[22]), "+f"(d[23]), "+f"(d[24]), "+f"(d[25]), "+f"(d[26]), "+f"(d[27]), "+f"(d[28]), "+f"(d[29]), "+f"(d[30]), "+f"(d[31]), "+f"(d[32]), "+f"(d[33]), "+f"(d[34]), "+f"(d[35]), "+f"(d[36]), "+f"(d[37]), "+f"(d[38]), "+f"(d[39]) : "r"(a0), "r"(a1), "r"(a2), "r"(a3), "l"(db), "r"(sd));
}
__device__ __forceinline__ void wg_rs224(float (&d)[112], uint32_t a0, uint32_t a1, uint32_t a2, uint32_t a3, uint64_t db, int sd) {
  asm volatile("{\n.reg .pred p;\nsetp.ne.b32 p, %117, 0;\n"
  "wgmma.mma_async.sync.aligned.m64n224k16.f32.bf16.bf16 {%0, %1, %2, %3, %4, %5, %6, %7, %8, %9, %10, %11, %12, %13, %14, %15, %16, %17, %18, %19, %20, %21, %22, %23, %24, %25, %26, %27, %28, %29, %30, %31, %32, %33, %34, %35, %36, %37, %38, %39, %40, %41, %42, %43, %44, %45, %46, %47, %48, %49, %50, %51, %52, %53, %54, %55, %56, %57, %58, %59, %60, %61, %62, %63, %64, %65, %66, %67, %68, %69, %70, %71, %72, %73, %74, %75, %76, %77, %78, %79, %80, %81, %82, %83, %84, %85, %86, %87, %88, %89, %90, %91, %92, %93, %94, %95, %96, %97, %98, %99, %100, %101, %102, %103, %104, %105, %106, %107, %108, %109, %110, %111}, {%112, %113, %114, %115}, %116, p, 1, 1, 1;\n}\n"
  : "+f"(d[0]), "+f"(d[1]), "+f"(d[2]), "+f"(d[3]), "+f"(d[4]), "+f"(d[5]), "+f"(d[6]), "+f"(d[7]), "+f"(d[8]), "+f"(d[9]), "+f"(d[10]), "+f"(d[11]), "+f"(d[12]), "+f"(d[13]), "+f"(d[14]), "+f"(d[15]), "+f"(d[16]), "+f"(d[17]), "+f"(d[18]), "+f"(d[19]), "+f"(d[20]), "+f"(d[21]), "+f"(d[22]), "+f"(d[23]), "+f"(d[24]), "+f"(d[25]), "+f"(d[26]), "+f"(d[27]), "+f"(d[28]), "+f"(d[29]), "+f"(d[30]), "+f"(d[31]), "+f"(d[32]), "+f"(d[33]), "+f"(d[34]), "+f"(d[35]), "+f"(d[36]), "+f"(d[37]), "+f"(d[38]), "+f"(d[39]), "+f"(d[40]), "+f"(d[41]), "+f"(d[42]), "+f"(d[43]), "+f"(d[44]), "+f"(d[45]), "+f"(d[46]), "+f"(d[47]), "+f"(d[48]), "+f"(d[49]), "+f"(d[50]), "+f"(d[51]), "+f"(d[52]), "+f"(d[53]), "+f"(d[54]), "+f"(d[55]), "+f"(d[56]), "+f"(d[57]), "+f"(d[58]), "+f"(d[59]), "+f"(d[60]), "+f"(d[61]), "+f"(d[62]), "+f"(d[63]), "+f"(d[64]), "+f"(d[65]), "+f"(d[66]), "+f"(d[67]), "+f"(d[68]), "+f"(d[69]), "+f"(d[70]), "+f"(d[71]), "+f"(d[72]), "+f"(d[73]), "+f"(d[74]), "+f"(d[75]), "+f"(d[76]), "+f"(d[77]), "+f"(d[78]), "+f"(d[79]), "+f"(d[80]), "+f"(d[81]), "+f"(d[82]), "+f"(d[83]), "+f"(d[84]), "+f"(d[85]), "+f"(d[86]), "+f"(d[87]), "+f"(d[88]), "+f"(d[89]), "+f"(d[90]), "+f"(d[91]), "+f"(d[92]), "+f"(d[93]), "+f"(d[94]), "+f"(d[95]), "+f"(d[96]), "+f"(d[97]), "+f"(d[98]), "+f"(d[99]), "+f"(d[100]), "+f"(d[101]), "+f"(d[102]), "+f"(d[103]), "+f"(d[104]), "+f"(d[105]), "+f"(d[106]), "+f"(d[107]), "+f"(d[108]), "+f"(d[109]), "+f"(d[110]), "+f"(d[111]) : "r"(a0), "r"(a1), "r"(a2), "r"(a3), "l"(db), "r"(sd));
}
__device__ __forceinline__ void wg_rs64k(float (&d)[32], uint32_t a0, uint32_t a1, uint32_t a2, uint32_t a3, uint64_t db, int sd) {
  asm volatile("{\n.reg .pred p;\nsetp.ne.b32 p, %37, 0;\n"
  "wgmma.mma_async.sync.aligned.m64n64k16.f32.bf16.bf16 {%0, %1, %2, %3, %4, %5, %6, %7, %8, %9, %10, %11, %12, %13, %14, %15, %16, %17, %18, %19, %20, %21, %22, %23, %24, %25, %26, %27, %28, %29, %30, %31}, {%32, %33, %34, %35}, %36, p, 1, 1, 0;\n}\n"
  : "+f"(d[0]), "+f"(d[1]), "+f"(d[2]), "+f"(d[3]), "+f"(d[4]), "+f"(d[5]), "+f"(d[6]), "+f"(d[7]), "+f"(d[8]), "+f"(d[9]), "+f"(d[10]), "+f"(d[11]), "+f"(d[12]), "+f"(d[13]), "+f"(d[14]), "+f"(d[15]), "+f"(d[16]), "+f"(d[17]), "+f"(d[18]), "+f"(d[19]), "+f"(d[20]), "+f"(d[21]), "+f"(d[22]), "+f"(d[23]), "+f"(d[24]), "+f"(d[25]), "+f"(d[26]), "+f"(d[27]), "+f"(d[28]), "+f"(d[29]), "+f"(d[30]), "+f"(d[31]) : "r"(a0), "r"(a1), "r"(a2), "r"(a3), "l"(db), "r"(sd));
}
__device__ __forceinline__ void wg_rs24(float (&d)[12], uint32_t a0, uint32_t a1, uint32_t a2, uint32_t a3, uint64_t db, int sd) {
  asm volatile("{\n.reg .pred p;\nsetp.ne.b32 p, %17, 0;\n"
  "wgmma.mma_async.sync.aligned.m64n24k16.f32.bf16.bf16 {%0, %1, %2, %3, %4, %5, %6, %7, %8, %9, %10, %11}, {%12, %13, %14, %15}, %16, p, 1, 1, 1;\n}\n"
  : "+f"(d[0]), "+f"(d[1]), "+f"(d[2]), "+f"(d[3]), "+f"(d[4]), "+f"(d[5]), "+f"(d[6]), "+f"(d[7]), "+f"(d[8]), "+f"(d[9]), "+f"(d[10]), "+f"(d[11]) : "r"(a0), "r"(a1), "r"(a2), "r"(a3), "l"(db), "r"(sd));
}
__device__ __forceinline__ void wg_rs128(float (&d)[64], uint32_t a0, uint32_t a1, uint32_t a2, uint32_t a3, uint64_t db, int sd) {
  asm volatile("{\n.reg .pred p;\nsetp.ne.b32 p, %69, 0;\n"
  "wgmma.mma_async.sync.aligned.m64n128k16.f32.bf16.bf16 {%0, %1, %2, %3, %4, %5, %6, %7, %8, %9, %10, %11, %12, %13, %14, %15, %16, %17, %18, %19, %20, %21, %22, %23, %24, %25, %26, %27, %28, %29, %30, %31, %32, %33, %34, %35, %36, %37, %38, %39, %40, %41, %42, %43, %44, %45, %46, %47, %48, %49, %50, %51, %52, %53, %54, %55, %56, %57, %58, %59, %60, %61, %62, %63}, {%64, %65, %66, %67}, %68, p, 1, 1, 1;\n}\n"
  : "+f"(d[0]), "+f"(d[1]), "+f"(d[2]), "+f"(d[3]), "+f"(d[4]), "+f"(d[5]), "+f"(d[6]), "+f"(d[7]), "+f"(d[8]), "+f"(d[9]), "+f"(d[10]), "+f"(d[11]), "+f"(d[12]), "+f"(d[13]), "+f"(d[14]), "+f"(d[15]), "+f"(d[16]), "+f"(d[17]), "+f"(d[18]), "+f"(d[19]), "+f"(d[20]), "+f"(d[21]), "+f"(d[22]), "+f"(d[23]), "+f"(d[24]), "+f"(d[25]), "+f"(d[26]), "+f"(d[27]), "+f"(d[28]), "+f"(d[29]), "+f"(d[30]), "+f"(d[31]), "+f"(d[32]), "+f"(d[33]), "+f"(d[34]), "+f"(d[35]), "+f"(d[36]), "+f"(d[37]), "+f"(d[38]), "+f"(d[39]), "+f"(d[40]), "+f"(d[41]), "+f"(d[42]), "+f"(d[43]), "+f"(d[44]), "+f"(d[45]), "+f"(d[46]), "+f"(d[47]), "+f"(d[48]), "+f"(d[49]), "+f"(d[50]), "+f"(d[51]), "+f"(d[52]), "+f"(d[53]), "+f"(d[54]), "+f"(d[55]), "+f"(d[56]), "+f"(d[57]), "+f"(d[58]), "+f"(d[59]), "+f"(d[60]), "+f"(d[61]), "+f"(d[62]), "+f"(d[63]) : "r"(a0), "r"(a1), "r"(a2), "r"(a3), "l"(db), "r"(sd));
}
__device__ __forceinline__ void wg_rs64(float (&d)[32], uint32_t a0, uint32_t a1, uint32_t a2, uint32_t a3, uint64_t db, int sd) {
  asm volatile("{\n.reg .pred p;\nsetp.ne.b32 p, %37, 0;\n"
  "wgmma.mma_async.sync.aligned.m64n64k16.f32.bf16.bf16 {%0, %1, %2, %3, %4, %5, %6, %7, %8, %9, %10, %11, %12, %13, %14, %15, %16, %17, %18, %19, %20, %21, %22, %23, %24, %25, %26, %27, %28, %29, %30, %31}, {%32, %33, %34, %35}, %36, p, 1, 1, 1;\n}\n"
  : "+f"(d[0]), "+f"(d[1]), "+f"(d[2]), "+f"(d[3]), "+f"(d[4]), "+f"(d[5]), "+f"(d[6]), "+f"(d[7]), "+f"(d[8]), "+f"(d[9]), "+f"(d[10]), "+f"(d[11]), "+f"(d[12]), "+f"(d[13]), "+f"(d[14]), "+f"(d[15]), "+f"(d[16]), "+f"(d[17]), "+f"(d[18]), "+f"(d[19]), "+f"(d[20]), "+f"(d[21]), "+f"(d[22]), "+f"(d[23]), "+f"(d[24]), "+f"(d[25]), "+f"(d[26]), "+f"(d[27]), "+f"(d[28]), "+f"(d[29]), "+f"(d[30]), "+f"(d[31]) : "r"(a0), "r"(a1), "r"(a2), "r"(a3), "l"(db), "r"(sd));
}

__device__ __forceinline__ uint32_t kv_addr(int i) {
  return 94208u + KVB * (uint32_t)((0x103254u >> (4 * i)) & 15u);
}
__device__ __forceinline__ uint32_t w1b_addr(int s) {
  return (s == 3 || s == 4) ? (uint32_t)(s - 3) * 35840u : 102400u + (uint32_t)(s >= 5 ? s - 5 : s) * 35840u;
}
__device__ __forceinline__ void stg128(void* p, uint32_t a, uint32_t b, uint32_t c, uint32_t d) {
  asm volatile("st.relaxed.gpu.global.v4.u32 [%0], {%1,%2,%3,%4};" ::"l"(p), "r"(a), "r"(b), "r"(c), "r"(d) : "memory");
}
__device__ __forceinline__ void stg32(void* p, uint32_t a) { asm volatile("st.global.u32 [%0], %1;" ::"l"(p), "r"(a) : "memory"); }
__device__ __forceinline__ void ld_tile(uint32_t (&a)[20], const uint8_t* p, int c, int i) {
  p += ((c + i) & 7) * 10240;
#pragma unroll
  for (int k = 0; k < 5; k++)
    asm volatile("ld.relaxed.gpu.global.v4.u32 {%0,%1,%2,%3}, [%4];" : "=r"(a[4 * k]), "=r"(a[4 * k + 1]), "=r"(a[4 * k + 2]), "=r"(a[4 * k + 3]) : "l"(p + k * 512) : "memory");
}
__device__ __forceinline__ uint32_t tag16(uint32_t v, uint32_t tag) { return (v & ~TAGM) | tag; }
__device__ __forceinline__ float tag32(float v, uint32_t ep) { return __uint_as_float((__float_as_uint(v) & ~3u) | ep); }
__device__ __forceinline__ void fix_tile(uint32_t (&a)[20], const uint8_t* p, int c, int i, uint32_t tag) {
  uint32_t n = 0;
  while (__any_sync(0xffffffffu, (((a[0] ^ tag) | (a[4] ^ tag) | (a[8] ^ tag) | (a[12] ^ tag) | (a[16] ^ tag)) & TAGM) != 0u) && ++n < SPIN_MAX) ld_tile(a, p, c, i);
}
__device__ __forceinline__ bool tile_bad(const uint32_t (&a)[20], uint32_t tag) { return (((a[0] ^ tag) | (a[4] ^ tag) | (a[8] ^ tag) | (a[12] ^ tag) | (a[16] ^ tag)) & TAGM) != 0u; }
__device__ __forceinline__ void fix_tile2(uint32_t (&a)[20], uint32_t (&b)[20], const uint8_t* p, int c, int i, uint32_t tag) {
  uint32_t n = 0;
  while (__any_sync(0xffffffffu, (((a[0] ^ tag) | (a[4] ^ tag) | (a[8] ^ tag) | (a[12] ^ tag) | (a[16] ^ tag) | (b[0] ^ tag) | (b[4] ^ tag) | (b[8] ^ tag) | (b[12] ^ tag) | (b[16] ^ tag)) & TAGM) != 0u) &&
         ++n < SPIN_MAX) {
    ld_tile(a, p, c, i);
    ld_tile(b, p, c, i + 1);
  }
}
__device__ __forceinline__ void probe_wait(uint32_t& ready, int i, const void* p, uint32_t tag) {
  uint32_t n = 0;
  while (!((ready >> i) & 1u) && ++n < SPIN_MAX) ready = __ballot_sync(0xffffffffu, ldcg32(p) == tag);
}
__device__ __forceinline__ void probe_async(uint32_t& ready, int i, uint32_t slot, int w, const uint32_t* p, bool on, uint32_t tag) {
  uint32_t n = w;
  while (!((ready >> i) & 1u) && n < 1024u) {
    uint32_t v;
    if (on && !(n & (APR - 1))) asm volatile("cp.async.cg.shared.global [%0], [%1], 16;" ::"r"(slot), "l"(p) : "memory");
    asm volatile("ld.volatile.shared.u32 %0, [%1];" : "=r"(v) : "r"(slot + w * 4) : "memory");
    ready = __ballot_sync(0xffffffffu, v == tag);
    n++;
  }
  probe_wait(ready, i, p + w, tag);
}
__device__ __forceinline__ void gather8(uint8_t* dst, const float* p, int stride, uint32_t ep, bool on) {
  uint4 v[8];
  uint32_t n = 0, bad;
  do {
    bad = 0;
#pragma unroll
    for (int i = 0; i < 8; i++) v[i] = ldcg128(p + i * stride);
#pragma unroll
    for (int i = 0; i < 8; i++) bad |= (v[i].x ^ ep) | (v[i].w ^ ep);
  } while (__any_sync(0xffffffffu, (bad & 3u) != 0u) && ++n < SPIN_MAX);
  float4 s = make_float4(0.f, 0.f, 0.f, 0.f);
#pragma unroll
  for (int i = 0; i < 8; i++) { s.x += __uint_as_float(v[i].x); s.y += __uint_as_float(v[i].y); s.z += __uint_as_float(v[i].z); s.w += __uint_as_float(v[i].w); }
  if (on) *reinterpret_cast<float4*>(dst) = s;
}

__device__ __forceinline__ uint64_t desc2(uint32_t lo, uint32_t hi) { uint64_t d; asm("mov.b64 %0, {%1, %2};" : "=l"(d) : "r"(lo), "r"(hi)); return d; }
template <int H>
__device__ __forceinline__ void qk_issue(float (&s)[32], const uint32_t (&q)[24], uint32_t m0, uint32_t m1, uint32_t kd) {
  constexpr int J0 = (H == 0) ? 0 : (H == 1) ? 2 : (H == 2) ? 5 : 7;
  wg_rs64k(s, q[H * 6 + 0], q[H * 6 + 1], q[H * 6 + 2], q[H * 6 + 3], desc2(kd + (0x400000u + J0 * 64), 8u), 0);
  wg_rs64k(s, q[H * 6 + 4], q[H * 6 + 5], m0, m1, desc2(kd + (((10 - J0) * 64u << 16) + (J0 + 2) * 64), 8u), 1);
}
template <int H, int FIRST>
__device__ __forceinline__ void pv_issue(float (&o)[12], const uint32_t (&p)[16], uint32_t kd) {
  if (FIRST && H == 3) return;
#pragma unroll
  for (int i = 0; i < 4; i++)
    wg_rs24(o, p[4 * i], p[4 * i + 1], p[4 * i + 2], p[4 * i + 3], desc2(kd + (0x80000u + 640 + 3 * H * 64 + i * 16), 64u), i || !FIRST);
}
template <int KIND>
__device__ __forceinline__ void sm_exp(const float (&s)[32], uint32_t (&p)[16], const uint32_t (&nk)[8], int w) {
#define EXU(i) pack2(ex2(s[2 * (i)]), ex2(s[2 * (i) + 1]))
  if (KIND == 0) {
#pragma unroll
    for (int i = 0; i < 16; i++) p[i] = EXU(i);
  } else {
#pragma unroll
    for (int u = 1; u < 4; u++) {
      const int i0 = KIND == 1 ? 2 * u : 15 - 2 * u, i1 = KIND == 1 ? 17 - 2 * u : 2 * u - 2;
      const uint32_t e = pack2(ex2(w >= u ? s[2 * i0] : s[2 * i1]), ex2(w >= u ? s[2 * i0 + 1] : s[2 * i1 + 1]));
      p[i0] = e & (KIND == 1 ? ~nk[i0 >> 1] : nk[i0 >> 1]);
      p[i1] = e & (KIND == 1 ? ~nk[i1 >> 1] : nk[i1 >> 1]);
    }
    if (KIND == 1) {
      p[0] = EXU(0) & ~nk[0];
      p[9] = EXU(9) & ~nk[4];
    } else {
      p[6] = EXU(6) & nk[3];
      p[15] = EXU(15) & nk[7];
    }
#pragma unroll
    for (int t = 0; t < 4; t++) {
      p[2 * t + (KIND == 1 ? 1 : 8)] = EXU(2 * t + (KIND == 1 ? 1 : 8));
      p[2 * t + (KIND == 1 ? 8 : 1)] = 0u;
    }
  }
#pragma unroll
  for (int i = 0; i < 16; i++) asm volatile("" : "+r"(p[i])::"memory");
}
__device__ __forceinline__ void mma16816(float* d, uint32_t a0, uint32_t a1, uint32_t a2, uint32_t a3, uint32_t b0, uint32_t b1) {
  asm volatile("mma.sync.aligned.m16n8k16.row.col.f32.bf16.bf16.f32 {%0,%1,%2,%3}, {%4,%5,%6,%7}, {%8,%9}, {%0,%1,%2,%3};"
               : "+f"(d[0]), "+f"(d[1]), "+f"(d[2]), "+f"(d[3]) : "r"(a0), "r"(a1), "r"(a2), "r"(a3), "r"(b0), "r"(b1));
}
__device__ __forceinline__ void safe_head(float (&o)[12], const uint32_t (&q)[6], int H, const uint8_t* kv, uint32_t seq, int nit, int d0, int d1, int tq, uint32_t tag) {
  const int J0 = (5 * H) >> 1;
  float m0 = -INFINITY, m1 = -INFINITY;
#pragma unroll
  for (int i = 0; i < 12; i++) o[i] = 0.f;
#pragma unroll 1
  for (int st = 0; st < 4 * nit; st++) {
    const uint8_t* a = kv + (size_t)((seq >> (st & 28)) & 15) * (8 * KVB) + (st & 3) * 256;
    uint32_t b[12], bad, n = 0;
    do {
      bad = 0;
#pragma unroll
      for (int i = 0; i < 12; i++) {
        b[i] = ldcg32(a + ((i < 6 ? J0 : 7 + 3 * H) + (i >> 1)) * 1024 + (i & 1) * 128);
        bad |= b[i] ^ tag;
      }
    } while (__any_sync(0xffffffffu, tq == 1 && (bad & TAGM) != 0u) && ++n < SPIN_MAX);
    float s[8];
#pragma unroll
    for (int i = 0; i < 8; i++) s[i] = 0.f;
#pragma unroll
    for (int t = 0; t < 2; t++) {
      mma16816(&s[4 * t], q[0], q[1], q[2], q[3], b[t], b[2 + t]);
      mma16816(&s[4 * t], q[4], q[5], 0u, 0u, b[4 + t], 0u);
    }
    if (st < 4 || st >= 16) {
#pragma unroll
      for (int i = 0; i < 8; i++)
        if (((st & 3) * 16 + (i >> 2) * 8 + (i & 1) <= ((i & 2) ? d1 : d0)) != (st < 4)) s[i] = -INFINITY;
    }
    float n0 = fmaxf(fmaxf(s[0], s[1]), fmaxf(s[4], s[5])), n1 = fmaxf(fmaxf(s[2], s[3]), fmaxf(s[6], s[7]));
    n0 = fmaxf(n0, __shfl_xor_sync(0xffffffffu, n0, 1));
    n1 = fmaxf(n1, __shfl_xor_sync(0xffffffffu, n1, 1));
    n0 = fmaxf(m0, fmaxf(n0, __shfl_xor_sync(0xffffffffu, n0, 2)));
    n1 = fmaxf(m1, fmaxf(n1, __shfl_xor_sync(0xffffffffu, n1, 2)));
    const float al0 = ex2(m0 - n0), al1 = ex2(m1 - n1);
    m0 = n0;
    m1 = n1;
    const uint32_t p0 = pack2(ex2(s[0] - n0), ex2(s[1] - n0)), p1 = pack2(ex2(s[2] - n1), ex2(s[3] - n1));
    const uint32_t p2 = pack2(ex2(s[4] - n0), ex2(s[5] - n0)), p3 = pack2(ex2(s[6] - n1), ex2(s[7] - n1));
#pragma unroll
    for (int i = 6; i < 12; i++) asm volatile("movmatrix.sync.aligned.m8n8.trans.b16 %0, %0;" : "+r"(b[i]));
#pragma unroll
    for (int t = 0; t < 3; t++) {
      o[4 * t] *= al0; o[4 * t + 1] *= al0; o[4 * t + 2] *= al1; o[4 * t + 3] *= al1;
      mma16816(&o[4 * t], p0, p1, p2, p3, b[6 + 2 * t], b[7 + 2 * t]);
    }
  }
}
#define ATT_STEP(KIND, HQ, sq, kq, HP, op, pp, kv, sc, pc, W) do { \
  WG_FENCE(); qk_issue<HQ>(sq, q, qm[2 * HQ], qm[2 * HQ + 1], kq); WG_COMMIT(); WG_WAIT(1); pv_issue<HP, KIND == 1>(op, pp, kv); WG_COMMIT(); \
  sm_exp<KIND>(sc, pc, nk, w); WG_WAIT(W); reg_fence(sq); } while (0)
__device__ __forceinline__ uint32_t bmul2(uint32_t a, uint32_t b) { uint32_t d; asm("mul.rn.bf16x2 %0, %1, %2;" : "=r"(d) : "r"(a), "r"(b)); return d; }
__device__ __forceinline__ uint32_t badd2(uint32_t a, uint32_t b) { uint32_t d; asm("add.rn.bf16x2 %0, %1, %2;" : "=r"(d) : "r"(a), "r"(b)); return d; }
__device__ __forceinline__ uint32_t bfma2(uint32_t a, uint32_t b, uint32_t c) { uint32_t d; asm("fma.rn.bf16x2 %0, %1, %2, %3;" : "=r"(d) : "r"(a), "r"(b), "r"(c)); return d; }

__global__ void __cluster_dims__(2, 1, 1) __launch_bounds__(384, 1) fused_block_kernel(const __grid_constant__ Params P) {
  extern __shared__ __align__(1024) uint8_t smem[];
  const uint32_t sb = s2u(smem);
  const int tid = threadIdx.x, lane = tid & 31, warp = __shfl_sync(0xffffffffu, tid >> 5, 0);
  const uint32_t bars = sb + OFF_MISC;
#define BAR(i) (bars + 8u * (uint32_t)(i))
#define TP(i)
  if (tid == 288) {
#pragma unroll
    for (int u = 0; u < 6; u++) mbar_init(BAR(u), 1);
    asm volatile("fence.mbarrier_init.release.cluster;" ::: "memory");
  }
  __syncwarp();
  asm volatile("barrier.cluster.arrive.relaxed.aligned;" ::: "memory");
  TP(0);
  const uint32_t rank = blockIdx.x & 1;
  const uint32_t mp = P.map[blockIdx.x >> 3] >> ((blockIdx.x & 6) * 4);
  const int c = mp & 7, rb = (int)(((mp >> 2) & 14) + rank);
  const int tile = rb * 8 + c;
  const int mainch = (c * 5) >> 1, leftch = c * 5 + 4;
  const CUtensorMap* mWqM = &P.mWqM[c & 1];
  const int kb0 = (5 * (rb >> 1)) >> 2;
  if (lane == 0 && (warp >> 1) != 4) {
    const int j = warp < 8 ? warp + 3 : warp - 9;
    const int cnt = (int)(0x4a108208108421ull >> (5 * j)) & 31;
#pragma unroll
    for (int u = 0; u < 6; u++) mbar_init(BAR(j * 6 + u), cnt);
    asm volatile("fence.mbarrier_init.release.cluster;" ::: "memory");
  }
  __syncwarp();
  TP(1);
  if (warp >= 8) asm volatile("setmaxnreg.dec.sync.aligned.u32 56;");
  TP(2);
  if (warp > 8) {
    asm volatile("bar.arrive 1, 384;" ::: "memory");
    if (lane == 0) {
      if (warp == 9) {
        mbar_expect(BAR(B_QFULL), QST);
        tma2d(sb, &P.mX, kb0 * 64, rb * 128, BAR(B_QFULL));
      } else {
        asm volatile("prefetch.tensormap [%0];" ::"l"(warp == 10 ? mWqM : &P.mWqL) : "memory");
      }
    }
    __syncwarp();
    asm volatile("bar.sync 2, 128;" ::: "memory");
  } else {
    asm volatile("bar.sync 1, 384;" ::: "memory");
  }
  TP(3);
  if (tid < 208) {
    const uint8_t* pp = tid < 192 ? reinterpret_cast<const uint8_t*>(P.wqkv) + (size_t)(kb0 * 64 + (int)rank * 32 + (tid & 31)) * 3840 + (tid >> 6) * 1280 + c * 160 + (tid & 32) * 4
                                  : reinterpret_cast<const uint8_t*>(P.x) + (size_t)(rb * 128 + c * 16 + tid - 192) * 1280 + kb0 * 128;
    l2_prefetch(pp);
  }
  if (warp == 8) {
    asm volatile("bar.arrive 2, 128;\nbarrier.cluster.wait.acquire.aligned;" ::: "memory");
    TP(4);
    if (lane == 0) {
#pragma unroll 1
      for (int kt = 0; kt < 4; kt++) {
        const uint32_t a = sb + kt * QST, fb = BAR(B_QFULL + kt);
        const int k0 = (kb0 + kt < 10 ? kb0 + kt : kb0 + kt - 10) * 64;
        if (kt) mbar_expect(fb, QST);
        tma4d_mc(a + 16384 + rank * 12288, mWqM, 0, k0 + rank * 32, mainch, 0, fb);
        tma4d_mc(a + 40960 + rank * 3072, &P.mWqL, 0, k0 + rank * 32, leftch, 0, fb);
        if (kt) tma2d(a, &P.mX, k0, rb * 128, fb);
        if (kt == 0) TP(5);
      }
      mbar_expect(BAR(B_XROW), 20480);
      bulk_load(sb + OFF_XROW, reinterpret_cast<const uint8_t*>(P.x) + (size_t)(rb * 128 + c * 16) * 1280, 20480, BAR(B_XROW));
    } else if (lane < 4) mbar_arrive(BAR(B_XROW));
    __syncwarp();
    STAMPW(9);
  }
  const int sc = (27 * c + 3) >> 2;

  if (warp >= 8) {
    const uint32_t epoch = __shfl_sync(0xffffffffu, ldcg32(&g_epoch[tile * 32 + lane]), 0) + 1u;
    const uint32_t ep = epoch & 3u, tag = (epoch & 1u) | ((epoch & 2u) << 15);
    if (warp == 8) {
      if (lane == 0) {
#pragma unroll 1
        for (int kt = 4; kt < 10; kt++) {
          const int st = kt & 3;
          mbar_wait(BAR(B_QEMPTY + st), ((kt >> 2) - 1) & 1);
          const uint32_t a = sb + st * QST, fb = BAR(B_QFULL + st);
          const int k0 = (kb0 + kt < 10 ? kb0 + kt : kb0 + kt - 10) * 64;
          mbar_expect(fb, QST);
          tma4d_mc(a + 16384 + rank * 12288, mWqM, 0, k0 + rank * 32, mainch, 0, fb);
          tma4d_mc(a + 40960 + rank * 3072, &P.mWqL, 0, k0 + rank * 32, leftch, 0, fb);
          tma2d(a, &P.mX, k0, rb * 128, fb);
        }
        l2_prefetch_bulk(reinterpret_cast<const uint8_t*>(P.wo) + tile * 6400, 6400);
        l2_prefetch_bulk(reinterpret_cast<const uint8_t*>(P.w1) + tile * 17280, 17280);
        l2_prefetch_bulk(reinterpret_cast<const uint8_t*>(P.w2) + tile * 17280, 17280);
        const CUtensorMap* mW1 = rank ? &P.mW1b : &P.mW1a;
        asm volatile("prefetch.tensormap [%0];" ::"l"(&P.mWo) : "memory");
        asm volatile("prefetch.tensormap [%0];" ::"l"(mW1) : "memory");
        asm volatile("prefetch.tensormap [%0];" ::"l"(&P.mW2) : "memory");
        mbar_wait(BAR(B_QEMPTY + 1), 0);
        if (rb) mbar_wait(BAR(B_KVFULL + 3), 0);
        mbar_expect(BAR(B_WOB), 89600);
#pragma unroll 1
        for (int i = 0; i < 4 - (int)rank; i++) {
          const int pos = rank * 4 + i;
          tma3d_mc(sb + OFF_WOB + pos * 12800, &P.mWo, 0, ((c + pos) & 7) * 80, c * 5, BAR(B_WOB));
        }
#pragma unroll 1
        for (int s = 0; s < 8; s++) {
          if (s == 0) {
            mbar_wait(BAR(B_ATT2), 0);
            mbar_expect(BAR(B_WOB7), 12800);
            if (rank) tma3d_mc(sb + OFF_WOB + 7 * 12800, &P.mWo, 0, ((c + 7) & 7) * 80, c * 5, BAR(B_WOB7));
            mbar_wait(BAR(B_OL1), 0);
          } else if (s == 1) mbar_wait(BAR(B_ATT4), 0);
          else if (s == 3 || s == 4) mbar_wait(BAR(s == 3 ? B_WODP : B_WODP2), 0);
          else if (s >= 5) mbar_wait(BAR(B_BEMPTY + s - 5), 0);
          if (s == DLY) mbar_wait(BAR(B_BEMPTY), 0);
          const uint32_t fb = BAR(B_BFULL + s);
          mbar_expect(fb, 35840);
          tma3d_mc(sb + w1b_addr(s) + rank * 20480, mW1, 0, ((c + s) & 7) * 80, sc + rank * 4, fb);
        }
#pragma unroll 1
        for (int u = 0; u < 10; u++) {
          if (u < 6) mbar_wait(BAR(B_BEMPTY + ((0x665443u >> (4 * u)) & 7)), 0);
          else mbar_wait(BAR(B_QEMPTY + 2 + (u & 3)), (u >> 3) & 1);
          const uint32_t fb = BAR(u < 5 ? B_W2FULL + u : B_BFULL - 5 + u);
          mbar_expect(fb, 28672);
          tma2d_mc(sb + (u < 6 ? u : u - 6) * 28672 + rank * 14336, &P.mW2, (c + u < 10 ? c + u : c + u - 10) * 64, sc * 32 + rank * 112, fb);
        }
      }
      __syncwarp();
    } else {
      float2* xst = &g_xstat[tile * 24 + (warp - 9) * 8 + (lane & 3) * 2 + (lane >> 4)];
      if (XRST && (lane & 15) < 4) *xst = make_float2(0.f, tag32(0.f, ep ^ 1u));
      if (warp == 11) {
        mbar_wait(BAR(B_PRE), 0);
        if (lane < 30) {
          float4 a = make_float4(0.f, 0.f, 0.f, 0.f);
#pragma unroll 4
          for (int i = 0; i < 16; i++) {
            const float4 v = *reinterpret_cast<const float4*>(smem + OFF_PRE + i * 512 + lane * 16);
            a.x += v.x; a.y += v.y; a.z += v.z; a.w += v.w;
          }
          *reinterpret_cast<float4*>(&g_csq[((rb >> 1) * 8 + c) * 240 + rank * 120 + lane * 4]) = make_float4(tag32(a.x, ep), tag32(a.y, ep), tag32(a.z, ep), tag32(a.w, ep));
        }
        __syncwarp();
        STAMPW(0);
      }
      mbar_wait(BAR(B_XROW), 0);
      if (warp == 9) STAMPW(8);
      {
        float s3[3] = {0.f, 0.f, 0.f}, m3[3] = {0.f, 0.f, 0.f}, sh[3];
        const uint32_t xb = sb + OFF_XROW + ((warp - 9) * 2 + (lane >> 4)) * 1280, x2 = warp == 11 ? 7680 : 15360;
#pragma unroll
        for (int p = 0; p < 3; p++) {
          uint32_t u0;
          asm volatile("ld.shared.u32 %0, [%1];" : "=r"(u0) : "r"(xb + (p < 2 ? p * 7680 : x2)) : "memory");
          sh[p] = bf_lo(u0);
        }
#pragma unroll 1
        for (int i = 0; i < 5; i++) {
          uint32_t u[12];
#pragma unroll
          for (int p = 0; p < 3; p++)
            asm volatile("ld.shared.v4.u32 {%0,%1,%2,%3}, [%4];" : "=r"(u[4 * p]), "=r"(u[4 * p + 1]), "=r"(u[4 * p + 2]), "=r"(u[4 * p + 3])
                         : "r"(xb + (p < 2 ? p * 7680 : x2) + (lane & 15) * 16 + i * 256) : "memory");
#define XS_ACC(j) do { \
            const float d0 = bf_lo(u[j]) - sh[(j) >> 2], d1 = bf_hi(u[j]) - sh[(j) >> 2]; \
            s3[(j) >> 2] += d0 + d1; \
            m3[(j) >> 2] = fmaf(d1, d1, fmaf(d0, d0, m3[(j) >> 2])); } while (0)
#pragma unroll
          for (int j = 0; j < 8; j++) XS_ACC(j);
          if (warp != 11) {
            asm volatile("" ::: "memory");
#pragma unroll
            for (int j = 8; j < 12; j++) XS_ACC(j);
          }
        }
#pragma unroll
        for (int o = 8; o; o >>= 1)
#pragma unroll
          for (int i = 0; i < 3; i++) {
            s3[i] += __shfl_xor_sync(0xffffffffu, s3[i], o);
            m3[i] += __shfl_xor_sync(0xffffffffu, m3[i], o);
          }
        const int p = lane & 15;
        const float s = (p == 0 ? s3[0] : p == 1 ? s3[1] : s3[2]) * (1.f / 640.f), m2 = (p == 0 ? m3[0] : p == 1 ? m3[1] : m3[2]) * (1.f / 640.f);
        if (p < 4) *xst = make_float2((p == 0 ? sh[0] : p == 1 ? sh[1] : sh[2]) + s, tag32(rsqrtf(fmaxf(fmaf(-s, s, m2), 0.f) + 1e-5f), ep));
      }
      if (warp == 9) STAMPW(17);
      if (warp != 11) {
        if (warp == 10) {
          mbar_wait(BAR(B_QEMPTY + 3), 0);
          uint4 v0, v1;
          uint32_t n = 0;
          const float2* xs = &g_xstat[(rb * 8 + (lane >> 3)) * 24 + ((lane & 7) % 3) * 8 + ((lane & 7) / 3) * 2];
          do {
            v0 = ldcg128(xs);
            v1 = ldcg128(xs + 96);
          } while (__any_sync(0xffffffffu, (((v0.y ^ ep) | (v0.w ^ ep) | (v1.y ^ ep) | (v1.w ^ ep)) & 3u) != 0u) && ++n < SPIN_MAX);
          *reinterpret_cast<uint4*>(smem + OFF_XST + lane * 16) = v0;
          *reinterpret_cast<uint4*>(smem + OFF_XST + 512 + lane * 16) = v1;
          __syncwarp();
          if (lane < 2) mbar_arrive(BAR(B_STAT));
          STAMPW(18);
        }
        if (warp == 10 && lane == 0) {
#pragma unroll 1
          for (int i = 0; i < 1 + KVP; i++) {
            if (i < 2) mbar_wait(BAR(B_KVOWN + i), 0);
            const uint32_t off = i ? (uint32_t)(i - 1) * (KVB / KVP) + KVB : 0u;
            asm volatile("cp.async.bulk.wait_group.read 0;\ncp.async.bulk.global.shared::cta.bulk_group [%0], [%1], %2;\ncp.async.bulk.commit_group;"
                         ::"l"(g_kv + (size_t)(rb * 16 + c) * KVB + (i ? 7 * KVB + off : 0u)), "r"(sb + kv_addr(4) + off), "r"(i ? KVB / KVP : KVB) : "memory");
          }
          asm volatile("cp.async.bulk.wait_group.read 0;" ::: "memory");
          mbar_arrive_pair(BAR(B_ATT2));
          STAMPW(6);
        }
        __syncwarp();
      }
      if (warp != 10) {
        const int u = (warp - 9) * 16 + lane;
        mbar_wait(BAR(B_QEMPTY + 3), 0);
        gather8(smem + OFF_CS + u * 16, g_csq + c * 240 + min(u, 59) * 4, 1920, ep, u < 60);
        __syncwarp();
        if (lane == 0) mbar_arrive(BAR(B_STAT));
        if (warp == 9) STAMPW(16);
        mbar_wait(BAR(B_QEMPTY + 1), 1);
      }
      if (warp == 9) STAMPW(19);
#pragma unroll 1
      for (int bi = warp == 9 ? 2 : warp == 10 ? 3 : 1; bi >= 0; bi -= (warp == 9 ? 2 : 4)) {
        const int blk = 2 * rb - 4 + bi;
        if (blk < 0) continue;
        const uint8_t* src = g_kv + (size_t)(blk * 8 + c) * KVB;
        const uint32_t dst = sb + kv_addr(bi);
        uint32_t n = 0, ph = 0;
        while (!__all_sync(0xffffffffu, ((ldcg32(src + lane * 704 + 692) ^ tag) & TAGM) == 0u) && ++n < SPIN_MAX) {}
        if (warp == 9 && bi == 2) STAMPW(3);
        mbar_wait(BAR(B_QEMPTY + 1), 0);
        while (true) {
          if (lane == 0) {
            mbar_expect(BAR(B_KVLAND + bi), KVB);
            bulk_load(dst, src, KVB, BAR(B_KVLAND + bi));
          }
          mbar_wait(BAR(B_KVLAND + bi), ph);
          ph ^= 1u;
          uint32_t bad = 0;
#pragma unroll 11
          for (int i = 0; i < 44; i++) {
            uint32_t v;
            asm volatile("ld.shared.u32 %0, [%1];" : "=r"(v) : "r"(dst + (i * 32 + lane) * 16 + 4) : "memory");
            bad |= v ^ tag;
          }
          if (!__any_sync(0xffffffffu, (bad & TAGM) != 0u) || ++n >= SPIN_MAX) break;
        }
        if (lane == 0) {
          mbar_arrive(BAR(B_KVFULL + bi));
        }
        if (warp == 9 && bi == 2) STAMPW(5);
        if (warp == 10) STAMPW(7);
      }
      __syncwarp();
      asm volatile("barrier.cluster.wait.acquire.aligned;" ::: "memory");
      if (warp == 10) {
        const int l16 = lane & 15, col = sc * 32 + (int)rank * 112 + l16 * 8;
        const uint8_t* wb = reinterpret_cast<const uint8_t*>(P.w1) + (size_t)((rb >> 1) * 80 + (lane >> 4) * 40) * 3456 + (size_t)col * 2;
        float acc[8];
#pragma unroll
        for (int i = 0; i < 8; i++) acc[i] = 0.f;
        if (l16 < 14 && col < 1728) {
#pragma unroll 1
          for (int i = 0; i < 40; i += CSU) {
            uint4 v[CSU];
#pragma unroll
            for (int u = 0; u < CSU; u++) v[u] = __ldg(reinterpret_cast<const uint4*>(wb + (size_t)(i + u) * 3456));
#pragma unroll
            for (int u = 0; u < CSU; u++) {
              acc[0] += bf_lo(v[u].x); acc[1] += bf_hi(v[u].x); acc[2] += bf_lo(v[u].y); acc[3] += bf_hi(v[u].y);
              acc[4] += bf_lo(v[u].z); acc[5] += bf_hi(v[u].z); acc[6] += bf_lo(v[u].w); acc[7] += bf_hi(v[u].w);
            }
          }
        }
        __syncwarp();
#pragma unroll
        for (int i = 0; i < 4; i++) {
          const float o = __shfl_xor_sync(0xffffffffu, lane < 16 ? acc[4 + i] : acc[i], 16);
          acc[i] = tag32((lane < 16 ? acc[i] : acc[4 + i]) + o, ep);
        }
        if (l16 < 14) *reinterpret_cast<float4*>(&g_cs1[((rb >> 1) * 8 + c) * 224 + rank * 112 + l16 * 8 + (lane >> 4) * 4]) = make_float4(acc[0], acc[1], acc[2], acc[3]);
        STAMPW(4);
      } else if (warp == 9) {
#pragma unroll 1
        for (int r = 1; r >= 0; r--) {
          const int cc = (c + 1 + (lane >> 2)) & 7;
          const uint32_t* hp = &g_hint[((rb * 2 + r) * 8 + cc) * HS + (lane & 3)];
          const uint32_t fb = BAR(r ? B_QFULL : B_KVFULL);
          const uint32_t dst = sb + (r ? 102400u : lane < 12 ? 179200u : 107520u) + (lane >> 2) * 10240;
          mbar_wait(BAR(r ? B_ATT2 : B_ATTL), 0);
          mbar_wait(BAR(B_ATT3), 0);
          if (lane < 4) mbar_expect(fb + lane * 8, lane < 3 ? 20480 : 10240);
          uint32_t n = 0, todo = 0x1111111u;
          while (todo) {
            uint32_t ok = __ballot_sync(0xffffffffu, ldcg32(hp) == tag || n >= SPIN_MAX);
            ok &= ok >> 1;
            ok &= (ok >> 2) & todo;
            if (r == 0 && !mbar_test(BAR(B_OL1L))) ok &= 0xfffu;
            if ((ok >> lane) & 1u) bulk_load(dst, g_o + (size_t)(rb * 16 + r * 8 + cc) * 10240, 10240, fb + (lane >> 3) * 8);
            todo &= ~ok;
            if (++n > 2 * SPIN_MAX) break;
          }
        }
      } else if (warp == 11) {
        mbar_wait(BAR(B_ATT3), 0);
#pragma unroll 1
        for (int u = lane; u < 64; u += 32) gather8(smem + OFF_XS + u * 16, g_cs1 + c * 224 + min(u, 55) * 4, 1792, ep, u < 56);
        __syncwarp();
        if (lane == 0) mbar_arrive(BAR(B_CS1));
        STAMPW(1);
      }
    }
    if (warp == 9 || warp == 10) {
      const int r = warp - 9;
      uint32_t* fl = &g_oflag[(rb * 2 + r) * 8];
      mbar_wait(BAR(B_HST + r), 0);
      if (lane == 0) {
        asm volatile("cp.async.bulk.tensor.2d.global.shared::cta.bulk_group [%0, {%2, %3}], [%1];\ncp.async.bulk.commit_group;\ncp.async.bulk.wait_group 0;"
                     ::"l"(&P.mOutH), "r"(sb + OFF_HST + r * 10240), "r"(c * 80), "r"(rb * 128 + r * 64) : "memory");
        asm volatile("fence.proxy.async.global;\nst.release.gpu.global.u32 [%0], %1;" ::"l"(fl + c), "r"(epoch) : "memory");
      }
      __syncwarp();
      uint32_t n = 0;
      while (!__all_sync(0xffffffffu, ld_flag(fl + (lane & 7)) == epoch) && ++n < SPIN_MAX) {}
      if (lane == 0) mbar_arrive(BAR(B_OUTOK + r));
      STAMPW(2);
    } else if (warp == 11) {
      st_flag(&g_epoch[tile * 32 + lane], epoch);
    }
  } else {
    const int r = warp >> 2, w = warp & 3, gq = lane >> 2, tq = lane & 3;
    asm volatile("setmaxnreg.inc.sync.aligned.u32 224;");
    STAMP(4);
    uint32_t ep = ldcg32(&g_epoch[tile * 32 + lane]);
    const int b = rb * 2 + r;
    if (w == 0 && lane < 4) stg128(&g_hint[((lane >> 1) * 256 + b * 8 + c) * 8 + (lane & 1) * 4], ~0u, ~0u, ~0u, ~0u);
    const int row0 = w * 8 + gq, row1 = 56 - w * 8 + gq;
    const int rowm = ((lane & 8) ? 56 - w * 8 : w * 8) + (lane & 7);
    uint32_t q[24], qm[8], tag;
    STAMP(0);
    {
      float accQ[32], accK[64], accL[24];
      uint32_t fa[16], fb[16];
      const uint32_t xa = sb + (uint32_t)(r * 64 + rowm) * 128u + (uint32_t)(((lane >> 4) ^ lane) & 7) * 16u;
#define QKV_DM(kt, k) (mkdesc(sb + ((kt) & 3) * QST + 16384, desc_hi(2048, 512, 2)) + ((k) >> 1) * 768 + ((k) & 1) * 64)
#define QKV_DL(kt, k) (mkdesc(sb + ((kt) & 3) * QST + 40960, desc_hi(1024, 256, 3)) + ((k) >> 1) * 192 + ((k) & 1) * 32)
#define QKV_STEP(f, kt, WQ, REL) do { \
        mbar_wait(BAR(B_QFULL + ((kt) & 3)), ((kt) >> 2) & 1); \
        _Pragma("unroll") for (int k = 0; k < 4; k++) ldsm4(&f[4 * k], (xa ^ (k * 32)) + ((kt) & 3) * QST); \
        WG_FENCE(); \
        _Pragma("unroll") for (int k = 0; k < 4; k++) { \
          wg_rs48(accL, f[4 * k], f[4 * k + 1], f[4 * k + 2], f[4 * k + 3], QKV_DL(kt, k), (kt) | k); \
          if (WQ) wg_rs64(accQ, f[4 * k], f[4 * k + 1], f[4 * k + 2], f[4 * k + 3], QKV_DM(kt, k), (kt) | k); \
          wg_rs128(accK, f[4 * k], f[4 * k + 1], f[4 * k + 2], f[4 * k + 3], QKV_DM(kt, k) + 256, (kt) | k); \
          if (k == 0 || k == 3) WG_COMMIT(); \
          if (k == 0) { WG_WAIT(1); REL; } \
        } } while (0)
#define Q_STEP(f, kt) do { \
        _Pragma("unroll") for (int k = 0; k < 4; k++) wg_rs64(accQ, f[4 * k], f[4 * k + 1], f[4 * k + 2], f[4 * k + 3], QKV_DM(kt, k), 1); \
        WG_COMMIT(); } while (0)
#pragma unroll 1
      for (int kt = 0; kt < 6; kt += 2) {
        QKV_STEP(fa, kt, 1, if (kt && lane == 0) mbar_arrive_pair(BAR(B_QEMPTY + ((kt - 1) & 3))));
        QKV_STEP(fb, kt + 1, 1, if (kt && lane == 0) mbar_arrive_pair(BAR(B_QEMPTY + (kt & 3))));
        if (kt == 0) {
          const int cl = min(lane & 15, 14) + (int)rank * 15, mat = cl / 10, pc = cl - mat * 10;
          const bool mn = pc < 8;
          const int pitch = mn ? 64 : 32;
          const uint8_t* wp = smem + (mn ? 16384 + mat * 4096 + (pc >> 2) * 2048 + ((pc ^ (warp >> 1)) & 3) * 16 : 40960 + mat * 1024 + ((pc ^ (warp >> 2)) & 1) * 16);
          float a[8];
#pragma unroll
          for (int i = 0; i < 8; i++) a[i] = 0.f;
#pragma unroll
          for (int u = 0; u < 5; u++) {
            const int kr = (rb >> 1) * 80 - kb0 * 64 + u * 16;
            const uint4 v = *reinterpret_cast<const uint4*>(wp + (kr >> 6) * QST + ((kr & 16) + (lane >> 4) * 8 + warp + (kr & 32) * (mn ? 6 : 3)) * pitch);
            a[0] += bf_lo(v.x); a[1] += bf_hi(v.x); a[2] += bf_lo(v.y); a[3] += bf_hi(v.y);
            a[4] += bf_lo(v.z); a[5] += bf_hi(v.z); a[6] += bf_lo(v.w); a[7] += bf_hi(v.w);
          }
          float4* dst = reinterpret_cast<float4*>(smem + OFF_PRE + warp * 1024 + lane * 32);
          dst[0] = make_float4(a[0], a[1], a[2], a[3]);
          dst[1] = make_float4(a[4], a[5], a[6], a[7]);
          __syncwarp();
          if (lane == 0) {
            mbar_arrive(BAR(B_PRE));
            mbar_arrive_pair(BAR(B_QEMPTY));
          }
          STAMP(5);
        } else if (kt == 4) {
          asm volatile("barrier.cluster.wait.acquire.aligned;" ::: "memory");
        }
      }
      uint32_t fc[16];
      QKV_STEP(fa, 6, 1, if (lane == 0) mbar_arrive_pair(BAR(B_QEMPTY + 1)));
      QKV_STEP(fb, 7, 0, if (lane == 0) mbar_arrive(BAR(B_Q23)));
      if (r) mbar_wait(BAR(B_XROW), 1);
      QKV_STEP(fa, 8, 0, );
      QKV_STEP(fc, 9, 0, if (!r && lane == 0) mbar_arrive(BAR(B_XROW)));
      ep = (__shfl_sync(0xffffffffu, ep, 0) + 1u) & 3u;
      tag = (ep & 1u) | ((ep & 2u) << 15);
      mbar_wait(BAR(B_STAT), 0);
      const float2 s0 = lds64f(sb + OFF_XST + (r * 64 + row0) * 8), s1 = lds64f(sb + OFF_XST + (r * 64 + row1) * 8);
      mbar_wait(BAR(B_Q23), 0);
      WG_WAIT(0);
      reg_fence(accK); reg_fence(accL);
      STAMP(2);
      const uint32_t km = tq == 1 ? ~TAGM : 0xffffffffu, kt1 = tq == 1 ? tag : 0u;
      const uint32_t csb = sb + OFF_CS + tq * 8;
      const uint32_t kvo = sb + kv_addr(4 + r) + (uint32_t)rowm * 16u + (uint32_t)(lane >> 4) * 1024u;
      const float qs = 0.22360679774997896f * 1.4426950408889634f;
      const bool lo = tq < 2;
      uint32_t qj[20], kj[20];
#define QKV_OUT(mat) do { \
        const float r0 = mat == 0 ? s0.y * qs : s0.y, r1 = mat == 0 ? s1.y * qs : s1.y; \
        const float n0 = -s0.x * r0, n1 = -s1.x * r1; \
        _Pragma("unroll") for (int t = 0; t < 10; t++) { \
          const float* a = t >= 8 ? &accL[(mat * 2 + t - 8) * 4] : mat ? &accK[(mat * 8 - 8 + t) * 4] : &accQ[t * 4]; \
          const float2 cs = lds64f(csb + mat * 320 + t * 32); \
          qj[2 * t] = pack2(fmaf(a[0], r0, cs.x * n0), fmaf(a[1], r0, cs.y * n0)); \
          qj[2 * t + 1] = pack2(fmaf(a[2], r1, cs.x * n1), fmaf(a[3], r1, cs.y * n1)); \
        } } while (0)
#define KV_OUT() do { \
        QKV_OUT(1); \
        _Pragma("unroll") for (int i = 0; i < 20; i++) kj[i] = (qj[i] & km) | kt1; \
        _Pragma("unroll") for (int t = 0; t < 10; t += 2) stsm4(kvo + t * 1024, kj[2 * t], kj[2 * t + 1], kj[2 * t + 2], kj[2 * t + 3]); \
        QKV_OUT(2); \
          \
        const uint32_t one = (tq & 1) ? 0u : 0x3f80u; \
        uint32_t vv[24]; \
        _Pragma("unroll") for (int hp = 0; hp < 2; hp++) { \
          const int j = hp * 10; \
          _Pragma("unroll") for (int i = 0; i < 4; i++) { vv[hp * 12 + i] = qj[j + i]; vv[hp * 12 + 8 + i] = qj[j + 6 + i]; } \
          vv[hp * 12 + 4] = lo ? qj[j + 4] : one; vv[hp * 12 + 5] = lo ? qj[j + 5] : one; \
          vv[hp * 12 + 6] = lo ? one : qj[j + 4]; vv[hp * 12 + 7] = lo ? one : qj[j + 5]; \
        } \
        _Pragma("unroll") for (int i = 0; i < 24; i++) vv[i] = (vv[i] & km) | kt1; \
        _Pragma("unroll") for (int t = 0; t < 6; t++) stsm4(kvo + 10240 + t * 2048, vv[4 * t], vv[4 * t + 1], vv[4 * t + 2], vv[4 * t + 3]); \
      } while (0)
      KV_OUT();
      fence_async_smem();
      __syncwarp();
      if (lane == 0) mbar_arrive(BAR(B_KVOWN + r));
      mbar_wait(BAR(B_STAT), 0);
      WG_FENCE();
      Q_STEP(fb, 7);
      Q_STEP(fa, 8);
      Q_STEP(fc, 9);
      WG_WAIT(0);
      reg_fence(accQ);
      if (lane == 0) mbar_arrive_pair(BAR(B_QEMPTY + 1));
      STAMP(1);
      QKV_OUT(0);
#pragma unroll
      for (int hp = 0; hp < 2; hp++) {
        const int j = hp * 10;
        q[hp * 12 + 0] = qj[j + 0]; q[hp * 12 + 1] = qj[j + 1]; q[hp * 12 + 2] = qj[j + 2]; q[hp * 12 + 3] = qj[j + 3];
        q[hp * 12 + 4] = lo ? qj[j + 4] : 0u; q[hp * 12 + 5] = lo ? qj[j + 5] : 0u;
        q[hp * 12 + 6] = lo ? 0u : qj[j + 4]; q[hp * 12 + 7] = lo ? 0u : qj[j + 5];
        q[hp * 12 + 8] = qj[j + 6]; q[hp * 12 + 9] = qj[j + 7]; q[hp * 12 + 10] = qj[j + 8]; q[hp * 12 + 11] = qj[j + 9];
      }
#pragma unroll
      for (int h = 0; h < 4; h++) {
        const int j = (h >> 1) * 10 + (h & 1) * 4;
        const uint32_t d0 = bfma2(q[6 * h + 4], kj[j + 4], bfma2(q[6 * h + 2], kj[j + 2], bmul2(q[6 * h], kj[j])));
        const uint32_t d1 = bfma2(q[6 * h + 5], kj[j + 5], bfma2(q[6 * h + 3], kj[j + 3], bmul2(q[6 * h + 1], kj[j + 1])));
        uint32_t u = badd2(__byte_perm(d0, d1, 0x5410), __byte_perm(d0, d1, 0x7632));
        u = badd2(u, __shfl_xor_sync(0xffffffffu, u, 1));
        u = badd2(u, __shfl_xor_sync(0xffffffffu, u, 2));
        u = tq == 2 ? u ^ 0x80008000u : 0u;
        qm[2 * h] = u & 0xffffu;
        qm[2 * h + 1] = u >> 16;
        asm volatile("" : "+r"(qm[2 * h]), "+r"(qm[2 * h + 1]));
      }
    }
    STAMP(3);
    uint32_t x0[20];
    {
      float o0[12], o1[12], o2[12], o3[12];
#pragma unroll
      for (int i = 0; i < 12; i++) o3[i] = 0.f;
      reg_fence(o3);
      float s0[32], s1[32];
      uint32_t p0[16], p1[16];
      uint32_t nk[8];
#pragma unroll
      for (int t = 0; t < 8; t++) asm("shl.b32 %0, %1, %2;" : "=r"(nk[t]) : "r"(0xffffffffu), "r"(max(((t < 4 ? row0 : row1) - 2 * tq - 8 * t + 1) * 16, 0)));
      const uint32_t seq = r ? 0x13245u : 0x01324u;
      const int nit = rb >= 2 ? 5 : 2 * rb + 1 + r;
      mbar_wait(BAR(B_KVOWN + r), 0);
      uint32_t kb = ((sb + kv_addr(4 + r)) & 0x3FFFF) >> 4, kp = kb;
      WG_FENCE();
      qk_issue<0>(s0, q, qm[0], qm[1], kb);
      WG_COMMIT();
      WG_WAIT(0);
      reg_fence(s0);
#define ATT_ITER(KIND) do { \
        ATT_STEP(KIND, 1, s1, kb, 3, o3, p1, kp, s0, p0, 1);     \
        ATT_STEP(KIND, 2, s0, kb, 0, o0, p0, kb, s1, p1, 1); \
        if (it == 2 && lane == 0) mbar_arrive_pair(BAR(B_ATT2));     \
        if (it == 3 + r && lane < 2) mbar_arrive(BAR(B_ATT3)); \
        ATT_STEP(KIND, 3, s1, kb, 1, o1, p1, kb, s0, p0, 1); \
        kp = kb; \
        if (KIND == 2) { \
          WG_FENCE(); pv_issue<2, 0>(o2, p0, kp); WG_COMMIT(); sm_exp<KIND>(s1, p1, nk, w); \
        } else { \
          if (it + 1 < nit) { \
            const int bi = (seq >> (4 * it + 4)) & 15; \
            mbar_wait(bi == 4 ? BAR(B_KVOWN) : BAR(B_KVFULL + bi), 0); \
            kb = ((sb + kv_addr(bi)) & 0x3FFFF) >> 4; \
          } \
          if (KIND == 1) ATT_STEP(KIND, 0, s0, kb, 2, o2, p0, kp, s1, p1, LW0); \
          else ATT_STEP(KIND, 0, s0, kb, 2, o2, p0, kp, s1, p1, LASTW); \
        } } while (0)
      {
        const int it = 0;
        ATT_ITER(1);
      }
#pragma unroll 1
      for (int it = 1; it < min(nit, 4); it++) {
        if (r == 0 && it == GOW) mbar_wait(BAR(B_GO), 0);
        if (r == 1 && it == GOIT && lane < 2) mbar_arrive(BAR(B_GO));
        ATT_ITER(0);
      }
      if (nit == 5) {
        const int it = 4;
        if (r == 1 && it == GOIT && lane < 2) mbar_arrive(BAR(B_GO));
        ATT_ITER(2);
        WG_FENCE();
        pv_issue<3, 0>(o3, p1, kp);
        WG_COMMIT();
        WG_WAIT(0);
        reg_fence(o0); reg_fence(o1); reg_fence(o2); reg_fence(o3);
      } else {
        WG_FENCE();
        pv_issue<3, 0>(o3, p1, kp);
        WG_COMMIT();
        WG_WAIT(0);
        reg_fence(o0); reg_fence(o1); reg_fence(o2); reg_fence(o3);
      }
      if (nit < 3 && lane == 0) mbar_arrive_pair(BAR(B_ATT2));
      if (nit < 4 + r && lane < 2) mbar_arrive(BAR(B_ATT3));
      if (lane == 0) mbar_arrive(BAR(B_ATTL));
      if (r == 1 && nit <= GOIT && lane < 2) mbar_arrive(BAR(B_GO));
      {
        const uint32_t e0 = 63u << 23;
        const uint32_t ba = (__float_as_uint(o0[8]) - e0) | (__float_as_uint(o0[10]) - e0) | (__float_as_uint(o2[8]) - e0) | (__float_as_uint(o2[10]) - e0);
        const uint32_t bb = (__float_as_uint(o1[0]) - e0) | (__float_as_uint(o1[2]) - e0) | (__float_as_uint(o3[0]) - e0) | (__float_as_uint(o3[2]) - e0);
        if (!NOFIX && __builtin_expect(__any_sync(0xffffffffu, ((tq == 2 ? ba : tq == 0 ? bb : 0u) >> 30) != FORCE_SAFE), 0)) {
          const uint8_t* kv = g_kv + (ptrdiff_t)((2 * rb - 4) * 8 + c) * KVB + lane * 4;
#pragma unroll 1
          for (int h = 0; h < 4; h++) {
            uint32_t qh[6];
            float t[12];
#pragma unroll
            for (int i = 0; i < 6; i++) qh[i] = h == 0 ? q[i] : h == 1 ? q[6 + i] : h == 2 ? q[12 + i] : q[18 + i];
            safe_head(t, qh, h, kv, seq, nit, row0 - 2 * tq, row1 - 2 * tq, tq, tag);
#pragma unroll
            for (int i = 0; i < 12; i++) {
              if (h == 0) o0[i] = t[i];
              if (h == 1) o1[i] = t[i];
              if (h == 2) o2[i] = t[i];
              if (h == 3) o3[i] = t[i];
            }
          }
          __syncwarp();
        }
      }
      float inv[4][2];
      inv[0][0] = rcp(__shfl_sync(0xffffffffu, o0[8], (lane & 28) + 2));
      inv[0][1] = rcp(__shfl_sync(0xffffffffu, o0[10], (lane & 28) + 2));
      inv[1][0] = rcp(__shfl_sync(0xffffffffu, o1[0], lane & 28));
      inv[1][1] = rcp(__shfl_sync(0xffffffffu, o1[2], lane & 28));
      inv[2][0] = rcp(__shfl_sync(0xffffffffu, o2[8], (lane & 28) + 2));
      inv[2][1] = rcp(__shfl_sync(0xffffffffu, o2[10], (lane & 28) + 2));
      inv[3][0] = rcp(__shfl_sync(0xffffffffu, o3[0], lane & 28));
      inv[3][1] = rcp(__shfl_sync(0xffffffffu, o3[2], lane & 28));
      const bool lo = tq < 2;
#define OPK(dst, o, t, h) do { x0[dst] = pack2(o[4 * (t)] * inv[h][0], o[4 * (t) + 1] * inv[h][0]); x0[dst + 1] = pack2(o[4 * (t) + 2] * inv[h][1], o[4 * (t) + 3] * inv[h][1]); } while (0)
#define OPK2(dst, oa, ha, ob, hb) do { \
        const float i0 = lo ? inv[ha][0] : inv[hb][0], i1 = lo ? inv[ha][1] : inv[hb][1]; \
        x0[dst] = pack2((lo ? oa[8] : ob[0]) * i0, (lo ? oa[9] : ob[1]) * i0); \
        x0[dst + 1] = pack2((lo ? oa[10] : ob[2]) * i1, (lo ? oa[11] : ob[3]) * i1); } while (0)
      OPK(0, o0, 0, 0); OPK(2, o0, 1, 0); OPK2(4, o0, 0, o1, 1); OPK(6, o1, 1, 1); OPK(8, o1, 2, 1);
      OPK(10, o2, 0, 2); OPK(12, o2, 1, 2); OPK2(14, o2, 2, o3, 3); OPK(16, o3, 1, 3); OPK(18, o3, 2, 3);
    }
    const int bw = b * 4 + w;
    const size_t tile_off = (size_t)b * 81920 + w * 2560 + lane * 16;
    uint32_t* hint = &g_hint[b * 8 * HS + w];
    {
#pragma unroll
      for (int k = 0; k < 5; k++) {
        x0[4 * k] = tag16(x0[4 * k], tag);
        stg128(g_o + tile_off + c * 10240 + k * 512, x0[4 * k], x0[4 * k + 1], x0[4 * k + 2], x0[4 * k + 3]);
      }
      if (lane == 0) st_flag(hint + c * HS, tag);
      STAMP(6);
      if (lane < 8) asm volatile("st.shared.v4.u32 [%0], {%1,%1,%1,%1};" ::"r"(sb + OFF_HINT + r * 128 + lane * 16), "r"(~0u) : "memory");
      mbar_wait(BAR(B_STAT), 0);
      uint32_t xr[20];
      {
        const uint8_t* xp = reinterpret_cast<const uint8_t*>(P.x) + (size_t)(b * 64 + row0) * 1280 + c * 160 + tq * 4;
        const uint8_t* xq = xp + (56 - w * 16) * 1280;
#pragma unroll
        for (int t = 0; t < 10; t++) {
          xr[2 * t] = ldnc32(xp + t * 16);
          xr[2 * t + 1] = ldnc32(xq + t * 16);
        }
      }
      float acc[40];
      constexpr uint64_t HI = desc_hi(2560, 256, 3);
      const uint64_t db = mkdesc(sb + OFF_WOB, HI);
      mbar_wait(BAR(B_WOB), 0);
#pragma unroll
      for (int t = 0; t < 10; t++) {
        acc[4 * t] = bf_lo(xr[2 * t]); acc[4 * t + 1] = bf_hi(xr[2 * t]);
        acc[4 * t + 2] = bf_lo(xr[2 * t + 1]); acc[4 * t + 3] = bf_hi(xr[2 * t + 1]);
      }
      WG_FENCE();
#pragma unroll
      for (int k = 0; k < 5; k++) wg_rs80(acc, x0[4 * k], x0[4 * k + 1], x0[4 * k + 2], x0[4 * k + 3], db + k * 32, 1);
      WG_COMMIT();
      STAMP(7);
      uint32_t xa[6][20];
      const uint32_t ol = sb + w * 2560 + lane * 16;
#define WO_LOAD(xx, i) do { \
        _Pragma("unroll") for (int k = 0; k < 5; k++) \
          asm volatile("ld.shared.v4.u32 {%0,%1,%2,%3}, [%4];" : "=r"(xx[4 * k]), "=r"(xx[4 * k + 1]), "=r"(xx[4 * k + 2]), "=r"(xx[4 * k + 3]) \
                       : "r"(ol + (r ? 102400u : (i) < 3 ? 179200u : 107520u) + (i) * 10240 + k * 512) : "memory"); } while (0)
#define WO_MMA(xx, i) do { \
        _Pragma("unroll") for (int k = 0; k < 5; k++) wg_rs80(acc, xx[4 * k], xx[4 * k + 1], xx[4 * k + 2], xx[4 * k + 3], db + ((i) + 1) * 800 + k * 32, 1); } while (0)
#define WO_LAND(j) mbar_wait(BAR((r ? B_QFULL : B_KVFULL) + (j)), r ? (j) < 2 : 2 * rb + (j) >= 4)
#define WO_PAIR(j) do { \
        WO_LAND(j); \
        ST8(j); \
        WO_LOAD(xa[2 * (j)], 2 * (j)); WO_LOAD(xa[2 * (j) + 1], 2 * (j) + 1); \
        fix_tile2(xa[2 * (j)], xa[2 * (j) + 1], g_o + tile_off, c, 2 * (j) + 1, tag); \
        WG_FENCE(); \
        WO_MMA(xa[2 * (j)], 2 * (j)); WO_MMA(xa[2 * (j) + 1], 2 * (j) + 1); \
        WG_COMMIT(); } while (0)
#define ST8(j)
      WG_WAIT(0);
#pragma unroll
      for (int j = 0; j < 3; j++) {
        WO_LAND(j);
        ST8(j);
        WO_LOAD(xa[2 * j], 2 * j); WO_LOAD(xa[2 * j + 1], 2 * j + 1);
      }
      WO_LAND(3);
      ST8(3);
      WO_LOAD(x0, 6);
      {
        uint32_t bad = 0;
#pragma unroll
        for (int k = 0; k < 5; k++) bad |= (xa[0][4 * k] ^ tag) | (xa[1][4 * k] ^ tag) | (xa[2][4 * k] ^ tag) | (xa[3][4 * k] ^ tag) | (xa[4][4 * k] ^ tag) | (xa[5][4 * k] ^ tag) | (x0[4 * k] ^ tag);
        bad = __any_sync(0xffffffffu, (bad & TAGM) != 0u);
        if (lane < 2 - r) mbar_arrive_pair(BAR(r ? B_OL1 : B_ATT4));
        if (r && lane < 2) mbar_arrive(BAR(B_OL1L));
        uint32_t n = 0;
        while (!NOFIX && bad && ++n < SPIN_MAX) {
          bad = 0;
#pragma unroll
          for (int i = 0; i < 6; i++) ld_tile(xa[i], g_o + tile_off, c, i + 1);
          ld_tile(x0, g_o + tile_off, c, 7);
#pragma unroll
          for (int k = 0; k < 5; k++) bad |= (xa[0][4 * k] ^ tag) | (xa[1][4 * k] ^ tag) | (xa[2][4 * k] ^ tag) | (xa[3][4 * k] ^ tag) | (xa[4][4 * k] ^ tag) | (xa[5][4 * k] ^ tag) | (x0[4 * k] ^ tag);
          bad = __any_sync(0xffffffffu, (bad & TAGM) != 0u);
        }
      }
      mbar_wait(BAR(B_WOB7), 0);
      WG_FENCE();
      WO_MMA(xa[0], 0); WO_MMA(xa[1], 1);
      WG_COMMIT();
      WO_MMA(xa[2], 2);
      WG_COMMIT();
      WG_WAIT(1);
      if (lane == 0) mbar_arrive_pair(BAR(B_WODP));
      WO_MMA(xa[3], 3); WO_MMA(xa[4], 4);
      WG_COMMIT();
      WO_MMA(xa[5], 5);
      WG_COMMIT();
      WG_WAIT(1);
      if (lane == 0) mbar_arrive_pair(BAR(B_WODP2));
      WO_MMA(x0, 6);
      WG_COMMIT();
      WG_WAIT(0);
      reg_fence(acc);
      STAMP(8);
#pragma unroll
      for (int t = 0; t < 10; t++) {
        x0[2 * t] = pack2(acc[4 * t], acc[4 * t + 1]);
        x0[2 * t + 1] = pack2(acc[4 * t + 2], acc[4 * t + 3]);
      }
#pragma unroll
      for (int k = 0; k < 5; k++) {
        x0[4 * k] = tag16(x0[4 * k], tag);
        stg128(g_h + tile_off + c * 10240 + k * 512, x0[4 * k], x0[4 * k + 1], x0[4 * k + 2], x0[4 * k + 3]);
      }
      if (lane == 0) st_flag(hint + 256 * HS + c * HS, tag);
    }
    uint32_t ha[56];
    {
      float acc[112];
      constexpr uint64_t HI = desc_hi(5120, 512, 2);
#define ST4(i)
#define ST5(i)
#define W1_ISSUE(xx, i) do { \
        const uint64_t db = mkdesc(sb + w1b_addr(i), HI); \
        mbar_wait(BAR(B_BFULL + (i)), 0); \
        WG_FENCE(); \
        _Pragma("unroll") for (int k = 0; k < 5; k++) wg_rs224(acc, xx[4 * k], xx[4 * k + 1], xx[4 * k + 2], xx[4 * k + 3], db + k * 64, (i) | k); \
        WG_COMMIT(); } while (0)
#define W1_STEP(xx, i) do { \
        ST4(i); \
        W1_ISSUE(xx, i); \
        WG_WAIT(1); \
        ST5(i); \
        if ((W2N || (i) != 4) && (i) != 1 && lane == 0) mbar_arrive_pair(BAR(B_BEMPTY - 1 + (i))); } while (0)
#define HT(i) ht, c, i
      const uint8_t* ht = g_h + tile_off;
      uint32_t x1[20], x2[20], x3[20];
#define FIRE()
#define H_STATS() do { \
        const uint32_t sh = __shfl_sync(0xffffffffu, __byte_perm(x0[0], x0[1], 0x5410), lane & 28); \
        const float sh0 = bf_lo(sh), sh1 = bf_hi(sh); \
        float sum0 = 0.f, sum1 = 0.f, v0 = 0.f, v1 = 0.f; \
        _Pragma("unroll") for (int t = 0; t < 10; t++) { \
          const float d0 = bf_lo(x0[2 * t]) - sh0, d1 = bf_hi(x0[2 * t]) - sh0, d2 = bf_lo(x0[2 * t + 1]) - sh1, d3 = bf_hi(x0[2 * t + 1]) - sh1; \
          sum0 += d0 + d1; \
          sum1 += d2 + d3; \
          v0 = fmaf(d1, d1, fmaf(d0, d0, v0)); \
          v1 = fmaf(d3, d3, fmaf(d2, d2, v1)); \
        } \
        { const float a = (tq & 1) ? sum0 : sum1, e = (tq & 1) ? v0 : v1; \
          sum0 = ((tq & 1) ? sum1 : sum0) + __shfl_xor_sync(0xffffffffu, a, 1); \
          v0 = ((tq & 1) ? v1 : v0) + __shfl_xor_sync(0xffffffffu, e, 1); } \
        sum0 += __shfl_xor_sync(0xffffffffu, sum0, 2); \
        v0 += __shfl_xor_sync(0xffffffffu, v0, 2); \
        const float mu = sum0 * (1.f / 80.f); \
        if (tq < 2) g_hstat[(bw * 8 + c) * 16 + gq + tq * 8] = make_float2((tq ? sh1 : sh0) + mu, tag32(fmaxf(fmaf(-mu, sum0, v0), 0.f), ep)); } while (0)
#define H_STAGE() do { \
        const uint32_t hs = sb + OFF_HST + (uint32_t)(r * 64 + rowm) * 160u + (uint32_t)(lane >> 4) * 16u; \
        mbar_wait(BAR(B_ATTL), 0); \
        _Pragma("unroll") for (int k = 0; k < 5; k++) stsm4(hs + k * 32, x0[4 * k], x0[4 * k + 1], x0[4 * k + 2], x0[4 * k + 3]); \
        fence_async_smem(); \
        __syncwarp(); \
        if (lane == 0) mbar_arrive(BAR(B_HST + r)); } while (0)
      W1_ISSUE(x0, 0);
      uint32_t ready = 0;
      probe_wait(ready, 1, hint + 256 * HS + ((c + lane) & 7) * HS, tag);
      ld_tile(x1, HT(1));
      probe_wait(ready, 2, hint + 256 * HS + ((c + lane) & 7) * HS, tag);
      ld_tile(x2, HT(2));
      probe_wait(ready, 3, hint + 256 * HS + ((c + lane) & 7) * HS, tag);
      ld_tile(x3, HT(3));
      STAMP(9);
      WG_WAIT(0);
      if (lane == 0) mbar_arrive_pair(BAR(B_BEMPTY));
      H_STAGE();
      fix_tile(x1, HT(1), tag);
      fix_tile(x2, HT(2), tag);
      fix_tile(x3, HT(3), tag);
      STAMP(10);
      W1_ISSUE(x1, 1);
      H_STATS();
      ld_tile(x0, HT(4));
      W1_STEP(x2, 2);
      ld_tile(x1, HT(5));
      W1_STEP(x3, 3);
      fix_tile(x0, HT(4), tag);
      fix_tile(x1, HT(5), tag);
      ld_tile(x2, HT(6));
      W1_STEP(x0, 4);
      ld_tile(x3, HT(7));
      uint2 hs[4];
      const float2* hp = &g_hstat[(bw * 8 + tq * 2) * 16 + gq];
      hs[0] = ldcg64(hp); hs[1] = ldcg64(hp + 16); hs[2] = ldcg64(hp + 8); hs[3] = ldcg64(hp + 24);
      W1_STEP(x1, 5);
      fix_tile(x2, HT(6), tag);
      fix_tile(x3, HT(7), tag);
      W1_STEP(x2, 6);
      W1_STEP(x3, 7);
      {
        uint32_t n = 0;
        while (__any_sync(0xffffffffu, (((hs[0].y ^ ep) | (hs[1].y ^ ep) | (hs[2].y ^ ep) | (hs[3].y ^ ep)) & 3u) != 0u) && ++n < SPIN_MAX) {
          hs[0] = ldcg64(hp); hs[1] = ldcg64(hp + 16); hs[2] = ldcg64(hp + 8); hs[3] = ldcg64(hp + 24);
        }
      }
      float mean0, mean1, rs0, rs1;
      {
        const float a0 = __uint_as_float(hs[0].x), a1 = __uint_as_float(hs[1].x), b0 = __uint_as_float(hs[2].x), b1 = __uint_as_float(hs[3].x);
        float t0 = a0 + a1, t1 = b0 + b1;
        t0 += __shfl_xor_sync(0xffffffffu, t0, 1);
        t1 += __shfl_xor_sync(0xffffffffu, t1, 1);
        t0 += __shfl_xor_sync(0xffffffffu, t0, 2);
        t1 += __shfl_xor_sync(0xffffffffu, t1, 2);
        mean0 = t0 * 0.125f;
        mean1 = t1 * 0.125f;
        float u0 = __uint_as_float(hs[0].y) + __uint_as_float(hs[1].y) + 80.f * ((a0 - mean0) * (a0 - mean0) + (a1 - mean0) * (a1 - mean0));
        float u1 = __uint_as_float(hs[2].y) + __uint_as_float(hs[3].y) + 80.f * ((b0 - mean1) * (b0 - mean1) + (b1 - mean1) * (b1 - mean1));
        u0 += __shfl_xor_sync(0xffffffffu, u0, 1);
        u1 += __shfl_xor_sync(0xffffffffu, u1, 1);
        u0 += __shfl_xor_sync(0xffffffffu, u0, 2);
        u1 += __shfl_xor_sync(0xffffffffu, u1, 2);
        rs0 = 0.5f * rsqrtf(u0 * (1.f / 640.f) + 1e-5f);
        rs1 = 0.5f * rsqrtf(u1 * (1.f / 640.f) + 1e-5f);
      }
      mbar_wait(BAR(B_CS1), 0);
      WG_WAIT(0);
      reg_fence(acc);
      if (lane == 0) mbar_arrive_pair(BAR(B_BEMPTY + 7));
      if (!r) asm volatile("bar.arrive 4, 256;" ::: "memory");
      STAMP(11);
      const float n0 = -mean0 * rs0, n1 = -mean1 * rs1;
#pragma unroll
      for (int t = 0; t < 28; t++) {
        const float2 cs = lds64f(sb + OFF_XS + t * 32 + tq * 8);
        const float h0 = fmaf(acc[4 * t], rs0, cs.x * n0), h1 = fmaf(acc[4 * t + 1], rs0, cs.y * n0);
        const float h2 = fmaf(acc[4 * t + 2], rs1, cs.x * n1), h3 = fmaf(acc[4 * t + 3], rs1, cs.y * n1);
        ha[2 * t] = pack2(fmaf(h0, tanh_fast(h0), h0), fmaf(h1, tanh_fast(h1), h1));
        ha[2 * t + 1] = pack2(fmaf(h2, tanh_fast(h2), h2), fmaf(h3, tanh_fast(h3), h3));
      }
      if ((c & 3) == 3) {
#pragma unroll
        for (int t = 48; t < 56; t++) ha[t] = 0u;
      }
    }
    STAMP(12);
    {
      float accA[32], accB[32];
      constexpr uint64_t HI = desc_hi(28672, 1024, 1);
      const uint32_t ost = sb + OFF_OST + (uint32_t)warp * 6144u;
      const uint32_t osw = ost + (uint32_t)(lane & 15) * 128u + (uint32_t)(((lane >> 4) ^ lane) & 7) * 16u;
      uint32_t so = 0;
#define W2_ISSUE(acc, u) do { \
        mbar_wait(BAR((u) < 5 ? B_W2FULL + (u) : B_BFULL - 5 + (u)), (u) >= 5); \
        const uint64_t db = mkdesc(sb + ((u) < 6 ? (u) : (u) - 6) * 28672, HI); \
        WG_FENCE(); \
        _Pragma("unroll") for (int k = 0; k < 14; k++) wg_rs64(acc, ha[4 * k], ha[4 * k + 1], ha[4 * k + 2], ha[4 * k + 3], db + k * 128, k); \
        WG_COMMIT(); } while (0)
#define W2_OUT(a, u) do { \
        reg_fence(a); \
        if (lane == 0) { \
          if ((u) < 4) mbar_arrive_pair(BAR(B_QEMPTY + 2 + (((u) + 2) & 3))); \
          asm volatile("cp.async.bulk.wait_group.read 2;" ::: "memory"); \
        } \
        __syncwarp(); \
        _Pragma("unroll") for (int t = 0; t < 8; t += 2) \
          stsm4((osw ^ (t * 16)) + so, pack2(a[4 * t], a[4 * t + 1]), pack2(a[4 * t + 2], a[4 * t + 3]), pack2(a[4 * t + 4], a[4 * t + 5]), pack2(a[4 * t + 6], a[4 * t + 7])); \
        fence_async_smem(); \
        __syncwarp(); \
        if (lane == 0) \
          asm volatile("cp.reduce.async.bulk.tensor.3d.global.shared::cta.add.bulk_group [%0, {%2, %3, %4}], [%1];\ncp.async.bulk.commit_group;" \
                       ::"l"(&P.mOut[w]), "r"(ost + so), "r"(min((uint32_t)(c + (u)) * 64u, (uint32_t)(c + (u)) * 64u - 640u)), "r"(b * 64 + w * 8), "r"(0) : "memory"); \
        so = so == 4096u ? 0u : so + 2048u; } while (0)
#define ST12(i)
      mbar_wait(BAR(B_BEMPTY + 7), 0);
      mbar_wait(BAR(B_OUTOK), 0);
      mbar_wait(BAR(B_OUTOK + r), 0);
      fence_async_glob();
      ST12(19);
#pragma unroll 1
      for (int u = 0; u < 10; u += 2) {
        asm volatile("bar.sync %0, 256;" ::"r"(3 + r) : "memory");
        W2_ISSUE(accA, u);
        W2_ISSUE(accB, u + 1);
        if (r || u < 8) asm volatile("bar.arrive %0, 256;" ::"r"(4 - r) : "memory");
        WG_WAIT(1);
        W2_OUT(accA, u);
        ST12(20 + u);
        WG_WAIT(0);
        W2_OUT(accB, u + 1);
        ST12(21 + u);
      }
      STAMP(15);
      if (lane == 0) asm volatile("cp.async.bulk.wait_group.read 0;" ::: "memory");
      STAMP(17);
    }
  }
}

typedef CUresult (*EncodeFn)(CUtensorMap*, CUtensorMapDataType, cuuint32_t, void*, const cuuint64_t*, const cuuint64_t*, const cuuint32_t*,
                             const cuuint32_t*, CUtensorMapInterleave, CUtensorMapSwizzle, CUtensorMapL2promotion, CUtensorMapFloatOOBfill);

static void make_map(EncodeFn enc, CUtensorMap* m, const void* p, int nd, const cuuint64_t* dims, const cuuint64_t* strides, const cuuint32_t* box,
                     CUtensorMapSwizzle sw) {
  const cuuint32_t es[5] = {1, 1, 1, 1, 1};
  enc(m, CU_TENSOR_MAP_DATA_TYPE_BFLOAT16, (cuuint32_t)nd, const_cast<void*>(p), dims, strides, box, es, CU_TENSOR_MAP_INTERLEAVE_NONE, sw,
      CU_TENSOR_MAP_L2_PROMOTION_L2_128B, CU_TENSOR_MAP_FLOAT_OOB_FILL_NONE);
}

extern "C" void kernel_launch(void* const* d_in, const int* in_sizes, int n_in, void* d_out, int out_size) {
  (void)in_sizes; (void)n_in; (void)out_size;
  static EncodeFn enc = nullptr;
  if (!enc) {
    void* f = nullptr;
    cudaDriverEntryPointQueryResult qr;
    cudaGetDriverEntryPoint("cuTensorMapEncodeTiled", &f, cudaEnableDefault, &qr);
    enc = (EncodeFn)f;
    cudaFuncSetAttribute(fused_block_kernel, cudaFuncAttributeMaxDynamicSharedMemorySize, (int)SMEM_BYTES);
  }
  Params P;
  P.x = (const __nv_bfloat16*)d_in[0];
  P.wqkv = (const __nv_bfloat16*)d_in[1];
  P.wo = (const __nv_bfloat16*)d_in[2];
  P.w1 = (const __nv_bfloat16*)d_in[4];
  P.w2 = (const __nv_bfloat16*)d_in[5];
  P.out = (__nv_bfloat16*)d_out;
  for (int k = 0; k < 64; k++) {
    const int c = k < 4 ? k + 4 : k < 36 ? (k - 4) >> 3 : (k * 37 - 308) >> 8;
    const int g = k < 4 ? 0 : k < 36 ? (k - 1) & 7 : k - 33 - 7 * ((k * 37 - 1258) >> 8);
    reinterpret_cast<uint8_t*>(P.map)[k] = (uint8_t)(c + 8 * g);
  }
  { const cuuint64_t d[2] = {640, 2048}, s[1] = {1280}; const cuuint32_t b[2] = {64, 128}; make_map(enc, &P.mX, P.x, 2, d, s, b, CU_TENSOR_MAP_SWIZZLE_128B); }
  for (int i = 0; i < 2; i++) {
    const cuuint64_t d[4] = {32, 640, 19, 3}, s[3] = {3840, 64, 1280};
    const cuuint32_t b[4] = {32, 32, 2, 3};
    make_map(enc, &P.mWqM[i], P.wqkv + 16 * i, 4, d, s, b, CU_TENSOR_MAP_SWIZZLE_64B);
  }
  { const cuuint64_t d[4] = {16, 640, 40, 3}, s[3] = {3840, 32, 1280}; const cuuint32_t b[4] = {16, 32, 1, 3}; make_map(enc, &P.mWqL, P.wqkv, 4, d, s, b, CU_TENSOR_MAP_SWIZZLE_32B); }
  { const cuuint64_t d[3] = {16, 640, 40}, s[2] = {1280, 32}; const cuuint32_t b[3] = {16, 80, 5}; make_map(enc, &P.mWo, P.wo, 3, d, s, b, CU_TENSOR_MAP_SWIZZLE_32B); }
  { const cuuint64_t d[3] = {32, 640, 54}, s[2] = {3456, 64}; const cuuint32_t b[3] = {32, 80, UNI ? 7 : 4}; make_map(enc, &P.mW1a, P.w1, 3, d, s, b, CU_TENSOR_MAP_SWIZZLE_64B); }
  { const cuuint64_t d[3] = {32, 640, 54}, s[2] = {3456, 64}; const cuuint32_t b[3] = {32, 80, 3}; make_map(enc, &P.mW1b, P.w1, 3, d, s, b, CU_TENSOR_MAP_SWIZZLE_64B); }
  { const cuuint64_t d[2] = {640, 1728}, s[1] = {1280}; const cuuint32_t b[2] = {64, UNI ? 224 : 112}; make_map(enc, &P.mW2, P.w2, 2, d, s, b, CU_TENSOR_MAP_SWIZZLE_128B); }
  { const cuuint64_t d[2] = {640, 2048}, s[1] = {1280}; const cuuint32_t b[2] = {80, 64}; make_map(enc, &P.mOutH, P.out, 2, d, s, b, CU_TENSOR_MAP_SWIZZLE_NONE); }
  for (int w = 0; w < 4; w++) {
    const cuuint64_t d[3] = {640, 2048, 2}, s[2] = {1280, (cuuint64_t)(56 - 16 * w) * 1280};
    const cuuint32_t b[3] = {64, 8, 2};
    make_map(enc, &P.mOut[w], P.out, 3, d, s, b, CU_TENSOR_MAP_SWIZZLE_128B);
  }
  fused_block_kernel<<<128, 384, SMEM_BYTES, cudaStreamPerThread>>>(P);
}
```

```cpp
#include <cuda_runtime.h>
#include <cuda.h>
#include <cuda_bf16.h>
#include <stdint.h>

#define PROF 0
#define KVP 8
#define GOIT 4
#define GOW 2
#define HS 8
#define EARL 0
#define CSU 8
#define PP 1
#define S6 0
#define SPL (S6 ? 6 : 0)
#define RELK 0
#define AV 0
#define PTR 0
#define MF1 2
#define KF 0
#define B3F 1
#define ETW 1
#define HF 1
#define PF 1
#define W2D 1
#define XNO 0
#define XT 1
#define C8 1
#define L5 1
#define CLATE 0
#define XRP 3
#define T2 1
#define PAUSE 2
#define ILV 2
#define ROLL 3
#define RK 2
#define RF 1
#define PFM 1
#define NOP 1
#define RD2 1
#define SLIM 1
#define SBB 0
#define FO1 1
#define EPF 3
#define EPD 0
#define MAPA 0
#define XPN 1
#define WP2 0
#define BFP 0
#define ALN 0
#define FORCE_SAFE 0u

__device__ __align__(1024) uint8_t g_kv[32 * 8 * 22528];
__device__ __align__(1024) uint8_t g_o[32 * 4 * 8 * 2560];
__device__ __align__(1024) uint8_t g_h[32 * 4 * 8 * 2560];
__device__ __align__(1024) float2 g_hstat[32 * 4 * 8 * 16];
__device__ __align__(128) uint32_t g_hint[2 * 32 * 8 * HS];
__device__ __align__(128) uint32_t g_oflag[32 * 8];
__device__ __align__(128) float2 g_xstat[128 * 24];
__device__ __align__(128) float g_csq[8 * 8 * 240];
__device__ __align__(128) float g_cs1[8 * 8 * 224];
__device__ __align__(128) uint32_t g_epoch[128 * 32];
#define STAMP(slot)
#define STAMPW(slot)

struct Params {
  const __nv_bfloat16 *x, *wqkv, *wo, *w1, *w2;
  __nv_bfloat16* out;
  uint32_t map[16];
  CUtensorMap mX, mXr, mWqM[2], mWqL, mWo, mW1a, mW1b, mW2, mOutH, mOut[1];
};

constexpr uint32_t QST = 47104;
constexpr uint32_t KVB = 22528;
constexpr uint32_t OFF_WOB = 0;
constexpr uint32_t OFF_PRE = 188416;
constexpr uint32_t OFF_XROW = 196608;
constexpr uint32_t OFF_OST = 174080;
constexpr uint32_t OFF_W1X = T2 ? 226816 : 223232;
constexpr uint32_t OFF_W1Y = 220160;
#define OSLOT(r, i) (((r) ? 201728u : 174080u) + (i) * 8192u)
constexpr uint32_t OFF_HST = 209920;
constexpr uint32_t OFF_XST = 230336;
constexpr uint32_t OFF_XS = 230912;
constexpr uint32_t OFF_MISC = 231808;
constexpr uint32_t SMEM_BYTES = 232448;

enum {
  B_QFULL = 0, B_KVFULL = 4, B_KVLAND = 8, B_K2FULL = 11, B_WOB = 12, B_WOB7 = 13, B_BFULL = 14, B_W2FULL = 22, B_CS1 = 27, B_OUTOK = 28,
  B_KVOWN = 30, B_HST = 32, B_STAT = 34, B_XROW = 35,
  B_Q23 = 36, B_PRE = 37, B_ATTL = 38, B_GO = 39, B_OL1 = 40, B_OL1L = 41,
  B_QEMPTY = 42, B_WODP = 48, B_BEMPTY = 49, B_WODP2 = 57, B_ATT4 = 58, B_ATT3 = 59,
  B_ATT2 = 60, B_WOE = 61,
  B_OFULL = 66, B_OFREE = 72
};
constexpr uint32_t TAGM = 0x00010001u;
constexpr uint32_t SPIN_MAX = 1u << 18;

__device__ __forceinline__ uint32_t s2u(const void* p) { return (uint32_t)__cvta_generic_to_shared(p); }
__device__ __forceinline__ void mbar_init(uint32_t b, int c) { asm volatile("mbarrier.init.shared::cta.b64 [%0], %1;" ::"r"(b), "r"(c)); }
__device__ __forceinline__ void mbar_expect(uint32_t b, int bytes) { asm volatile("mbarrier.arrive.expect_tx.shared::cta.b64 _, [%0], %1;" ::"r"(b), "r"(bytes) : "memory"); }
__device__ __forceinline__ void mbar_arrive(uint32_t b) { asm volatile("mbarrier.arrive.shared::cta.b64 _, [%0];" ::"r"(b) : "memory"); }
__device__ __forceinline__ void mbar_arrive_pair(uint32_t b) {
  asm volatile("{\n.reg .b32 r;\nmapa.shared::cluster.u32 r, %0, 0;\nmbarrier.arrive.shared::cluster.b64 _, [r];\n"
               "mapa.shared::cluster.u32 r, %0, 1;\nmbarrier.arrive.shared::cluster.b64 _, [r];\n}" ::"r"(b) : "memory");
}
__device__ __forceinline__ void mbar_wait(uint32_t b, uint32_t ph) {
  asm volatile("{\n.reg .pred p;\n.reg .u32 n;\nmov.u32 n, 0;\nW%=:\nmbarrier.try_wait.parity.shared::cta.b64 p, [%0], %1;\n"
               "add.u32 n, n, 1;\nsetp.lt.and.u32 p, n, 0x100000, !p;\n@p bra W%=;\n}" ::"r"(b), "r"(ph) : "memory");
}
__device__ __forceinline__ bool mbar_test(uint32_t b) {
  uint32_t v;
  asm volatile("{\n.reg .pred p;\nmbarrier.test_wait.parity.shared::cta.b64 p, [%1], 0;\nselp.u32 %0, 1, 0, p;\n}" : "=r"(v) : "r"(b) : "memory");
  return v != 0u;
}
__device__ __forceinline__ void tma2d(uint32_t dst, const CUtensorMap* m, int c0, int c1, uint32_t bar) {
  asm volatile("cp.async.bulk.tensor.2d.shared::cluster.global.mbarrier::complete_tx::bytes [%0], [%1, {%3, %4}], [%2];" ::"r"(dst), "l"(m), "r"(bar), "r"(c0), "r"(c1) : "memory");
}
__device__ __forceinline__ void tma2d_mc(uint32_t dst, const CUtensorMap* m, int c0, int c1, uint32_t bar) {
  asm volatile("cp.async.bulk.tensor.2d.shared::cluster.global.mbarrier::complete_tx::bytes.multicast::cluster [%0], [%1, {%3, %4}], [%2], %5;" ::"r"(dst), "l"(m), "r"(bar), "r"(c0), "r"(c1), "h"((uint16_t)3) : "memory");
}
__device__ __forceinline__ void tma3d_mc(uint32_t dst, const CUtensorMap* m, int c0, int c1, int c2, uint32_t bar) {
  asm volatile("cp.async.bulk.tensor.3d.shared::cluster.global.mbarrier::complete_tx::bytes.multicast::cluster [%0], [%1, {%3, %4, %5}], [%2], %6;" ::"r"(dst), "l"(m), "r"(bar), "r"(c0), "r"(c1), "r"(c2), "h"((uint16_t)3) : "memory");
}
__device__ __forceinline__ void tma3d(uint32_t dst, const CUtensorMap* m, int c0, int c1, int c2, uint32_t bar) {
  asm volatile("cp.async.bulk.tensor.3d.shared::cluster.global.mbarrier::complete_tx::bytes [%0], [%1, {%3, %4, %5}], [%2];" ::"r"(dst), "l"(m), "r"(bar), "r"(c0), "r"(c1), "r"(c2) : "memory");
}
__device__ __forceinline__ void tma4d_mc(uint32_t dst, const CUtensorMap* m, int c0, int c1, int c2, int c3, uint32_t bar) {
  asm volatile("cp.async.bulk.tensor.4d.shared::cluster.global.mbarrier::complete_tx::bytes.multicast::cluster [%0], [%1, {%3, %4, %5, %6}], [%2], %7;" ::"r"(dst), "l"(m), "r"(bar), "r"(c0), "r"(c1), "r"(c2), "r"(c3), "h"((uint16_t)3) : "memory");
}
__device__ __forceinline__ void bulk_load(uint32_t dst, const void* src, int bytes, uint32_t bar) {
  asm volatile("cp.async.bulk.shared::cluster.global.mbarrier::complete_tx::bytes [%0], [%1], %2, [%3];" ::"r"(dst), "l"(src), "r"(bytes), "r"(bar) : "memory");
}
__device__ __forceinline__ void l2_prefetch_bulk(const void* p, int bytes) { asm volatile("cp.async.bulk.prefetch.L2.global [%0], %1;" ::"l"(p), "r"(bytes) : "memory"); }
__device__ __forceinline__ void l2_prefetch(const void* p) { asm volatile("prefetch.global.L2 [%0];" ::"l"(p)); }
__device__ __forceinline__ uint32_t ld_flag(const uint32_t* p) { uint32_t v; asm volatile("ld.acquire.gpu.global.u32 %0, [%1];" : "=r"(v) : "l"(p) : "memory"); return v; }
__device__ __forceinline__ void st_flag(uint32_t* p, uint32_t v) { asm volatile("st.relaxed.gpu.global.u32 [%0], %1;" ::"l"(p), "r"(v) : "memory"); }
__device__ __forceinline__ void fence_async_smem() { asm volatile("fence.proxy.async.shared::cta;" ::: "memory"); }
__device__ __forceinline__ void fence_async_glob() { asm volatile("fence.proxy.async.global;" ::: "memory"); }
__device__ __forceinline__ uint4 ldcg128(const void* p) { uint4 v; asm volatile("ld.relaxed.gpu.global.v4.u32 {%0,%1,%2,%3}, [%4];" : "=r"(v.x), "=r"(v.y), "=r"(v.z), "=r"(v.w) : "l"(p) : "memory"); return v; }
__device__ __forceinline__ uint32_t ldnc32(const void* p) { uint32_t v; asm volatile("ld.global.nc.u32 %0, [%1];" : "=r"(v) : "l"(p)); return v; }
__device__ __forceinline__ uint2 ldcg64(const void* p) { uint2 v; asm volatile("ld.relaxed.gpu.global.v2.u32 {%0,%1}, [%2];" : "=r"(v.x), "=r"(v.y) : "l"(p) : "memory"); return v; }
__device__ __forceinline__ uint32_t ldcg32(const void* p) { uint32_t v; asm volatile("ld.relaxed.gpu.global.u32 %0, [%1];" : "=r"(v) : "l"(p) : "memory"); return v; }
__device__ __forceinline__ uint32_t pack2(float lo, float hi) { uint32_t r; asm("cvt.rn.bf16x2.f32 %0, %1, %2;" : "=r"(r) : "f"(hi), "f"(lo)); return r; }
__device__ __forceinline__ float bf_lo(uint32_t v) { return __uint_as_float(v << 16); }
__device__ __forceinline__ float bf_hi(uint32_t v) { return __uint_as_float(v & 0xffff0000u); }
__device__ __forceinline__ float ex2(float x) { float y; asm("ex2.approx.ftz.f32 %0, %1;" : "=f"(y) : "f"(x)); return y; }
__device__ __forceinline__ float rcp(float x) { float y; asm("rcp.approx.ftz.f32 %0, %1;" : "=f"(y) : "f"(x)); return y; }
__device__ __forceinline__ float tanh_fast(float x) { float y; asm("tanh.approx.f32 %0, %1;" : "=f"(y) : "f"(x)); return y; }
__device__ __forceinline__ void stsm4(uint32_t a, uint32_t r0, uint32_t r1, uint32_t r2, uint32_t r3) {
  asm volatile("stmatrix.sync.aligned.m8n8.x4.shared.b16 [%0], {%1,%2,%3,%4};" ::"r"(a), "r"(r0), "r"(r1), "r"(r2), "r"(r3) : "memory");
}
__device__ __forceinline__ void ldsm4(uint32_t* r, uint32_t a) {
  asm volatile("ldmatrix.sync.aligned.m8n8.x4.shared.b16 {%0,%1,%2,%3}, [%4];" : "=r"(r[0]), "=r"(r[1]), "=r"(r[2]), "=r"(r[3]) : "r"(a) : "memory");
}
__device__ __forceinline__ float2 lds64f(uint32_t a) { float2 v; asm volatile("ld.shared.v2.f32 {%0,%1}, [%2];" : "=f"(v.x), "=f"(v.y) : "r"(a)); return v; }
__device__ __forceinline__ constexpr uint64_t desc_hi(uint32_t lbo, uint32_t sbo, uint32_t sw) {
  return ((uint64_t)(lbo >> 4) << 16) | ((uint64_t)(sbo >> 4) << 32) | ((uint64_t)sw << 62);
}
__device__ __forceinline__ uint64_t mkdesc(uint32_t addr, uint64_t hi) { return hi | (uint64_t)((addr & 0x3FFFF) >> 4); }
#define WG_FENCE() asm volatile("wgmma.fence.sync.aligned;" ::: "memory")
#define WG_COMMIT() asm volatile("wgmma.commit_group.sync.aligned;" ::: "memory")
#define WG_WAIT_(n) asm volatile("wgmma.wait_group.sync.aligned " #n ";" ::: "memory")
#define WG_WAIT(n) WG_WAIT_(n)
template <int N> __device__ __forceinline__ void reg_fence(float (&a)[N]) {
#pragma unroll
  for (int i = 0; i < N; i++) asm volatile("" : "+f"(a[i])::"memory");
}

__device__ __forceinline__ void wg_rs48(float (&d)[24], uint32_t a0, uint32_t a1, uint32_t a2, uint32_t a3, uint64_t db, int sd) {
  asm volatile("{\n.reg .pred p;\nsetp.ne.b32 p, %29, 0;\n"
  "wgmma.mma_async.sync.aligned.m64n48k16.f32.bf16.bf16 {%0, %1, %2, %3, %4, %5, %6, %7, %8, %9, %10, %11, %12, %13, %14, %15, %16, %17, %18, %19, %20, %21, %22, %23}, {%24, %25, %26, %27}, %28, p, 1, 1, 1;\n}\n"
  : "+f"(d[0]), "+f"(d[1]), "+f"(d[2]), "+f"(d[3]), "+f"(d[4]), "+f"(d[5]), "+f"(d[6]), "+f"(d[7]), "+f"(d[8]), "+f"(d[9]), "+f"(d[10]), "+f"(d[11]), "+f"(d[12]), "+f"(d[13]), "+f"(d[14]), "+f"(d[15]), "+f"(d[16]), "+f"(d[17]), "+f"(d[18]), "+f"(d[19]), "+f"(d[20]), "+f"(d[21]), "+f"(d[22]), "+f"(d[23]) : "r"(a0), "r"(a1), "r"(a2), "r"(a3), "l"(db), "r"(sd));
}
__device__ __forceinline__ void wg_rs80(float (&d)[40], uint32_t a0, uint32_t a1, uint32_t a2, uint32_t a3, uint64_t db, int sd) {
  asm volatile("{\n.reg .pred p;\nsetp.ne.b32 p, %45, 0;\n"
  "wgmma.mma_async.sync.aligned.m64n80k16.f32.bf16.bf16 {%0, %1, %2, %3, %4, %5, %6, %7, %8, %9, %10, %11, %12, %13, %14, %15, %16, %17, %18, %19, %20, %21, %22, %23, %24, %25, %26, %27, %28, %29, %30, %31, %32, %33, %34, %35, %36, %37, %38, %39}, {%40, %41, %42, %43}, %44, p, 1, 1, 1;\n}\n"
  : "+f"(d[0]), "+f"(d[1]), "+f"(d[2]), "+f"(d[3]), "+f"(d[4]), "+f"(d[5]), "+f"(d[6]), "+f"(d[7]), "+f"(d[8]), "+f"(d[9]), "+f"(d[10]), "+f"(d[11]), "+f"(d[12]), "+f"(d[13]), "+f"(d[14]), "+f"(d[15]), "+f"(d[16]), "+f"(d[17]), "+f"(d[18]), "+f"(d[19]), "+f"(d[20]), "+f"(d[21]), "+f"(d[22]), "+f"(d[23]), "+f"(d[24]), "+f"(d[25]), "+f"(d[26]), "+f"(d[27]), "+f"(d[28]), "+f"(d[29]), "+f"(d[30]), "+f"(d[31]), "+f"(d[32]), "+f"(d[33]), "+f"(d[34]), "+f"(d[35]), "+f"(d[36]), "+f"(d[37]), "+f"(d[38]), "+f"(d[39]) : "r"(a0), "r"(a1), "r"(a2), "r"(a3), "l"(db), "r"(sd));
}
__device__ __forceinline__ void wg_rs224(float (&d)[112], uint32_t a0, uint32_t a1, uint32_t a2, uint32_t a3, uint64_t db, int sd) {
  asm volatile("{\n.reg .pred p;\nsetp.ne.b32 p, %117, 0;\n"
  "wgmma.mma_async.sync.aligned.m64n224k16.f32.bf16.bf16 {%0, %1, %2, %3, %4, %5, %6, %7, %8, %9, %10, %11, %12, %13, %14, %15, %16, %17, %18, %19, %20, %21, %22, %23, %24, %25, %26, %27, %28, %29, %30, %31, %32, %33, %34, %35, %36, %37, %38, %39, %40, %41, %42, %43, %44, %45, %46, %47, %48, %49, %50, %51, %52, %53, %54, %55, %56, %57, %58, %59, %60, %61, %62, %63, %64, %65, %66, %67, %68, %69, %70, %71, %72, %73, %74, %75, %76, %77, %78, %79, %80, %81, %82, %83, %84, %85, %86, %87, %88, %89, %90, %91, %92, %93, %94, %95, %96, %97, %98, %99, %100, %101, %102, %103, %104, %105, %106, %107, %108, %109, %110, %111}, {%112, %113, %114, %115}, %116, p, 1, 1, 1;\n}\n"
  : "+f"(d[0]), "+f"(d[1]), "+f"(d[2]), "+f"(d[3]), "+f"(d[4]), "+f"(d[5]), "+f"(d[6]), "+f"(d[7]), "+f"(d[8]), "+f"(d[9]), "+f"(d[10]), "+f"(d[11]), "+f"(d[12]), "+f"(d[13]), "+f"(d[14]), "+f"(d[15]), "+f"(d[16]), "+f"(d[17]), "+f"(d[18]), "+f"(d[19]), "+f"(d[20]), "+f"(d[21]), "+f"(d[22]), "+f"(d[23]), "+f"(d[24]), "+f"(d[25]), "+f"(d[26]), "+f"(d[27]), "+f"(d[28]), "+f"(d[29]), "+f"(d[30]), "+f"(d[31]), "+f"(d[32]), "+f"(d[33]), "+f"(d[34]), "+f"(d[35]), "+f"(d[36]), "+f"(d[37]), "+f"(d[38]), "+f"(d[39]), "+f"(d[40]), "+f"(d[41]), "+f"(d[42]), "+f"(d[43]), "+f"(d[44]), "+f"(d[45]), "+f"(d[46]), "+f"(d[47]), "+f"(d[48]), "+f"(d[49]), "+f"(d[50]), "+f"(d[51]), "+f"(d[52]), "+f"(d[53]), "+f"(d[54]), "+f"(d[55]), "+f"(d[56]), "+f"(d[57]), "+f"(d[58]), "+f"(d[59]), "+f"(d[60]), "+f"(d[61]), "+f"(d[62]), "+f"(d[63]), "+f"(d[64]), "+f"(d[65]), "+f"(d[66]), "+f"(d[67]), "+f"(d[68]), "+f"(d[69]), "+f"(d[70]), "+f"(d[71]), "+f"(d[72]), "+f"(d[73]), "+f"(d[74]), "+f"(d[75]), "+f"(d[76]), "+f"(d[77]), "+f"(d[78]), "+f"(d[79]), "+f"(d[80]), "+f"(d[81]), "+f"(d[82]), "+f"(d[83]), "+f"(d[84]), "+f"(d[85]), "+f"(d[86]), "+f"(d[87]), "+f"(d[88]), "+f"(d[89]), "+f"(d[90]), "+f"(d[91]), "+f"(d[92]), "+f"(d[93]), "+f"(d[94]), "+f"(d[95]), "+f"(d[96]), "+f"(d[97]), "+f"(d[98]), "+f"(d[99]), "+f"(d[100]), "+f"(d[101]), "+f"(d[102]), "+f"(d[103]), "+f"(d[104]), "+f"(d[105]), "+f"(d[106]), "+f"(d[107]), "+f"(d[108]), "+f"(d[109]), "+f"(d[110]), "+f"(d[111]) : "r"(a0), "r"(a1), "r"(a2), "r"(a3), "l"(db), "r"(sd));
}
__device__ __forceinline__ void wg_rs64k(float (&d)[32], uint32_t a0, uint32_t a1, uint32_t a2, uint32_t a3, uint64_t db, int sd) {
  asm volatile("{\n.reg .pred p;\nsetp.ne.b32 p, %37, 0;\n"
  "wgmma.mma_async.sync.aligned.m64n64k16.f32.bf16.bf16 {%0, %1, %2, %3, %4, %5, %6, %7, %8, %9, %10, %11, %12, %13, %14, %15, %16, %17, %18, %19, %20, %21, %22, %23, %24, %25, %26, %27, %28, %29, %30, %31}, {%32, %33, %34, %35}, %36, p, 1, 1, 0;\n}\n"
  : "+f"(d[0]), "+f"(d[1]), "+f"(d[2]), "+f"(d[3]), "+f"(d[4]), "+f"(d[5]), "+f"(d[6]), "+f"(d[7]), "+f"(d[8]), "+f"(d[9]), "+f"(d[10]), "+f"(d[11]), "+f"(d[12]), "+f"(d[13]), "+f"(d[14]), "+f"(d[15]), "+f"(d[16]), "+f"(d[17]), "+f"(d[18]), "+f"(d[19]), "+f"(d[20]), "+f"(d[21]), "+f"(d[22]), "+f"(d[23]), "+f"(d[24]), "+f"(d[25]), "+f"(d[26]), "+f"(d[27]), "+f"(d[28]), "+f"(d[29]), "+f"(d[30]), "+f"(d[31]) : "r"(a0), "r"(a1), "r"(a2), "r"(a3), "l"(db), "r"(sd));
}
__device__ __forceinline__ void wg_rs24(float (&d)[12], uint32_t a0, uint32_t a1, uint32_t a2, uint32_t a3, uint64_t db, int sd) {
  asm volatile("{\n.reg .pred p;\nsetp.ne.b32 p, %17, 0;\n"
  "wgmma.mma_async.sync.aligned.m64n24k16.f32.bf16.bf16 {%0, %1, %2, %3, %4, %5, %6, %7, %8, %9, %10, %11}, {%12, %13, %14, %15}, %16, p, 1, 1, 1;\n}\n"
  : "+f"(d[0]), "+f"(d[1]), "+f"(d[2]), "+f"(d[3]), "+f"(d[4]), "+f"(d[5]), "+f"(d[6]), "+f"(d[7]), "+f"(d[8]), "+f"(d[9]), "+f"(d[10]), "+f"(d[11]) : "r"(a0), "r"(a1), "r"(a2), "r"(a3), "l"(db), "r"(sd));
}
__device__ __forceinline__ void wg_rs128(float (&d)[64], uint32_t a0, uint32_t a1, uint32_t a2, uint32_t a3, uint64_t db, int sd) {
  asm volatile("{\n.reg .pred p;\nsetp.ne.b32 p, %69, 0;\n"
  "wgmma.mma_async.sync.aligned.m64n128k16.f32.bf16.bf16 {%0, %1, %2, %3, %4, %5, %6, %7, %8, %9, %10, %11, %12, %13, %14, %15, %16, %17, %18, %19, %20, %21, %22, %23, %24, %25, %26, %27, %28, %29, %30, %31, %32, %33, %34, %35, %36, %37, %38, %39, %40, %41, %42, %43, %44, %45, %46, %47, %48, %49, %50, %51, %52, %53, %54, %55, %56, %57, %58, %59, %60, %61, %62, %63}, {%64, %65, %66, %67}, %68, p, 1, 1, 1;\n}\n"
  : "+f"(d[0]), "+f"(d[1]), "+f"(d[2]), "+f"(d[3]), "+f"(d[4]), "+f"(d[5]), "+f"(d[6]), "+f"(d[7]), "+f"(d[8]), "+f"(d[9]), "+f"(d[10]), "+f"(d[11]), "+f"(d[12]), "+f"(d[13]), "+f"(d[14]), "+f"(d[15]), "+f"(d[16]), "+f"(d[17]), "+f"(d[18]), "+f"(d[19]), "+f"(d[20]), "+f"(d[21]), "+f"(d[22]), "+f"(d[23]), "+f"(d[24]), "+f"(d[25]), "+f"(d[26]), "+f"(d[27]), "+f"(d[28]), "+f"(d[29]), "+f"(d[30]), "+f"(d[31]), "+f"(d[32]), "+f"(d[33]), "+f"(d[34]), "+f"(d[35]), "+f"(d[36]), "+f"(d[37]), "+f"(d[38]), "+f"(d[39]), "+f"(d[40]), "+f"(d[41]), "+f"(d[42]), "+f"(d[43]), "+f"(d[44]), "+f"(d[45]), "+f"(d[46]), "+f"(d[47]), "+f"(d[48]), "+f"(d[49]), "+f"(d[50]), "+f"(d[51]), "+f"(d[52]), "+f"(d[53]), "+f"(d[54]), "+f"(d[55]), "+f"(d[56]), "+f"(d[57]), "+f"(d[58]), "+f"(d[59]), "+f"(d[60]), "+f"(d[61]), "+f"(d[62]), "+f"(d[63]) : "r"(a0), "r"(a1), "r"(a2), "r"(a3), "l"(db), "r"(sd));
}
__device__ __forceinline__ void wg_rs64(float (&d)[32], uint32_t a0, uint32_t a1, uint32_t a2, uint32_t a3, uint64_t db, int sd) {
  asm volatile("{\n.reg .pred p;\nsetp.ne.b32 p, %37, 0;\n"
  "wgmma.mma_async.sync.aligned.m64n64k16.f32.bf16.bf16 {%0, %1, %2, %3, %4, %5, %6, %7, %8, %9, %10, %11, %12, %13, %14, %15, %16, %17, %18, %19, %20, %21, %22, %23, %24, %25, %26, %27, %28, %29, %30, %31}, {%32, %33, %34, %35}, %36, p, 1, 1, 1;\n}\n"
  : "+f"(d[0]), "+f"(d[1]), "+f"(d[2]), "+f"(d[3]), "+f"(d[4]), "+f"(d[5]), "+f"(d[6]), "+f"(d[7]), "+f"(d[8]), "+f"(d[9]), "+f"(d[10]), "+f"(d[11]), "+f"(d[12]), "+f"(d[13]), "+f"(d[14]), "+f"(d[15]), "+f"(d[16]), "+f"(d[17]), "+f"(d[18]), "+f"(d[19]), "+f"(d[20]), "+f"(d[21]), "+f"(d[22]), "+f"(d[23]), "+f"(d[24]), "+f"(d[25]), "+f"(d[26]), "+f"(d[27]), "+f"(d[28]), "+f"(d[29]), "+f"(d[30]), "+f"(d[31]) : "r"(a0), "r"(a1), "r"(a2), "r"(a3), "l"(db), "r"(sd));
}
#if SPL == 5
__device__ __forceinline__ void wg_rsa(float (&d)[112], uint32_t a0, uint32_t a1, uint32_t a2, uint32_t a3, uint64_t db, int sd) {
  asm volatile("{\n.reg .pred p;\nsetp.ne.b32 p, %85, 0;\n"
  "wgmma.mma_async.sync.aligned.m64n160k16.f32.bf16.bf16 {%0, %1, %2, %3, %4, %5, %6, %7, %8, %9, %10, %11, %12, %13, %14, %15, %16, %17, %18, %19, %20, %21, %22, %23, %24, %25, %26, %27, %28, %29, %30, %31, %32, %33, %34, %35, %36, %37, %38, %39, %40, %41, %42, %43, %44, %45, %46, %47, %48, %49, %50, %51, %52, %53, %54, %55, %56, %57, %58, %59, %60, %61, %62, %63, %64, %65, %66, %67, %68, %69, %70, %71, %72, %73, %74, %75, %76, %77, %78, %79}, {%80, %81, %82, %83}, %84, p, 1, 1, 1;\n}\n"
  : "+f"(d[0]), "+f"(d[1]), "+f"(d[2]), "+f"(d[3]), "+f"(d[4]), "+f"(d[5]), "+f"(d[6]), "+f"(d[7]), "+f"(d[8]), "+f"(d[9]), "+f"(d[10]), "+f"(d[11]), "+f"(d[12]), "+f"(d[13]), "+f"(d[14]), "+f"(d[15]), "+f"(d[16]), "+f"(d[17]), "+f"(d[18]), "+f"(d[19]), "+f"(d[20]), "+f"(d[21]), "+f"(d[22]), "+f"(d[23]), "+f"(d[24]), "+f"(d[25]), "+f"(d[26]), "+f"(d[27]), "+f"(d[28]), "+f"(d[29]), "+f"(d[30]), "+f"(d[31]), "+f"(d[32]), "+f"(d[33]), "+f"(d[34]), "+f"(d[35]), "+f"(d[36]), "+f"(d[37]), "+f"(d[38]), "+f"(d[39]), "+f"(d[40]), "+f"(d[41]), "+f"(d[42]), "+f"(d[43]), "+f"(d[44]), "+f"(d[45]), "+f"(d[46]), "+f"(d[47]), "+f"(d[48]), "+f"(d[49]), "+f"(d[50]), "+f"(d[51]), "+f"(d[52]), "+f"(d[53]), "+f"(d[54]), "+f"(d[55]), "+f"(d[56]), "+f"(d[57]), "+f"(d[58]), "+f"(d[59]), "+f"(d[60]), "+f"(d[61]), "+f"(d[62]), "+f"(d[63]), "+f"(d[64]), "+f"(d[65]), "+f"(d[66]), "+f"(d[67]), "+f"(d[68]), "+f"(d[69]), "+f"(d[70]), "+f"(d[71]), "+f"(d[72]), "+f"(d[73]), "+f"(d[74]), "+f"(d[75]), "+f"(d[76]), "+f"(d[77]), "+f"(d[78]), "+f"(d[79]) : "r"(a0), "r"(a1), "r"(a2), "r"(a3), "l"(db), "r"(sd));
}
__device__ __forceinline__ void wg_rsb(float (&d)[112], uint32_t a0, uint32_t a1, uint32_t a2, uint32_t a3, uint64_t db, int sd) {
  asm volatile("{\n.reg .pred p;\nsetp.ne.b32 p, %37, 0;\n"
  "wgmma.mma_async.sync.aligned.m64n64k16.f32.bf16.bf16 {%0, %1, %2, %3, %4, %5, %6, %7, %8, %9, %10, %11, %12, %13, %14, %15, %16, %17, %18, %19, %20, %21, %22, %23, %24, %25, %26, %27, %28, %29, %30, %31}, {%32, %33, %34, %35}, %36, p, 1, 1, 1;\n}\n"
  : "+f"(d[80]), "+f"(d[81]), "+f"(d[82]), "+f"(d[83]), "+f"(d[84]), "+f"(d[85]), "+f"(d[86]), "+f"(d[87]), "+f"(d[88]), "+f"(d[89]), "+f"(d[90]), "+f"(d[91]), "+f"(d[92]), "+f"(d[93]), "+f"(d[94]), "+f"(d[95]), "+f"(d[96]), "+f"(d[97]), "+f"(d[98]), "+f"(d[99]), "+f"(d[100]), "+f"(d[101]), "+f"(d[102]), "+f"(d[103]), "+f"(d[104]), "+f"(d[105]), "+f"(d[106]), "+f"(d[107]), "+f"(d[108]), "+f"(d[109]), "+f"(d[110]), "+f"(d[111]) : "r"(a0), "r"(a1), "r"(a2), "r"(a3), "l"(db), "r"(sd));
}
#elif SPL == 4
__device__ __forceinline__ void wg_rsa(float (&d)[112], uint32_t a0, uint32_t a1, uint32_t a2, uint32_t a3, uint64_t db, int sd) {
  asm volatile("{\n.reg .pred p;\nsetp.ne.b32 p, %69, 0;\n"
  "wgmma.mma_async.sync.aligned.m64n128k16.f32.bf16.bf16 {%0, %1, %2, %3, %4, %5, %6, %7, %8, %9, %10, %11, %12, %13, %14, %15, %16, %17, %18, %19, %20, %21, %22, %23, %24, %25, %26, %27, %28, %29, %30, %31, %32, %33, %34, %35, %36, %37, %38, %39, %40, %41, %42, %43, %44, %45, %46, %47, %48, %49, %50, %51, %52, %53, %54, %55, %56, %57, %58, %59, %60, %61, %62, %63}, {%64, %65, %66, %67}, %68, p, 1, 1, 1;\n}\n"
  : "+f"(d[0]), "+f"(d[1]), "+f"(d[2]), "+f"(d[3]), "+f"(d[4]), "+f"(d[5]), "+f"(d[6]), "+f"(d[7]), "+f"(d[8]), "+f"(d[9]), "+f"(d[10]), "+f"(d[11]), "+f"(d[12]), "+f"(d[13]), "+f"(d[14]), "+f"(d[15]), "+f"(d[16]), "+f"(d[17]), "+f"(d[18]), "+f"(d[19]), "+f"(d[20]), "+f"(d[21]), "+f"(d[22]), "+f"(d[23]), "+f"(d[24]), "+f"(d[25]), "+f"(d[26]), "+f"(d[27]), "+f"(d[28]), "+f"(d[29]), "+f"(d[30]), "+f"(d[31]), "+f"(d[32]), "+f"(d[33]), "+f"(d[34]), "+f"(d[35]), "+f"(d[36]), "+f"(d[37]), "+f"(d[38]), "+f"(d[39]), "+f"(d[40]), "+f"(d[41]), "+f"(d[42]), "+f"(d[43]), "+f"(d[44]), "+f"(d[45]), "+f"(d[46]), "+f"(d[47]), "+f"(d[48]), "+f"(d[49]), "+f"(d[50]), "+f"(d[51]), "+f"(d[52]), "+f"(d[53]), "+f"(d[54]), "+f"(d[55]), "+f"(d[56]), "+f"(d[57]), "+f"(d[58]), "+f"(d[59]), "+f"(d[60]), "+f"(d[61]), "+f"(d[62]), "+f"(d[63]) : "r"(a0), "r"(a1), "r"(a2), "r"(a3), "l"(db), "r"(sd));
}
__device__ __forceinline__ void wg_rsb(float (&d)[112], uint32_t a0, uint32_t a1, uint32_t a2, uint32_t a3, uint64_t db, int sd) {
  asm volatile("{\n.reg .pred p;\nsetp.ne.b32 p, %53, 0;\n"
  "wgmma.mma_async.sync.aligned.m64n96k16.f32.bf16.bf16 {%0, %1, %2, %3, %4, %5, %6, %7, %8, %9, %10, %11, %12, %13, %14, %15, %16, %17, %18, %19, %20, %21, %22, %23, %24, %25, %26, %27, %28, %29, %30, %31, %32, %33, %34, %35, %36, %37, %38, %39, %40, %41, %42, %43, %44, %45, %46, %47}, {%48, %49, %50, %51}, %52, p, 1, 1, 1;\n}\n"
  : "+f"(d[64]), "+f"(d[65]), "+f"(d[66]), "+f"(d[67]), "+f"(d[68]), "+f"(d[69]), "+f"(d[70]), "+f"(d[71]), "+f"(d[72]), "+f"(d[73]), "+f"(d[74]), "+f"(d[75]), "+f"(d[76]), "+f"(d[77]), "+f"(d[78]), "+f"(d[79]), "+f"(d[80]), "+f"(d[81]), "+f"(d[82]), "+f"(d[83]), "+f"(d[84]), "+f"(d[85]), "+f"(d[86]), "+f"(d[87]), "+f"(d[88]), "+f"(d[89]), "+f"(d[90]), "+f"(d[91]), "+f"(d[92]), "+f"(d[93]), "+f"(d[94]), "+f"(d[95]), "+f"(d[96]), "+f"(d[97]), "+f"(d[98]), "+f"(d[99]), "+f"(d[100]), "+f"(d[101]), "+f"(d[102]), "+f"(d[103]), "+f"(d[104]), "+f"(d[105]), "+f"(d[106]), "+f"(d[107]), "+f"(d[108]), "+f"(d[109]), "+f"(d[110]), "+f"(d[111]) : "r"(a0), "r"(a1), "r"(a2), "r"(a3), "l"(db), "r"(sd));
}
#endif

#define wg_rsa wg_rs224
#define wg_rsb wg_rs224

__device__ __forceinline__ uint32_t kv_addr(int i) {
  return 94208u + KVB * (uint32_t)((0x103254u >> (4 * i)) & 15u);
}
__device__ __forceinline__ uint32_t w1b_addr(int s) {
  return (s == 3 || s == 4) ? (uint32_t)(s - 3) * 35840u : 102400u + (uint32_t)(s >= 5 ? s - 5 : s) * 35840u;
}
__device__ __forceinline__ void stg128(void* p, uint32_t a, uint32_t b, uint32_t c, uint32_t d) {
  asm volatile("st.relaxed.gpu.global.v4.u32 [%0], {%1,%2,%3,%4};" ::"l"(p), "r"(a), "r"(b), "r"(c), "r"(d) : "memory");
}
__device__ __forceinline__ void ld_tile(uint32_t (&a)[20], const uint8_t* p, int c, int i) {
  p += ((c + i) & 7) * 10240;
#pragma unroll
  for (int k = 0; k < 5; k++)
    asm volatile("ld.relaxed.gpu.global.v4.u32 {%0,%1,%2,%3}, [%4];" : "=r"(a[4 * k]), "=r"(a[4 * k + 1]), "=r"(a[4 * k + 2]), "=r"(a[4 * k + 3]) : "l"(p + k * 512) : "memory");
}
__device__ __forceinline__ uint32_t tag16(uint32_t v, uint32_t tag) { return (v & ~TAGM) | tag; }
__device__ __forceinline__ float tag32(float v, uint32_t ep) { return __uint_as_float((__float_as_uint(v) & ~3u) | ep); }
__device__ __forceinline__ void fix_tile(uint32_t (&a)[20], const uint8_t* p, int c, int i, uint32_t tag) {
  uint32_t n = 0;
  while (__any_sync(0xffffffffu, (((a[0] ^ tag) | (a[4] ^ tag) | (a[8] ^ tag) | (a[12] ^ tag) | (a[16] ^ tag)) & TAGM) != 0u) && ++n < SPIN_MAX) ld_tile(a, p, c, i);
}
__device__ __forceinline__ void probe_wait(uint32_t& ready, int i, const void* p, uint32_t tag) {
  uint32_t n = 0;
  while (!((ready >> i) & 1u) && ++n < SPIN_MAX) ready = __ballot_sync(0xffffffffu, ldcg32(p) == tag);
}
__device__ __forceinline__ float4 gather8(const float* p, int stride, uint32_t ep) {
  uint4 v[8];
  uint32_t n = 0, bad;
  do {
    bad = 0;
#pragma unroll
    for (int i = 0; i < 8; i++) v[i] = ldcg128(p + i * stride);
#pragma unroll
    for (int i = 0; i < 8; i++) bad |= (v[i].x ^ ep) | (v[i].w ^ ep);
  } while (__any_sync(0xffffffffu, (bad & 3u) != 0u) && ++n < SPIN_MAX);
  float4 s = make_float4(0.f, 0.f, 0.f, 0.f);
#pragma unroll
  for (int i = 0; i < 8; i++) { s.x += __uint_as_float(v[i].x); s.y += __uint_as_float(v[i].y); s.z += __uint_as_float(v[i].z); s.w += __uint_as_float(v[i].w); }
  return s;
}

__device__ __forceinline__ uint64_t desc2(uint32_t lo, uint32_t hi) { uint64_t d; asm("mov.b64 %0, {%1, %2};" : "=l"(d) : "r"(lo), "r"(hi)); return d; }
template <int H>
__device__ __forceinline__ void qk_issue(float (&s)[32], const uint32_t (&q)[24], uint32_t m0, uint32_t m1, uint32_t kd) {
  constexpr int J0 = (H == 0) ? 0 : (H == 1) ? 2 : (H == 2) ? 5 : 7;
  wg_rs64k(s, q[H * 6 + 0], q[H * 6 + 1], q[H * 6 + 2], q[H * 6 + 3], desc2(kd + (0x400000u + J0 * 64), 8u), 0);
  wg_rs64k(s, q[H * 6 + 4], q[H * 6 + 5], m0, m1, desc2(kd + (((10 - J0) * 64u << 16) + (J0 + 2) * 64), 8u), 1);
}
template <int H, int FIRST>
__device__ __forceinline__ void pv_issue(float (&o)[12], const uint32_t (&p)[16], uint32_t kd) {
  if (FIRST && H == 3) return;
#pragma unroll
  for (int i = 0; i < 4; i++)
    wg_rs24(o, p[4 * i], p[4 * i + 1], p[4 * i + 2], p[4 * i + 3], desc2(kd + (0x80000u + 640 + 3 * H * 64 + i * 16), 64u), i || !FIRST);
}
#define PKP(lo, hi) pack2(lo, hi)
template <int KIND>
__device__ __forceinline__ void sm_exp(const float (&s)[32], uint32_t (&p)[16], const uint32_t (&nk)[8], int w) {
#define EXU(i) PKP(ex2(s[2 * (i)]), ex2(s[2 * (i) + 1]))
  if (KIND == 0) {
#pragma unroll
    for (int i = 0; i < 16; i++) p[i] = EXU(i);
  } else {
#pragma unroll
    for (int u = 1; u < 4; u++) {
      const int i0 = KIND == 1 ? 2 * u : 15 - 2 * u, i1 = KIND == 1 ? 17 - 2 * u : 2 * u - 2;
      const uint32_t e = PKP(ex2(w >= u ? s[2 * i0] : s[2 * i1]), ex2(w >= u ? s[2 * i0 + 1] : s[2 * i1 + 1]));
      p[i0] = e & (KIND == 1 ? ~nk[i0 >> 1] : nk[i0 >> 1]);
      p[i1] = e & (KIND == 1 ? ~nk[i1 >> 1] : nk[i1 >> 1]);
    }
    if (KIND == 1) {
      p[0] = EXU(0) & ~nk[0];
      p[9] = EXU(9) & ~nk[4];
    } else {
      p[6] = EXU(6) & nk[3];
      p[15] = EXU(15) & nk[7];
    }
#pragma unroll
    for (int t = 0; t < 4; t++) {
      p[2 * t + (KIND == 1 ? 1 : 8)] = EXU(2 * t + (KIND == 1 ? 1 : 8));
      p[2 * t + (KIND == 1 ? 8 : 1)] = 0u;
    }
  }
#pragma unroll
  for (int i = 0; i < 16; i++) asm volatile("" : "+r"(p[i])::"memory");
}
__device__ __forceinline__ void mma16816(float* d, uint32_t a0, uint32_t a1, uint32_t a2, uint32_t a3, uint32_t b0, uint32_t b1) {
  asm volatile("mma.sync.aligned.m16n8k16.row.col.f32.bf16.bf16.f32 {%0,%1,%2,%3}, {%4,%5,%6,%7}, {%8,%9}, {%0,%1,%2,%3};"
               : "+f"(d[0]), "+f"(d[1]), "+f"(d[2]), "+f"(d[3]) : "r"(a0), "r"(a1), "r"(a2), "r"(a3), "r"(b0), "r"(b1));
}
__device__ __forceinline__ void safe_head(float (&o)[12], const uint32_t (&q)[6], int H, const uint8_t* kv, uint32_t seq, int nit, int d0, int d1, int tq, uint32_t tag) {
  const int J0 = (5 * H) >> 1;
  float m0 = -INFINITY, m1 = -INFINITY;
#pragma unroll
  for (int i = 0; i < 12; i++) o[i] = 0.f;
#pragma unroll 1
  for (int st = 0; st < 4 * nit; st++) {
    const uint8_t* a = kv + (size_t)((seq >> (st & 28)) & 15) * (8 * KVB) + (st & 3) * 256;
    uint32_t b[12], bad, n = 0;
    do {
      bad = 0;
#pragma unroll
      for (int i = 0; i < 12; i++) {
        b[i] = ldcg32(a + ((i < 6 ? J0 : 7 + 3 * H) + (i >> 1)) * 1024 + (i & 1) * 128);
        bad |= b[i] ^ tag;
      }
    } while (__any_sync(0xffffffffu, tq == 1 && (bad & TAGM) != 0u) && ++n < SPIN_MAX);
    float s[8];
#pragma unroll
    for (int i = 0; i < 8; i++) s[i] = 0.f;
#pragma unroll
    for (int t = 0; t < 2; t++) {
      mma16816(&s[4 * t], q[0], q[1], q[2], q[3], b[t], b[2 + t]);
      mma16816(&s[4 * t], q[4], q[5], 0u, 0u, b[4 + t], 0u);
    }
    if (st < 4 || st >= 16) {
#pragma unroll
      for (int i = 0; i < 8; i++)
        if (((st & 3) * 16 + (i >> 2) * 8 + (i & 1) <= ((i & 2) ? d1 : d0)) != (st < 4)) s[i] = -INFINITY;
    }
    float n0 = fmaxf(fmaxf(s[0], s[1]), fmaxf(s[4], s[5])), n1 = fmaxf(fmaxf(s[2], s[3]), fmaxf(s[6], s[7]));
    n0 = fmaxf(n0, __shfl_xor_sync(0xffffffffu, n0, 1));
    n1 = fmaxf(n1, __shfl_xor_sync(0xffffffffu, n1, 1));
    n0 = fmaxf(m0, fmaxf(n0, __shfl_xor_sync(0xffffffffu, n0, 2)));
    n1 = fmaxf(m1, fmaxf(n1, __shfl_xor_sync(0xffffffffu, n1, 2)));
    const float al0 = ex2(m0 - n0), al1 = ex2(m1 - n1);
    m0 = n0;
    m1 = n1;
    const uint32_t p0 = pack2(ex2(s[0] - n0), ex2(s[1] - n0)), p1 = pack2(ex2(s[2] - n1), ex2(s[3] - n1));
    const uint32_t p2 = pack2(ex2(s[4] - n0), ex2(s[5] - n0)), p3 = pack2(ex2(s[6] - n1), ex2(s[7] - n1));
#pragma unroll
    for (int i = 6; i < 12; i++) asm volatile("movmatrix.sync.aligned.m8n8.trans.b16 %0, %0;" : "+r"(b[i]));
#pragma unroll
    for (int t = 0; t < 3; t++) {
      o[4 * t] *= al0; o[4 * t + 1] *= al0; o[4 * t + 2] *= al1; o[4 * t + 3] *= al1;
      mma16816(&o[4 * t], p0, p1, p2, p3, b[6 + 2 * t], b[7 + 2 * t]);
    }
  }
}
#define ATT_STEP(KIND, HQ, sq, kq, HP, op, pp, kv, sc, pc, W) do { \
  WG_FENCE(); qk_issue<HQ>(sq, q, qm[2 * HQ], qm[2 * HQ + 1], kq); WG_COMMIT(); WG_WAIT(1); pv_issue<HP, KIND == 1>(op, pp, kv); WG_COMMIT(); \
  sm_exp<KIND>(sc, pc, nk, w); WG_WAIT(W); reg_fence(sq); } while (0)
__device__ __forceinline__ uint32_t bmul2(uint32_t a, uint32_t b) { uint32_t d; asm("mul.rn.bf16x2 %0, %1, %2;" : "=r"(d) : "r"(a), "r"(b)); return d; }
__device__ __forceinline__ uint32_t badd2(uint32_t a, uint32_t b) { uint32_t d; asm("add.rn.bf16x2 %0, %1, %2;" : "=r"(d) : "r"(a), "r"(b)); return d; }
__device__ __forceinline__ uint32_t bfma2(uint32_t a, uint32_t b, uint32_t c) { uint32_t d; asm("fma.rn.bf16x2 %0, %1, %2, %3;" : "=r"(d) : "r"(a), "r"(b), "r"(c)); return d; }

__global__ void __cluster_dims__(2, 1, 1) __launch_bounds__(384, 1) fused_block_kernel(const __grid_constant__ Params P) {
  extern __shared__ __align__(1024) uint8_t smem[];
  const uint32_t sb = s2u(smem);
  const int tid = threadIdx.x, lane = tid & 31, warp = __shfl_sync(0xffffffffu, tid >> 5, 0);
  const uint32_t bars = sb + OFF_MISC;
#define BAR(i) (bars + 8u * (uint32_t)(i))
#define TP(i)
  const uint32_t rank = blockIdx.x & 1;
  const uint32_t mp = P.map[blockIdx.x >> 3] >> ((blockIdx.x & 6) * 4);
  const int c = mp & 7, rb = (int)(((mp >> 2) & 14) + rank);
  const int tile = rb * 8 + c;
  const int mainch = (c * 5) >> 1, leftch = c * 5 + 4;
  const CUtensorMap* mWqM = &P.mWqM[c & 1];
  const int kb0 = (5 * (rb >> 1)) >> 2;
#define FIRST_PF() do { if (tid < 192 + 16 * XPN) {     \
    const int kx = kb0 + ((tid - 192) >> 4); \
    const uint8_t* pp = tid < 192 ? reinterpret_cast<const uint8_t*>(P.wqkv) + (size_t)(kb0 * 64 + (int)rank * 32 + (tid & 31)) * 3840 + (tid >> 6) * 1280 + c * 160 + (tid & 32) * 4 \
                                  : reinterpret_cast<const uint8_t*>(P.x) + (size_t)(rb * 128 + c * 16 + (tid & 15)) * 1280 + (XPN == 1 ? kb0 : XPN == 2 || kx < 10 ? kx : kx - 10) * 128; \
    l2_prefetch(pp); \
    if (WP2 && tid < 192 && (WP2 == 2 || (rb & 6) == 6)) l2_prefetch(pp + 64 * 3840); } } while (0)
  if (EPF == 3) FIRST_PF();
  if (tid == 288) {
#pragma unroll
    for (int u = 0; u < 6; u++) mbar_init(BAR(u), 1);
    asm volatile("fence.mbarrier_init.release.cluster;" ::: "memory");
  }
  __syncwarp();
  if (EPF == 4) FIRST_PF();
  asm volatile("barrier.cluster.arrive.relaxed.aligned;" ::: "memory");
  TP(0);
  if (EPF == 2) FIRST_PF();
  if (lane == 0 && (EPD && EPD < 4 ? warp < 8 : (warp >> 1) != 4)) {
    const int j = warp < 8 ? warp + 3 : warp - 9;
    const int cnt = (int)(0x4a108208108421ull >> (5 * j)) & 31;
#pragma unroll
    for (int u = 0; u < 6; u++) mbar_init(BAR(j * 6 + u), cnt);
    asm volatile("fence.mbarrier_init.release.cluster;" ::: "memory");
  }
  __syncwarp();
  if (EPF == 1) FIRST_PF();
  TP(1);
  if (warp >= 8) asm volatile("setmaxnreg.dec.sync.aligned.u32 56;");
  TP(2);
  if (warp > 8) {
    asm volatile("bar.arrive 1, 384;" ::: "memory");
    if (lane == 0) {
      if (warp == 9) {
        mbar_expect(BAR(B_QFULL), QST);
        tma2d(sb, &P.mX, kb0 * 64, rb * 128, BAR(B_QFULL));
      } else {
        asm volatile("prefetch.tensormap [%0];" ::"l"(warp == 10 ? mWqM : &P.mWqL) : "memory");
      }
    }
    __syncwarp();
    asm volatile("bar.sync 2, 128;" ::: "memory");
  } else {
    asm volatile("bar.sync 1, 384;" ::: "memory");
  }
  TP(3);
  if (EPF == 0) FIRST_PF();
  if (warp == 8) {
    asm volatile("bar.arrive 2, 128;\nbarrier.cluster.wait.acquire.aligned;" ::: "memory");
    TP(4);
    if (lane == 0) {
#pragma unroll 1
      for (int kt = 0; kt < 4; kt++) {
        const uint32_t a = sb + kt * QST, fb = BAR(B_QFULL + kt);
        const int k0 = (kb0 + kt < 10 ? kb0 + kt : kb0 + kt - 10) * 64;
        if (kt) mbar_expect(fb, QST);
        tma4d_mc(a + 16384 + rank * 12288, mWqM, 0, k0 + rank * 32, mainch, 0, fb);
        tma4d_mc(a + 40960 + rank * 3072, &P.mWqL, 0, k0 + rank * 32, leftch, 0, fb);
        if (kt) tma2d(a, &P.mX, k0, rb * 128, fb);
        if (kt == 0) TP(5);
        if (kt == XRP) {
          mbar_expect(BAR(B_XROW), 20480);
          bulk_load(sb + OFF_XROW, reinterpret_cast<const uint8_t*>(P.x) + (size_t)(rb * 128 + c * 16) * 1280, 20480, BAR(B_XROW));
        }
      }
    } else if (lane < 4) mbar_arrive(BAR(B_XROW));
    __syncwarp();
    STAMPW(9);
  }
  const int sc = (27 * c + 3) >> 2;

  if (warp >= 8) {
    const uint32_t epoch = __shfl_sync(0xffffffffu, ldcg32(&g_epoch[tile * 32 + lane]), 0) + 1u;
    const uint32_t ep = epoch & 3u, tag = (epoch & 1u) | ((epoch & 2u) << 15);
    if (warp == 8) {
      if (lane == 0) {
#pragma unroll 1
        for (int kt = 4; kt < 10; kt++) {
          const int st = kt & 3;
          mbar_wait(BAR(B_QEMPTY + st), ((kt >> 2) - 1) & 1);
          const uint32_t a = sb + st * QST, fb = BAR(B_QFULL + st);
          const int k0 = (kb0 + kt < 10 ? kb0 + kt : kb0 + kt - 10) * 64;
          mbar_expect(fb, QST);
          tma4d_mc(a + 16384 + rank * 12288, mWqM, 0, k0 + rank * 32, mainch, 0, fb);
          tma4d_mc(a + 40960 + rank * 3072, &P.mWqL, 0, k0 + rank * 32, leftch, 0, fb);
          tma2d(a, &P.mX, k0, rb * 128, fb);
        }
        l2_prefetch_bulk(reinterpret_cast<const uint8_t*>(P.wo) + tile * 6400, 6400);
        l2_prefetch_bulk(reinterpret_cast<const uint8_t*>(P.w1) + tile * 17280, 17280);
        l2_prefetch_bulk(reinterpret_cast<const uint8_t*>(P.w2) + tile * 17280, 17280);
        const CUtensorMap* mW1 = rank ? &P.mW1b : &P.mW1a;
        asm volatile("prefetch.tensormap [%0];" ::"l"(&P.mWo) : "memory");
        asm volatile("prefetch.tensormap [%0];" ::"l"(mW1) : "memory");
        asm volatile("prefetch.tensormap [%0];" ::"l"(&P.mW2) : "memory");
        if (XT) asm volatile("prefetch.tensormap [%0];" ::"l"(&P.mXr) : "memory");
      }
      __syncwarp();
      if (C8 == 1) mbar_wait(BAR(B_QFULL + 1), 0);
      {
        const int l16 = lane & 15, col = sc * 32 + (int)rank * 112 + l16 * 8;
        const uint8_t* wb = reinterpret_cast<const uint8_t*>(P.w1) + (size_t)((rb >> 1) * 80 + (lane >> 4) * 40) * 3456 + (size_t)col * 2;
        float acc[8];
#pragma unroll
        for (int i = 0; i < 8; i++) acc[i] = 0.f;
        if (l16 < 14 && col < 1728 && !(XNO & 1)) {
#pragma unroll 1
          for (int i = 0; i < 40; i += CSU) {
            uint4 v[CSU];
#pragma unroll
            for (int u = 0; u < CSU; u++) v[u] = __ldg(reinterpret_cast<const uint4*>(wb + (size_t)(i + u) * 3456));
#pragma unroll
            for (int u = 0; u < CSU; u++) {
              acc[0] += bf_lo(v[u].x); acc[1] += bf_hi(v[u].x); acc[2] += bf_lo(v[u].y); acc[3] += bf_hi(v[u].y);
              acc[4] += bf_lo(v[u].z); acc[5] += bf_hi(v[u].z); acc[6] += bf_lo(v[u].w); acc[7] += bf_hi(v[u].w);
            }
          }
        }
        __syncwarp();
#pragma unroll
        for (int i = 0; i < 4; i++) {
          const float o = __shfl_xor_sync(0xffffffffu, lane < 16 ? acc[4 + i] : acc[i], 16);
          acc[i] = tag32((lane < 16 ? acc[i] : acc[4 + i]) + o, ep);
        }
        if (l16 < 14) *reinterpret_cast<float4*>(&g_cs1[((rb >> 1) * 8 + c) * 224 + rank * 112 + l16 * 8 + (lane >> 4) * 4]) = make_float4(acc[0], acc[1], acc[2], acc[3]);
        STAMPW(4);
      }
      if (lane == 0) {
        const CUtensorMap* mW1 = rank ? &P.mW1b : &P.mW1a;
        mbar_wait(BAR(B_QEMPTY + 1), 0);
        if (rb) mbar_wait(BAR(B_KVFULL + 3), 0);
        mbar_expect(BAR(B_WOB), 89600);
#pragma unroll 1
        for (int i = 0; i < 4 - (int)rank; i++) {
          const int pos = rank * 4 + i;
          tma3d_mc(sb + OFF_WOB + pos * 12800, &P.mWo, 0, ((c + pos) & 7) * 80, c * 5, BAR(B_WOB));
        }
#pragma unroll 1
        for (int s = 0; s < 8; s++) {
          if (s == 0) {
            mbar_wait(BAR(B_ATT2), 0);
            mbar_expect(BAR(B_WOB7), 12800);
            if (rank) tma3d_mc(sb + OFF_WOB + 7 * 12800, &P.mWo, 0, ((c + 7) & 7) * 80, c * 5, BAR(B_WOB7));
            mbar_wait(BAR(B_OL1), 0);
          } else if (s == 1) mbar_wait(BAR(B_ATT4), 0);
          else if (s == 3 || s == 4) mbar_wait(BAR(s == 3 ? B_WODP : B_WODP2), 0);
          else if (s >= 5) mbar_wait(BAR(B_BEMPTY + s - 5), 0);
          const uint32_t fb = BAR(B_BFULL + s);
          mbar_expect(fb, 35840);
          tma3d_mc(sb + w1b_addr(s) + rank * 20480, mW1, 0, ((c + s) & 7) * 80, sc + rank * 4, fb);
        }
#pragma unroll 1
        for (int u = 0; u < 10; u++) {
          if (u == W2D) mbar_wait(BAR(B_BFULL + 7), 0);
          if (u < 6) mbar_wait(BAR(B_BEMPTY + (((S6 ? 0x776543u : 0x665443u) >> (4 * u)) & 7)), 0);
          else mbar_wait(BAR(B_QEMPTY + 2 + (u & 3)), (u >> 3) & 1);
          const uint32_t fb = BAR(u < 5 ? B_W2FULL + u : B_BFULL - 5 + u);
          mbar_expect(fb, 28672);
          tma2d_mc(sb + (u < 6 ? u : u - 6) * 28672 + rank * 14336, &P.mW2, (c + u < 10 ? c + u : c + u - 10) * 64, sc * 32 + rank * 112, fb);
        }
      }
      __syncwarp();
    } else {
      float2* xst = &g_xstat[tile * 24 + (warp - 9) * 8 + (lane & 3) * 2 + (lane >> 4)];
      if ((lane & 15) < 4) *xst = make_float2(0.f, tag32(0.f, ep ^ 1u));
      if (warp == 11) {
        mbar_wait(BAR(B_PRE), 0);
        if (lane < 30) {
          float4 a = make_float4(0.f, 0.f, 0.f, 0.f);
#pragma unroll 4
          for (int i = 0; i < 16; i++) {
            const float4 v = *reinterpret_cast<const float4*>(smem + OFF_PRE + i * 512 + lane * 16);
            a.x += v.x; a.y += v.y; a.z += v.z; a.w += v.w;
          }
          *reinterpret_cast<float4*>(&g_csq[((rb >> 1) * 8 + c) * 240 + rank * 120 + lane * 4]) = make_float4(tag32(a.x, ep), tag32(a.y, ep), tag32(a.z, ep), tag32(a.w, ep));
        }
        __syncwarp();
        STAMPW(0);
      }
      mbar_wait(BAR(B_XROW), 0);
      if (warp == 9) STAMPW(8);
      {
        float s3[3] = {0.f, 0.f, 0.f}, m3[3] = {0.f, 0.f, 0.f}, sh[3];
        const uint32_t xb = sb + OFF_XROW + ((warp - 9) * 2 + (lane >> 4)) * 1280, x2 = warp == 11 ? 7680 : 15360;
#pragma unroll
        for (int p = 0; p < 3; p++) {
          uint32_t u0;
          asm volatile("ld.shared.u32 %0, [%1];" : "=r"(u0) : "r"(xb + (p < 2 ? p * 7680 : x2)) : "memory");
          sh[p] = bf_lo(u0);
        }
#pragma unroll 1
        for (int i = 0; i < 5; i++) {
          uint32_t u[12];
#pragma unroll
          for (int p = 0; p < 3; p++)
            asm volatile("ld.shared.v4.u32 {%0,%1,%2,%3}, [%4];" : "=r"(u[4 * p]), "=r"(u[4 * p + 1]), "=r"(u[4 * p + 2]), "=r"(u[4 * p + 3])
                         : "r"(xb + (p < 2 ? p * 7680 : x2) + (lane & 15) * 16 + i * 256) : "memory");
#define XS_ACC(j) do { \
            const float d0 = bf_lo(u[j]) - sh[(j) >> 2], d1 = bf_hi(u[j]) - sh[(j) >> 2]; \
            s3[(j) >> 2] += d0 + d1; \
            m3[(j) >> 2] = fmaf(d1, d1, fmaf(d0, d0, m3[(j) >> 2])); } while (0)
#pragma unroll
          for (int j = 0; j < 8; j++) XS_ACC(j);
          if (warp != 11) {
            asm volatile("" ::: "memory");
#pragma unroll
            for (int j = 8; j < 12; j++) XS_ACC(j);
          }
        }
#pragma unroll
        for (int o = 8; o; o >>= 1)
#pragma unroll
          for (int i = 0; i < 3; i++) {
            s3[i] += __shfl_xor_sync(0xffffffffu, s3[i], o);
            m3[i] += __shfl_xor_sync(0xffffffffu, m3[i], o);
          }
        const int p = lane & 15;
        const float s = (p == 0 ? s3[0] : p == 1 ? s3[1] : s3[2]) * (1.f / 640.f), m2 = (p == 0 ? m3[0] : p == 1 ? m3[1] : m3[2]) * (1.f / 640.f);
        if (p < 4) *xst = make_float2((p == 0 ? sh[0] : p == 1 ? sh[1] : sh[2]) + s, tag32(rsqrtf(fmaxf(fmaf(-s, s, m2), 0.f) + 1e-5f), ep));
      }
      if (warp == 9) STAMPW(17);
      if (warp != 11) {
        if (warp == 10) {
          mbar_wait(BAR(B_QEMPTY + 3), 0);
          uint4 v0, v1;
          uint32_t n = 0;
          const float2* xs = &g_xstat[(rb * 8 + (lane >> 3)) * 24 + ((lane & 7) % 3) * 8 + ((lane & 7) / 3) * 2];
          do {
            v0 = ldcg128(xs);
            v1 = ldcg128(xs + 96);
          } while (__any_sync(0xffffffffu, (((v0.y ^ ep) | (v0.w ^ ep) | (v1.y ^ ep) | (v1.w ^ ep)) & 3u) != 0u) && ++n < SPIN_MAX);
          *reinterpret_cast<uint4*>(smem + OFF_XST + lane * 16) = v0;
          *reinterpret_cast<uint4*>(smem + OFF_XST + 512 + lane * 16) = v1;
          __syncwarp();
          if (lane < 2) mbar_arrive(BAR(B_STAT));
          STAMPW(18);
        }
        if (warp == 10 && lane == 0) {
#pragma unroll 1
          for (int i = 0; i < 1 + KVP; i++) {
            if (i < 2) mbar_wait(BAR(B_KVOWN + i), 0);
            const uint32_t off = i ? (uint32_t)(i - 1) * (KVB / KVP) + KVB : 0u;
            asm volatile("cp.async.bulk.wait_group.read 0;\ncp.async.bulk.global.shared::cta.bulk_group [%0], [%1], %2;\ncp.async.bulk.commit_group;"
                         ::"l"(g_kv + (size_t)(rb * 16 + c) * KVB + (i ? 7 * KVB + off : 0u)), "r"(sb + kv_addr(4) + off), "r"(i ? KVB / KVP : KVB) : "memory");
          }
          asm volatile("cp.async.bulk.wait_group.read 0;" ::: "memory");
          mbar_arrive_pair(BAR(B_ATT2));
          STAMPW(6);
        }
        __syncwarp();
      }
      if (warp != 10) {
        const int u = (warp - 9) * 16 + lane;
        mbar_wait(BAR(B_QEMPTY + 3), 0);
        const float4 cs = gather8(g_csq + c * 240 + min(u, 59) * 4, 1920, ep);
        if (u < 60) {
          const uint32_t h0 = pack2(cs.x, cs.y), h1 = pack2(cs.z, cs.w);
          const uint32_t l0 = pack2(cs.x - bf_lo(h0), cs.y - bf_hi(h0)), l1 = pack2(cs.z - bf_lo(h1), cs.w - bf_hi(h1));
          const int mat = u / 20, j = u - mat * 20;
          const bool mn = j < 16;
          uint8_t* d = smem + OFF_PRE + (mn ? (mat * 2 + (j >> 3)) * 512 : 3072 + mat * 256) + (j & 1) * 8;
#pragma unroll
          for (int i = 0; i < 4; i++) {
            uint8_t* e = d + (mn ? i * 128 + (((j >> 1) ^ i) & 3) * 16 : i * 64 + (((j >> 1) ^ (i >> 1)) & 1) * 16);
            *reinterpret_cast<uint2*>(e) = make_uint2(h0, h1);
            *reinterpret_cast<uint2*>(e + (mn ? 64 : 32)) = make_uint2(l0, l1);
          }
        }
        fence_async_smem();
        __syncwarp();
        if (lane == 0) mbar_arrive(BAR(B_STAT));
        if (warp == 9) STAMPW(16);
        mbar_wait(BAR(B_QEMPTY + 1), 1);
      }
      if (warp == 9) STAMPW(19);
#pragma unroll 1
      for (int bi = warp == 9 ? 2 : warp == 10 ? 3 : 1; bi >= 0; bi -= (warp == 9 ? 2 : 4)) {
        const int blk = 2 * rb - 4 + bi;
        if (blk < 0) continue;
        const uint8_t* src = g_kv + (size_t)(blk * 8 + c) * KVB;
        const uint32_t dst = sb + kv_addr(bi);
        uint32_t n = 0, ph = 0;
        while (!__all_sync(0xffffffffu, ((ldcg32(src + lane * 704 + 692) ^ tag) & TAGM) == 0u) && ++n < SPIN_MAX) {}
        if (warp == 9 && bi == 2) STAMPW(3);
        mbar_wait(BAR(B_QEMPTY + 1), 0);
        while (true) {
          if (lane == 0) {
            mbar_expect(BAR(B_KVLAND + bi), KVB);
            bulk_load(dst, src, KVB, BAR(B_KVLAND + bi));
          }
          mbar_wait(BAR(B_KVLAND + bi), ph);
          ph ^= 1u;
          uint32_t bad = 0;
#pragma unroll 11
          for (int i = 0; i < 44; i++) {
            uint32_t v;
            asm volatile("ld.shared.u32 %0, [%1];" : "=r"(v) : "r"(dst + (i * 32 + lane) * 16 + 4) : "memory");
            bad |= v ^ tag;
          }
          if (!__any_sync(0xffffffffu, (bad & TAGM) != 0u) || ++n >= SPIN_MAX) break;
        }
        if (lane == 0) {
          mbar_arrive(BAR(B_KVFULL + bi));
        }
        if (warp == 9 && bi == 2) STAMPW(5);
        if (warp == 10) STAMPW(7);
      }
      __syncwarp();
      asm volatile("barrier.cluster.wait.acquire.aligned;" ::: "memory");
      if (warp == 10) {
      } else if (warp == 9) {
#pragma unroll 1
        for (int r = 1; r >= 0; r--) {
          const int cc = (c + 1 + (lane >> 2)) & 7;
          const uint32_t* hp = &g_hint[((rb * 2 + r) * 8 + cc) * HS + (lane & 3)];
          const uint32_t fb = BAR(r ? B_QFULL : B_KVFULL);
          const uint32_t dst = sb + (r ? 102400u : lane < 12 ? 179200u : 107520u) + (lane >> 2) * 10240;
          mbar_wait(BAR(r ? B_ATT2 : B_ATTL), 0);
          if (lane < 4) mbar_expect(fb + lane * 8, lane < 3 ? 20480 : 10240);
          if (XT && lane == 28) {
            mbar_expect(BAR(B_OUTOK + r), 10240);
            tma2d(sb + (r ? 143360u : OFF_HST), &P.mXr, c * 80, rb * 128 + r * 64, BAR(B_OUTOK + r));
          }
          if (!L5) mbar_wait(BAR(B_ATT3), 0);
          uint32_t n = 0, todo = 0x1111111u;
          while (todo) {
            uint32_t ok = __ballot_sync(0xffffffffu, ldcg32(hp) == tag || n >= SPIN_MAX);
            ok &= ok >> 1;
            ok &= (ok >> 2) & todo;
            if (!mbar_test(BAR(r ? B_ATT3 : B_OL1L))) ok &= r ? 0xffffu : 0xfffu;
            if ((ok >> lane) & 1u) bulk_load(dst, g_o + (size_t)(rb * 16 + r * 8 + cc) * 10240, 10240, fb + (lane >> 3) * 8);
            todo &= ~ok;
            if (++n > 2 * SPIN_MAX) break;
          }
        }
      } else if (warp == 11) {
        mbar_wait(BAR(CLATE == 1 ? B_ATT4 : CLATE == 2 ? B_HST : C8 ? B_ATTL : B_ATT3), 0);
#pragma unroll 1
        for (int u = lane; u < 64; u += 32) {
          const float4 cs = gather8(g_cs1 + c * 224 + min(u, 55) * 4, 1792, ep);
          const uint32_t h0 = pack2(cs.x, cs.y), h1 = pack2(cs.z, cs.w);
          if (u < 56) *reinterpret_cast<uint4*>(smem + OFF_XS + u * 16) = make_uint4(h0, h1, pack2(cs.x - bf_lo(h0), cs.y - bf_hi(h0)), pack2(cs.z - bf_lo(h1), cs.w - bf_hi(h1)));
        }
        __syncwarp();
        if (lane == 0) mbar_arrive(BAR(B_CS1));
        STAMPW(1);
      }
    }
    if (warp == 9 || warp == 10) {
      const int r = warp - 9;
      uint32_t* fl = &g_oflag[(rb * 2 + r) * 8];
      if (lane < (SLIM ? 2 : 5) && r) asm volatile("prefetch.tensormap [%0];" ::"l"(&P.mOutH + lane) : "memory");
      mbar_wait(BAR(B_HST + r), KF && !r);
      if (lane == 0) {
        asm volatile("cp.async.bulk.tensor.2d.global.shared::cta.bulk_group [%0, {%2, %3}], [%1];\ncp.async.bulk.commit_group;\ncp.async.bulk.wait_group.read 0;"
                     ::"l"(&P.mOutH), "r"(sb + OFF_HST + r * 10240), "r"(c * 80), "r"(rb * 128 + r * 64) : "memory");
        if (S6 && r) mbar_arrive_pair(BAR(B_WOE));
        asm volatile("cp.async.bulk.wait_group 0;\nfence.proxy.async.global;\nst.release.gpu.global.u32 [%0], %1;" ::"l"(fl + c), "r"(epoch) : "memory");
      }
      __syncwarp();
      if (r) {
        mbar_wait(BAR(B_CS1), 0);
#pragma unroll 1
        for (int u = lane; u < 56; u += 32) {
          const uint4 v = *reinterpret_cast<const uint4*>(smem + OFF_XS + u * 16);
#pragma unroll
          for (int i = 0; i < 4; i++) {
            uint8_t* d = smem + OFF_W1X + (u >> 3) * 512 + i * 128 + ((((u >> 1) ^ i) & 3) * 16) + (u & 1) * 8;
            *reinterpret_cast<uint2*>(d) = make_uint2(v.x, v.y);
            *reinterpret_cast<uint2*>(d + 64) = make_uint2(v.z, v.w);
          }
        }
        fence_async_smem();
        __syncwarp();
        if (lane == 0) mbar_arrive(BAR(B_CS1));
        STAMPW(1);
      }
      if (lane < 6) mbar_init(BAR((lane < 3 ? B_OFULL : B_OFREE - 3) + r * 3 + lane), lane < 3 ? 4 : 1);
      __syncwarp();
      uint32_t n = 0;
      while (!__all_sync(0xffffffffu, ld_flag(fl + (lane & 7)) == epoch) && ++n < SPIN_MAX) {}
      if (lane == 0) mbar_arrive(BAR(B_OUTOK + r));
      STAMPW(2);
      if (lane == 0) fence_async_glob();
      uint32_t si = S6 ? 0 : r, sp = 0, ph = 0;
#pragma unroll 1
      for (int u = 0; u < 10; u++) {
        mbar_wait(BAR(B_OFULL + r * 3 + si), (ph >> si) & 1u);
        if (lane == 0) {
          fence_async_smem();
#pragma unroll
          for (int j = 0; j < NOP; j++)
            asm volatile("cp.reduce.async.bulk.tensor.2d.global.shared::cta.add.bulk_group [%0, {%2, %3}], [%1];"
                       ::"l"(&P.mOut[0]), "r"(sb + OSLOT(r, si) + j * (8192 / NOP)), "r"((c + u < 10 ? c + u : c + u - 10) * 64), "r"(rb * 128 + r * 64 + j * (64 / NOP)) : "memory");
          asm volatile("cp.async.bulk.commit_group;" ::: "memory");
        }
        if (u < 4 && lane < 8)
          asm volatile("{\n.reg .b32 a;\nmapa.shared::cluster.u32 a, %0, %1;\nmbarrier.arrive.shared::cluster.b64 _, [a];\n}" ::"r"(BAR(B_QEMPTY + 2 + ((u + 2) & 3))), "r"(lane & 1) : "memory");
        if (lane == 0) {
          asm volatile("cp.async.bulk.wait_group.read 2;" ::: "memory");
          if (u > 1) mbar_arrive(BAR(B_OFREE + r * 3 + (si == 2u ? 0u : si + 1u)));
        }
        __syncwarp();
        ph ^= 1u << si;
        sp = si;
        si = si == 2u ? 0u : si + 1u;
      }
      if (lane == 0) asm volatile("cp.async.bulk.wait_group.read 0;" ::: "memory");
      STAMPW(3);
    } else if (warp == 11) {
      st_flag(&g_epoch[tile * 32 + lane], epoch);
    }
  } else {
    const int r = warp >> 2, w = warp & 3, gq = lane >> 2, tq = lane & 3;
    asm volatile("setmaxnreg.inc.sync.aligned.u32 224;");
    STAMP(4);
    uint32_t ep = ldcg32(&g_epoch[tile * 32 + lane]);
    const int b = rb * 2 + r;
    if (w == 0 && lane < 4) stg128(&g_hint[((lane >> 1) * 256 + b * 8 + c) * 8 + (lane & 1) * 4], ~0u, ~0u, ~0u, ~0u);
    const int row0 = w * 8 + gq, row1 = 56 - w * 8 + gq;
    const int rowm = ((lane & 8) ? 56 - w * 8 : w * 8) + (lane & 7);
    uint32_t q[24], qm[8], tag;
    STAMP(0);
    {
      float accQ[32], accK[64], accL[24];
      uint32_t fa[16], fb[16];
      const uint32_t xa = sb + (uint32_t)(r * 64 + rowm) * 128u + (uint32_t)(((lane >> 4) ^ lane) & 7) * 16u;
#define QKV_DM(kt, k) (mkdesc(sb + ((kt) & 3) * QST + 16384, desc_hi(2048, 512, 2)) + ((k) >> 1) * 768 + ((k) & 1) * 64)
#define QKV_DL(kt, k) (mkdesc(sb + ((kt) & 3) * QST + 40960, desc_hi(1024, 256, 3)) + ((k) >> 1) * 192 + ((k) & 1) * 32)
#define QKV_LOAD(f, kt) do { \
        mbar_wait(BAR(B_QFULL + ((kt) & 3)), ((kt) >> 2) & 1); \
        _Pragma("unroll") for (int k = 0; k < 4; k++) ldsm4(&f[4 * k], (xa ^ (k * 32)) + ((kt) & 3) * QST); } while (0)
#define QKV_MMA(f, kt, WQ, REL) do { \
        WG_FENCE(); \
        _Pragma("unroll") for (int k = 0; k < 4; k++) { \
          wg_rs48(accL, f[4 * k], f[4 * k + 1], f[4 * k + 2], f[4 * k + 3], QKV_DL(kt, k), (kt) | k); \
          if (WQ) wg_rs64(accQ, f[4 * k], f[4 * k + 1], f[4 * k + 2], f[4 * k + 3], QKV_DM(kt, k), (kt) | k); \
          wg_rs128(accK, f[4 * k], f[4 * k + 1], f[4 * k + 2], f[4 * k + 3], QKV_DM(kt, k) + 256, (kt) | k); \
          if ((k == 0 && (kt) < 8) || k == 3) WG_COMMIT(); \
          if (k == 0 && (kt) < 8) { WG_WAIT(1); REL; } \
        } } while (0)
#define QKV_STEP(f, kt, WQ, REL) do { QKV_LOAD(f, kt); QKV_MMA(f, kt, WQ, REL); } while (0)
#define Q_STEP(f, kt) do { \
        _Pragma("unroll") for (int k = 0; k < 4; k++) wg_rs64(accQ, f[4 * k], f[4 * k + 1], f[4 * k + 2], f[4 * k + 3], QKV_DM(kt, k), 1); \
        WG_COMMIT(); } while (0)
#pragma unroll 1
      for (int kt = 0; kt < 6; kt += 2) {
        QKV_STEP(fa, kt, 1, if (kt && lane == 0) mbar_arrive_pair(BAR(B_QEMPTY + ((kt - 1) & 3))));
        QKV_STEP(fb, kt + 1, 1, if (kt && lane == 0) mbar_arrive_pair(BAR(B_QEMPTY + (kt & 3))));
        if (kt == 0) {
          const int cl = min(lane & 15, 14) + (int)rank * 15, mat = cl / 10, pc = cl - mat * 10;
          const bool mn = pc < 8;
          const int pitch = mn ? 64 : 32;
          const uint8_t* wp = smem + (mn ? 16384 + mat * 4096 + (pc >> 2) * 2048 + ((pc ^ (warp >> 1)) & 3) * 16 : 40960 + mat * 1024 + ((pc ^ (warp >> 2)) & 1) * 16);
          float a[8];
#pragma unroll
          for (int i = 0; i < 8; i++) a[i] = 0.f;
#pragma unroll
          for (int u = 0; u < 5; u++) {
            const int kr = (rb >> 1) * 80 - kb0 * 64 + u * 16;
            const uint4 v = *reinterpret_cast<const uint4*>(wp + (kr >> 6) * QST + ((kr & 16) + (lane >> 4) * 8 + warp + (kr & 32) * (mn ? 6 : 3)) * pitch);
            a[0] += bf_lo(v.x); a[1] += bf_hi(v.x); a[2] += bf_lo(v.y); a[3] += bf_hi(v.y);
            a[4] += bf_lo(v.z); a[5] += bf_hi(v.z); a[6] += bf_lo(v.w); a[7] += bf_hi(v.w);
          }
          float4* dst = reinterpret_cast<float4*>(smem + OFF_PRE + warp * 1024 + lane * 32);
          dst[0] = make_float4(a[0], a[1], a[2], a[3]);
          dst[1] = make_float4(a[4], a[5], a[6], a[7]);
          __syncwarp();
          if (lane == 0) {
            mbar_arrive(BAR(B_PRE));
            mbar_arrive_pair(BAR(B_QEMPTY));
          }
          STAMP(5);
        } else if (kt == 4) {
          asm volatile("barrier.cluster.wait.acquire.aligned;" ::: "memory");
        }
      }
      uint32_t fc[16];
      QKV_STEP(fa, 6, 1, if (lane == 0) mbar_arrive_pair(BAR(B_QEMPTY + 1)));
      QKV_STEP(fb, 7, 0, if (lane == 0) mbar_arrive(BAR(B_Q23)));
      float2 s0, s1;
      uint32_t e0, e1;
#define QKV_MEAN() do { \
        mbar_wait(BAR(B_STAT), 0); \
        s0 = lds64f(sb + OFF_XST + (r * 64 + row0) * 8); \
        s1 = lds64f(sb + OFF_XST + (r * 64 + row1) * 8); \
        const uint32_t m0 = pack2(-s0.x, -s0.x), m1 = pack2(-s1.x, -s1.x); \
        const float l0 = -s0.x - bf_lo(m0), l1 = -s1.x - bf_lo(m1); \
        e0 = tq == 0 ? m0 : tq == 1 ? pack2(l0, l0) : 0u; \
        e1 = tq == 0 ? m1 : tq == 1 ? pack2(l1, l1) : 0u; } while (0)
      if (r) mbar_wait(BAR(B_XROW), 1);
      QKV_STEP(fa, 8, 0, );
      QKV_STEP(fc, 9, 0, );
      ep = (__shfl_sync(0xffffffffu, ep, 0) + 1u) & 3u;
      tag = (ep & 1u) | ((ep & 2u) << 15);
      QKV_MEAN();
      WG_FENCE();
      wg_rs48(accL, e0, e1, 0u, 0u, mkdesc(sb + OFF_PRE + 3072, desc_hi(256, 0, 3)), 1);
      wg_rs128(accK, e0, e1, 0u, 0u, mkdesc(sb + OFF_PRE + 1024, desc_hi(512, 0, 2)), 1);
      WG_COMMIT();
      if (!r && lane == 0) mbar_arrive(BAR(B_XROW));
      mbar_wait(BAR(B_Q23), 0);
      WG_WAIT(0);
      reg_fence(accK); reg_fence(accL);
      STAMP(2);
      const uint32_t km = tq == 1 ? ~TAGM : 0xffffffffu, kt1 = tq == 1 ? tag : 0u;
      const uint32_t kvo = sb + kv_addr(4 + r) + (uint32_t)rowm * 16u + (uint32_t)(lane >> 4) * 1024u;
      const float qs = 0.22360679774997896f * 1.4426950408889634f;
      const bool lo = tq < 2;
      uint32_t qj[20], kj[20];
#define KST(i)
#define QKV_OUT(mat) do { \
        const float r0 = mat == 0 ? s0.y * qs : s0.y, r1 = mat == 0 ? s1.y * qs : s1.y; \
        _Pragma("unroll") for (int t = 0; t < 10; t++) { \
          const float* a = t >= 8 ? &accL[(mat * 2 + t - 8) * 4] : mat ? &accK[(mat * 8 - 8 + t) * 4] : &accQ[t * 4]; \
          qj[2 * t] = pack2(a[0] * r0, a[1] * r0); \
          qj[2 * t + 1] = pack2(a[2] * r1, a[3] * r1); \
        } } while (0)
#define KV_OUT() do { \
        QKV_OUT(1); \
        _Pragma("unroll") for (int i = 0; i < 20; i++) kj[i] = (qj[i] & km) | kt1; \
        _Pragma("unroll") for (int t = 0; t < 10; t += 2) stsm4(kvo + t * 1024, kj[2 * t], kj[2 * t + 1], kj[2 * t + 2], kj[2 * t + 3]); \
        KST(0); \
        if (KF && !r) { fence_async_smem(); __syncwarp(); if (lane == 0) mbar_arrive(BAR(B_HST)); } \
        QKV_OUT(2); \
          \
        const uint32_t one = (tq & 1) ? 0u : 0x3f80u; \
        uint32_t vv[24]; \
        _Pragma("unroll") for (int hp = 0; hp < 2; hp++) { \
          const int j = hp * 10; \
          _Pragma("unroll") for (int i = 0; i < 4; i++) { vv[hp * 12 + i] = qj[j + i]; vv[hp * 12 + 8 + i] = qj[j + 6 + i]; } \
          vv[hp * 12 + 4] = lo ? qj[j + 4] : one; vv[hp * 12 + 5] = lo ? qj[j + 5] : one; \
          vv[hp * 12 + 6] = lo ? one : qj[j + 4]; vv[hp * 12 + 7] = lo ? one : qj[j + 5]; \
        } \
        _Pragma("unroll") for (int i = 0; i < 24; i++) vv[i] = (vv[i] & km) | kt1; \
        _Pragma("unroll") for (int t = 0; t < 6; t++) stsm4(kvo + 10240 + t * 2048, vv[4 * t], vv[4 * t + 1], vv[4 * t + 2], vv[4 * t + 3]); \
      } while (0)
      KV_OUT();
      KST(4);
      fence_async_smem();
      __syncwarp();
      if (lane == 0) mbar_arrive(BAR(B_KVOWN + r));
      KST(3);
      mbar_wait(BAR(B_STAT), 0);
      WG_FENCE();
      wg_rs64(accQ, e0, e1, 0u, 0u, mkdesc(sb + OFF_PRE, desc_hi(512, 0, 2)), 1);
      Q_STEP(fb, 7);
      Q_STEP(fa, 8);
      Q_STEP(fc, 9);
      WG_WAIT(0);
      reg_fence(accQ);
      if (lane == 0) mbar_arrive_pair(BAR(B_QEMPTY + 1));
      STAMP(1);
      QKV_OUT(0);
#pragma unroll
      for (int hp = 0; hp < 2; hp++) {
        const int j = hp * 10;
        q[hp * 12 + 0] = qj[j + 0]; q[hp * 12 + 1] = qj[j + 1]; q[hp * 12 + 2] = qj[j + 2]; q[hp * 12 + 3] = qj[j + 3];
        q[hp * 12 + 4] = lo ? qj[j + 4] : 0u; q[hp * 12 + 5] = lo ? qj[j + 5] : 0u;
        q[hp * 12 + 6] = lo ? 0u : qj[j + 4]; q[hp * 12 + 7] = lo ? 0u : qj[j + 5];
        q[hp * 12 + 8] = qj[j + 6]; q[hp * 12 + 9] = qj[j + 7]; q[hp * 12 + 10] = qj[j + 8]; q[hp * 12 + 11] = qj[j + 9];
      }
#pragma unroll
      for (int h = 0; h < 4; h++) {
        const int j = (h >> 1) * 10 + (h & 1) * 4;
        const uint32_t d0 = bfma2(q[6 * h + 4], kj[j + 4], bfma2(q[6 * h + 2], kj[j + 2], bmul2(q[6 * h], kj[j])));
        const uint32_t d1 = bfma2(q[6 * h + 5], kj[j + 5], bfma2(q[6 * h + 3], kj[j + 3], bmul2(q[6 * h + 1], kj[j + 1])));
        uint32_t u = badd2(__byte_perm(d0, d1, 0x5410), __byte_perm(d0, d1, 0x7632));
        u = badd2(u, __shfl_xor_sync(0xffffffffu, u, 1));
        u = badd2(u, __shfl_xor_sync(0xffffffffu, u, 2));
        u = tq == 2 ? u ^ 0x80008000u : 0u;
        qm[2 * h] = u & 0xffffu;
        qm[2 * h + 1] = u >> 16;
        asm volatile("" : "+r"(qm[2 * h]), "+r"(qm[2 * h + 1]));
      }
    }
    STAMP(3);
    uint32_t x0[20];
    {
      float o0[12], o1[12], o2[12], o3[12];
#pragma unroll
      for (int i = 0; i < 12; i++) o3[i] = 0.f;
      reg_fence(o3);
      float s0[32], s1[32];
      uint32_t p0[16], p1[16];
      uint32_t nk[8];
#pragma unroll
      for (int t = 0; t < 8; t++) asm("shl.b32 %0, %1, %2;" : "=r"(nk[t]) : "r"(0xffffffffu), "r"(max(((t < 4 ? row0 : row1) - 2 * tq - 8 * t + 1) * 16, 0)));
      const uint32_t seq = r ? 0x13245u : 0x01324u;
      const int nit = rb >= 2 ? 5 : 2 * rb + 1 + r;
      mbar_wait(BAR(B_KVOWN + r), 0);
      uint32_t kb = ((sb + kv_addr(4 + r)) & 0x3FFFF) >> 4, kp = kb;
      WG_FENCE();
      qk_issue<0>(s0, q, qm[0], qm[1], kb);
      WG_COMMIT();
      WG_WAIT(0);
      reg_fence(s0);
#define ATT_ITER(KIND) do { \
        ATT_STEP(KIND, 1, s1, kb, 3, o3, p1, kp, s0, p0, 1);     \
        ATT_STEP(KIND, 2, s0, kb, 0, o0, p0, kb, s1, p1, 1); \
        if (it == 2 && lane == 0) mbar_arrive_pair(BAR(B_ATT2));     \
        if (it == 3 + (XT ? 8 : 1) * r && lane < 2) mbar_arrive(BAR(B_ATT3)); \
        const int bi = it + 1 < nit ? (seq >> (4 * it + 4)) & 15 : 4; \
        const uint32_t nb = bi == 4 ? BAR(B_KVOWN) : BAR(B_KVFULL + bi), gb = it + 1 == GOW + 8 * r && it + 1 < nit ? BAR(B_GO) : BAR(B_KVOWN); \
        const bool ok = KIND == 2 || (mbar_test(nb) & mbar_test(gb)); \
        ATT_STEP(KIND, 3, s1, kb, 1, o1, p1, kb, s0, p0, 1); \
        kp = kb; \
        if (KIND == 2) { \
          WG_FENCE(); pv_issue<2, 0>(o2, p0, kp); WG_COMMIT(); WG_WAIT(1); sm_exp<KIND>(s1, p1, nk, w); \
        } else { \
          kb = ((sb + kv_addr(bi)) & 0x3FFFF) >> 4; \
          if (!ok) { mbar_wait(nb, 0); mbar_wait(gb, 0); } \
          ATT_STEP(KIND, 0, s0, kb, 2, o2, p0, kp, s1, p1, 1); \
        } } while (0)
      {
        const int it = 0;
        ATT_ITER(1);
      }
#pragma unroll 1
      for (int it = 1; it < min(nit, 4); it++) {
        if (!ETW && r == 0 && it == GOW) mbar_wait(BAR(B_GO), 0);
        if (KF && it == 1 + r) mbar_wait(BAR(B_KVFULL + 2), 0);
        if (r == 1 && it == GOIT && lane < 2) mbar_arrive(BAR(B_GO));
        ATT_ITER(0);
      }
      if (nit == 5) {
        const int it = 4;
        if (r == 1 && it == GOIT && lane < 2) mbar_arrive(BAR(B_GO));
        ATT_ITER(2);
        WG_FENCE();
        pv_issue<3, 0>(o3, p1, kp);
        WG_COMMIT();
        WG_WAIT(0);
        reg_fence(o0); reg_fence(o1); reg_fence(o2); reg_fence(o3);
      } else {
        WG_FENCE();
        pv_issue<3, 0>(o3, p1, kp);
        WG_COMMIT();
        WG_WAIT(0);
        reg_fence(o0); reg_fence(o1); reg_fence(o2); reg_fence(o3);
      }
      if (nit < 3 && lane == 0) mbar_arrive_pair(BAR(B_ATT2));
      if ((XT ? nit < 4 && !r : nit < 4 + r) && lane < 2) mbar_arrive(BAR(B_ATT3));
      if (lane == 0) mbar_arrive(BAR(B_ATTL));
      if (r == 1 && nit <= GOIT && lane < 2) mbar_arrive(BAR(B_GO));
      {
        const uint32_t e0 = 63u << 23;
        const uint32_t ba = (__float_as_uint(o0[8]) - e0) | (__float_as_uint(o0[10]) - e0) | (__float_as_uint(o2[8]) - e0) | (__float_as_uint(o2[10]) - e0);
        const uint32_t bb = (__float_as_uint(o1[0]) - e0) | (__float_as_uint(o1[2]) - e0) | (__float_as_uint(o3[0]) - e0) | (__float_as_uint(o3[2]) - e0);
        if (__builtin_expect(__any_sync(0xffffffffu, ((tq == 2 ? ba : tq == 0 ? bb : 0u) >> 30) != FORCE_SAFE), 0)) {
          const uint8_t* kv = g_kv + (ptrdiff_t)((2 * rb - 4) * 8 + c) * KVB + lane * 4;
#pragma unroll 1
          for (int h = 0; h < 4; h++) {
            uint32_t qh[6];
            float t[12];
#pragma unroll
            for (int i = 0; i < 6; i++) qh[i] = h == 0 ? q[i] : h == 1 ? q[6 + i] : h == 2 ? q[12 + i] : q[18 + i];
            safe_head(t, qh, h, kv, seq, nit, row0 - 2 * tq, row1 - 2 * tq, tq, tag);
#pragma unroll
            for (int i = 0; i < 12; i++) {
              if (h == 0) o0[i] = t[i];
              if (h == 1) o1[i] = t[i];
              if (h == 2) o2[i] = t[i];
              if (h == 3) o3[i] = t[i];
            }
          }
          __syncwarp();
        }
      }
      float inv[4][2];
      inv[0][0] = rcp(__shfl_sync(0xffffffffu, o0[8], (lane & 28) + 2));
      inv[0][1] = rcp(__shfl_sync(0xffffffffu, o0[10], (lane & 28) + 2));
      inv[1][0] = rcp(__shfl_sync(0xffffffffu, o1[0], lane & 28));
      inv[1][1] = rcp(__shfl_sync(0xffffffffu, o1[2], lane & 28));
      inv[2][0] = rcp(__shfl_sync(0xffffffffu, o2[8], (lane & 28) + 2));
      inv[2][1] = rcp(__shfl_sync(0xffffffffu, o2[10], (lane & 28) + 2));
      inv[3][0] = rcp(__shfl_sync(0xffffffffu, o3[0], lane & 28));
      inv[3][1] = rcp(__shfl_sync(0xffffffffu, o3[2], lane & 28));
      const bool lo = tq < 2;
#define OPK(dst, o, t, h) do { x0[dst] = pack2(o[4 * (t)] * inv[h][0], o[4 * (t) + 1] * inv[h][0]); x0[dst + 1] = pack2(o[4 * (t) + 2] * inv[h][1], o[4 * (t) + 3] * inv[h][1]); } while (0)
#define OPK2(dst, oa, ha, ob, hb) do { \
        const float i0 = lo ? inv[ha][0] : inv[hb][0], i1 = lo ? inv[ha][1] : inv[hb][1]; \
        x0[dst] = pack2((lo ? oa[8] : ob[0]) * i0, (lo ? oa[9] : ob[1]) * i0); \
        x0[dst + 1] = pack2((lo ? oa[10] : ob[2]) * i1, (lo ? oa[11] : ob[3]) * i1); } while (0)
      OPK(0, o0, 0, 0); OPK(2, o0, 1, 0); OPK2(4, o0, 0, o1, 1); OPK(6, o1, 1, 1); OPK(8, o1, 2, 1);
      OPK(10, o2, 0, 2); OPK(12, o2, 1, 2); OPK2(14, o2, 2, o3, 3); OPK(16, o3, 1, 3); OPK(18, o3, 2, 3);
    }
    const int bw = b * 4 + w;
    const size_t tile_off = (size_t)b * 81920 + w * 2560 + lane * 16;
    uint32_t* hint = &g_hint[b * 8 * HS + w];
    {
#pragma unroll
      for (int k = 0; k < 5; k++) {
        x0[4 * k] = tag16(x0[4 * k], tag);
        stg128(g_o + tile_off + c * 10240 + k * 512, x0[4 * k], x0[4 * k + 1], x0[4 * k + 2], x0[4 * k + 3]);
      }
      if (lane == 0) st_flag(hint + c * HS, tag);
      STAMP(6);
      uint32_t xr[20];
      mbar_wait(BAR(B_OUTOK + r), 0);
#pragma unroll
      for (int k = 0; k < 5; k++) ldsm4(&xr[4 * k], sb + (r ? 143360u : OFF_HST) + (uint32_t)rowm * 160u + (uint32_t)(lane >> 4) * 16u + k * 32);
      float acc[40];
      constexpr uint64_t HI = desc_hi(2560, 256, 3);
      const uint64_t db = mkdesc(sb + OFF_WOB, HI);
      mbar_wait(BAR(B_WOB), 0);
#pragma unroll
      for (int t = 0; t < 10; t++) {
        acc[4 * t] = bf_lo(xr[2 * t]); acc[4 * t + 1] = bf_hi(xr[2 * t]);
        acc[4 * t + 2] = bf_lo(xr[2 * t + 1]); acc[4 * t + 3] = bf_hi(xr[2 * t + 1]);
      }
      WG_FENCE();
#pragma unroll
      for (int k = 0; k < 5; k++) wg_rs80(acc, x0[4 * k], x0[4 * k + 1], x0[4 * k + 2], x0[4 * k + 3], db + k * 32, 1);
      WG_COMMIT();
      if (XT && r && lane < 2) mbar_arrive(BAR(B_ATT3));
      STAMP(7);
      uint32_t xa[6][20];
      const uint32_t ol = sb + w * 2560 + lane * 16;
#define WO_LOAD(xx, i) do { \
        _Pragma("unroll") for (int k = 0; k < 5; k++) \
          asm volatile("ld.shared.v4.u32 {%0,%1,%2,%3}, [%4];" : "=r"(xx[4 * k]), "=r"(xx[4 * k + 1]), "=r"(xx[4 * k + 2]), "=r"(xx[4 * k + 3]) \
                       : "r"(ol + (r ? 102400u : (i) < 3 ? 179200u : 107520u) + (i) * 10240 + k * 512) : "memory"); } while (0)
#define WO_MMA(xx, i) do { \
        _Pragma("unroll") for (int k = 0; k < 5; k++) wg_rs80(acc, xx[4 * k], xx[4 * k + 1], xx[4 * k + 2], xx[4 * k + 3], db + ((i) + 1) * 800 + k * 32, 1); } while (0)
#define WO_LAND(j) mbar_wait(BAR((r ? B_QFULL : B_KVFULL) + (j)), r ? (j) < 2 : 2 * rb + (j) >= 4)
#define ST8(j)
      WG_WAIT(0);
#pragma unroll
      for (int j = 0; j < 3; j++) {
        WO_LAND(j);
        ST8(j);
        WO_LOAD(xa[2 * j], 2 * j); WO_LOAD(xa[2 * j + 1], 2 * j + 1);
      }
      WO_LAND(3);
      ST8(3);
      WO_LOAD(x0, 6);
      {
        uint32_t bad = 0;
#pragma unroll
        for (int k = 0; k < 5; k++) bad |= (xa[0][4 * k] ^ tag) | (xa[1][4 * k] ^ tag) | (xa[2][4 * k] ^ tag) | (xa[3][4 * k] ^ tag) | (xa[4][4 * k] ^ tag) | (xa[5][4 * k] ^ tag) | (x0[4 * k] ^ tag);
        bad = __any_sync(0xffffffffu, (bad & TAGM) != 0u);
        if (lane < 2 - r) mbar_arrive_pair(BAR(r ? B_OL1 : B_ATT4));
        if (r && lane < 2) mbar_arrive(BAR(B_OL1L));
        uint32_t n = 0;
        while (bad && ++n < SPIN_MAX) {
          bad = 0;
#pragma unroll
          for (int i = 0; i < 6; i++) ld_tile(xa[i], g_o + tile_off, c, i + 1);
          ld_tile(x0, g_o + tile_off, c, 7);
#pragma unroll
          for (int k = 0; k < 5; k++) bad |= (xa[0][4 * k] ^ tag) | (xa[1][4 * k] ^ tag) | (xa[2][4 * k] ^ tag) | (xa[3][4 * k] ^ tag) | (xa[4][4 * k] ^ tag) | (xa[5][4 * k] ^ tag) | (x0[4 * k] ^ tag);
          bad = __any_sync(0xffffffffu, (bad & TAGM) != 0u);
        }
      }
      mbar_wait(BAR(B_WOB7), 0);
      WG_FENCE();
      WO_MMA(xa[0], 0); WO_MMA(xa[1], 1);
      WG_COMMIT();
      WO_MMA(xa[2], 2);
      WG_COMMIT();
      WG_WAIT(1);
      if (lane == 0) mbar_arrive_pair(BAR(B_WODP));
      WO_MMA(xa[3], 3); WO_MMA(xa[4], 4);
      WG_COMMIT();
      WO_MMA(xa[5], 5);
      WG_COMMIT();
      WG_WAIT(1);
      if (lane == 0) mbar_arrive_pair(BAR(B_WODP2));
      WO_MMA(x0, 6);
      WG_COMMIT();
      WG_WAIT(0);
      reg_fence(acc);
      if (S6 && lane == 0) mbar_arrive_pair(BAR(B_WOE));
      STAMP(8);
#pragma unroll
      for (int t = 0; t < 10; t++) {
        x0[2 * t] = pack2(acc[4 * t], acc[4 * t + 1]);
        x0[2 * t + 1] = pack2(acc[4 * t + 2], acc[4 * t + 3]);
      }
#pragma unroll
      for (int k = 0; k < 5; k++) {
        x0[4 * k] = tag16(x0[4 * k], tag);
        stg128(g_h + tile_off + c * 10240 + k * 512, x0[4 * k], x0[4 * k + 1], x0[4 * k + 2], x0[4 * k + 3]);
      }
      if (lane == 0) st_flag(hint + 256 * HS + c * HS, tag);
    }
    uint32_t ha[56];
    float accA[32], accB[32];
    {
      float acc[112];
      constexpr uint64_t HI = desc_hi(5120, 512, 2);
#define ST4(i)
#define ST5(i)
#define W1_ISSUE(xx, i) do { \
        const uint64_t db = mkdesc(sb + w1b_addr(i), HI); \
        mbar_wait(BAR(B_BFULL + (i)), 0); \
        WG_FENCE(); \
        _Pragma("unroll") for (int k = 0; k < 5; k++) { \
          if (S6) { \
            wg_rsa(acc, xx[4 * k], xx[4 * k + 1], xx[4 * k + 2], xx[4 * k + 3], db + k * 64, (i) | k); \
            wg_rsb(acc, xx[4 * k], xx[4 * k + 1], xx[4 * k + 2], xx[4 * k + 3], db + 1920 + k * 64, (i) | k); \
          } else wg_rs224(acc, xx[4 * k], xx[4 * k + 1], xx[4 * k + 2], xx[4 * k + 3], db + k * 64, (i) | k); \
        } \
        WG_COMMIT(); } while (0)
#define W1_STE(xx, i, REL) W1_STP(xx, i, REL, )
#define W1_STP(xx, i, REL, PRE) do { \
        ST4(i); \
        const uint64_t db = mkdesc(sb + w1b_addr(i), HI); \
        mbar_wait(BAR(B_BFULL + (i)), 0); \
        PRE; \
        WG_FENCE(); \
        _Pragma("unroll") for (int k = 0; k < 5; k++) { \
          if (S6) { \
            wg_rsa(acc, xx[4 * k], xx[4 * k + 1], xx[4 * k + 2], xx[4 * k + 3], db + k * 64, 1); \
            wg_rsb(acc, xx[4 * k], xx[4 * k + 1], xx[4 * k + 2], xx[4 * k + 3], ((i) == 5 ? mkdesc(sb + OFF_W1Y, HI) : db + 1920) + k * 64, 1); \
          } else wg_rs224(acc, xx[4 * k], xx[4 * k + 1], xx[4 * k + 2], xx[4 * k + 3], db + k * 64, 1); \
          if (k == RELK || k == 4) WG_COMMIT(); \
          if (k == RELK) { \
            WG_WAIT(1); \
            if ((i) != 1 && lane == 0) mbar_arrive_pair(BAR(B_BEMPTY - 1 + (i))); \
            REL; \
            WG_FENCE(); \
          } \
        } } while (0)
#define HT(i) ht, c, i
      const uint8_t* ht = g_h + tile_off;
      uint32_t x1[20], x2[20], x3[20];
#define H_STATS() do { \
        const uint32_t sh = __shfl_sync(0xffffffffu, __byte_perm(x0[0], x0[1], 0x5410), lane & 28); \
        const float sh0 = bf_lo(sh), sh1 = bf_hi(sh); \
        float sum0 = 0.f, sum1 = 0.f, v0 = 0.f, v1 = 0.f; \
        _Pragma("unroll") for (int t = 0; t < 10; t++) { \
          const float d0 = bf_lo(x0[2 * t]) - sh0, d1 = bf_hi(x0[2 * t]) - sh0, d2 = bf_lo(x0[2 * t + 1]) - sh1, d3 = bf_hi(x0[2 * t + 1]) - sh1; \
          sum0 += d0 + d1; \
          sum1 += d2 + d3; \
          v0 = fmaf(d1, d1, fmaf(d0, d0, v0)); \
          v1 = fmaf(d3, d3, fmaf(d2, d2, v1)); \
        } \
        { const float a = (tq & 1) ? sum0 : sum1, e = (tq & 1) ? v0 : v1; \
          sum0 = ((tq & 1) ? sum1 : sum0) + __shfl_xor_sync(0xffffffffu, a, 1); \
          v0 = ((tq & 1) ? v1 : v0) + __shfl_xor_sync(0xffffffffu, e, 1); } \
        sum0 += __shfl_xor_sync(0xffffffffu, sum0, 2); \
        v0 += __shfl_xor_sync(0xffffffffu, v0, 2); \
        const float mu = sum0 * (1.f / 80.f); \
        hst = make_float2((tq ? sh1 : sh0) + mu, tag32(fmaxf(fmaf(-mu, sum0, v0), 0.f), ep)); \
        if (HF != 1) H_PUB(); } while (0)
#define H_PUB() do { if (tq < 2) g_hstat[(bw * 8 + c) * 16 + gq + tq * 8] = hst; } while (0)
#define H_FIN() do { fence_async_smem(); __syncwarp(); if (lane == 0) mbar_arrive(BAR(B_HST + r)); } while (0)
#define H_STAGE() do { \
        const uint32_t hs = sb + OFF_HST + (uint32_t)(r * 64 + rowm) * 160u + (uint32_t)(lane >> 4) * 16u; \
        mbar_wait(BAR(B_ATTL), 0); \
        _Pragma("unroll") for (int k = 0; k < 5; k++) stsm4(hs + k * 32, x0[4 * k], x0[4 * k + 1], x0[4 * k + 2], x0[4 * k + 3]); \
        if (!HF) H_FIN(); } while (0)
      float2 hst;
      W1_ISSUE(x0, 0);
      uint32_t ready = 0;
      const uint32_t* hh = hint + 256 * HS + ((c + lane) & 7) * HS;
      if (EARL) {
        WG_WAIT(0);
        if (lane == 0) mbar_arrive_pair(BAR(B_BEMPTY));
      }
      probe_wait(ready, 1, hh, tag);
      ld_tile(x1, HT(1));
      probe_wait(ready, 2, hh, tag);
      ld_tile(x2, HT(2));
      probe_wait(ready, 3, hh, tag);
      ld_tile(x3, HT(3));
      STAMP(9);
      WG_WAIT(0);
      if (!EARL && lane == 0) mbar_arrive_pair(BAR(B_BEMPTY));
      H_STAGE();
      H_STATS();
      uint2 hs[4];
      const float2* hp = &g_hstat[(bw * 8 + tq * 2) * 16 + gq];
      fix_tile(x1, HT(1), tag);
      STAMP(10);
      W1_STE(x1, 1, H_FIN(); H_PUB(); ld_tile(x0, HT(4)));
      fix_tile(x2, HT(2), tag);
      W1_STE(x2, 2, ld_tile(x1, HT(5)));
      fix_tile(x3, HT(3), tag);
      W1_STE(x3, 3, );
      W1_STP(x0, 4, ld_tile(x3, HT(7)), fix_tile(x0, HT(4), tag); fix_tile(x1, HT(5), tag); ld_tile(x2, HT(6)));
      hs[0] = ldcg64(hp); hs[1] = ldcg64(hp + 16); hs[2] = ldcg64(hp + 8); hs[3] = ldcg64(hp + 24);
      W1_STE(x1, 5, );
      W1_STP(x2, 6, , fix_tile(x2, HT(6), tag); fix_tile(x3, HT(7), tag));
      {
        uint32_t n = 0;
        while (__any_sync(0xffffffffu, (((hs[0].y ^ ep) | (hs[1].y ^ ep) | (hs[2].y ^ ep) | (hs[3].y ^ ep)) & 3u) != 0u) && ++n < SPIN_MAX) {
          hs[0] = ldcg64(hp); hs[1] = ldcg64(hp + 16); hs[2] = ldcg64(hp + 8); hs[3] = ldcg64(hp + 24);
        }
      }
      float mean0, mean1, rs0, rs1;
      {
        const float a0 = __uint_as_float(hs[0].x), a1 = __uint_as_float(hs[1].x), b0 = __uint_as_float(hs[2].x), b1 = __uint_as_float(hs[3].x);
        float t0 = a0 + a1, t1 = b0 + b1;
        t0 += __shfl_xor_sync(0xffffffffu, t0, 1);
        t1 += __shfl_xor_sync(0xffffffffu, t1, 1);
        t0 += __shfl_xor_sync(0xffffffffu, t0, 2);
        t1 += __shfl_xor_sync(0xffffffffu, t1, 2);
        mean0 = t0 * 0.125f;
        mean1 = t1 * 0.125f;
        {
          const uint32_t m0 = pack2(-mean0, -mean0), m1 = pack2(-mean1, -mean1);
          const float l0 = -mean0 - bf_lo(m0), l1 = -mean1 - bf_lo(m1);
          const uint32_t e0 = tq == 0 ? m0 : tq == 1 ? pack2(l0, l0) : 0u, e1 = tq == 0 ? m1 : tq == 1 ? pack2(l1, l1) : 0u;
          const uint64_t db = mkdesc(sb + w1b_addr(7), HI);
          mbar_wait(BAR(B_CS1), 1);
          WG_FENCE();
          if (S6) {
            wg_rsa(acc, e0, e1, 0u, 0u, mkdesc(sb + OFF_W1X, desc_hi(512, 0, 2)), 1);
            wg_rsb(acc, e0, e1, 0u, 0u, mkdesc(sb + OFF_W1X + 3072, desc_hi(512, 0, 2)), 1);
          } else wg_rs224(acc, e0, e1, 0u, 0u, mkdesc(sb + OFF_W1X, desc_hi(512, 0, 2)), 1);
          WG_COMMIT();
          WG_WAIT(1);
          if (lane == 0) mbar_arrive_pair(BAR(B_BEMPTY + 6));
          ST4(7);
          mbar_wait(BAR(B_BFULL + 7), 0);
          if (T2 && PAUSE == 1 && !r) asm volatile("bar.sync 4, 256;" ::: "memory");
          WG_FENCE();
#pragma unroll
          for (int k = 0; k < 5; k++) {
            if (S6) {
              wg_rsa(acc, x3[4 * k], x3[4 * k + 1], x3[4 * k + 2], x3[4 * k + 3], db + k * 64, 1);
              wg_rsb(acc, x3[4 * k], x3[4 * k + 1], x3[4 * k + 2], x3[4 * k + 3], db + 1920 + k * 64, 1);
            } else wg_rs224(acc, x3[4 * k], x3[4 * k + 1], x3[4 * k + 2], x3[4 * k + 3], db + k * 64, 1);
          }
          WG_COMMIT();
        }
        float u0 = __uint_as_float(hs[0].y) + __uint_as_float(hs[1].y) + 80.f * ((a0 - mean0) * (a0 - mean0) + (a1 - mean0) * (a1 - mean0));
        float u1 = __uint_as_float(hs[2].y) + __uint_as_float(hs[3].y) + 80.f * ((b0 - mean1) * (b0 - mean1) + (b1 - mean1) * (b1 - mean1));
        u0 += __shfl_xor_sync(0xffffffffu, u0, 1);
        u1 += __shfl_xor_sync(0xffffffffu, u1, 1);
        u0 += __shfl_xor_sync(0xffffffffu, u0, 2);
        u1 += __shfl_xor_sync(0xffffffffu, u1, 2);
        rs0 = 0.5f * rsqrtf(u0 * (1.f / 640.f) + 1e-5f);
        rs1 = 0.5f * rsqrtf(u1 * (1.f / 640.f) + 1e-5f);
      }
      WG_WAIT(0);
      reg_fence(acc);
      if (T2 && !S6) { if (lane < 2) mbar_arrive(BAR(B_BEMPTY + 7)); }
      else if (lane == 0) mbar_arrive_pair(BAR(B_BEMPTY + 7));
      STAMP(11);
      if (PAUSE == 2 && !r) asm volatile("bar.sync 4, 256;" ::: "memory");
      if (ILV) mbar_wait(BAR(B_W2FULL), 0);
#pragma unroll
      for (int t = 0; t < 28; t++) {
        const float h0 = acc[4 * t] * rs0, h1 = acc[4 * t + 1] * rs0, h2 = acc[4 * t + 2] * rs1, h3 = acc[4 * t + 3] * rs1;
        ha[2 * t] = pack2(fmaf(h0, tanh_fast(h0), h0), fmaf(h1, tanh_fast(h1), h1));
        ha[2 * t + 1] = pack2(fmaf(h2, tanh_fast(h2), h2), fmaf(h3, tanh_fast(h3), h3));
        if (t >= 24 && (c & 3) == 3) ha[2 * t] = ha[2 * t + 1] = 0u;
        if (ILV && (t + 1) % (2 * ILV) == 0) {
          WG_FENCE();
#pragma unroll
          for (int k = (t + 1) / 2 - ILV; k < (t + 1) / 2; k++) wg_rs64(accA, ha[4 * k], ha[4 * k + 1], ha[4 * k + 2], ha[4 * k + 3], mkdesc(sb, desc_hi(28672, 1024, 1)) + k * 128, k);
        }
      }
      if (ILV) WG_COMMIT();
      if (PAUSE && r) asm volatile("bar.arrive 4, 256;" ::: "memory");
    }
    STAMP(12);
    {
      constexpr uint64_t HI = desc_hi(28672, 1024, 1);
      const uint32_t ost = sb + (r ? 201728u : OFF_OST) + (uint32_t)w * 2048u;
      const uint32_t osw = ost + (uint32_t)(lane & 15) * 128u + (uint32_t)(((lane >> 4) ^ lane) & 7) * 16u;
      uint32_t so = r * 8192;
#define W2_ISSUE(acc, u) do { \
        mbar_wait(BAR((u) < 5 ? B_W2FULL + (u) : B_BFULL - 5 + (u)), (u) >= (C8 == 3 ? 4 : 5)); \
        const uint64_t db = mkdesc(sb + ((u) < 6 ? (u) : (u) - 6) * 28672, HI); \
        WG_FENCE(); \
        _Pragma("unroll") for (int k = 0; k < 14; k++) wg_rs64(acc, ha[4 * k], ha[4 * k + 1], ha[4 * k + 2], ha[4 * k + 3], db + k * 128, k); \
        WG_COMMIT(); } while (0)
#define W2_OUT(a, u) do { \
        reg_fence(a); \
        if (lane == 0) { \
          if ((u) < 4) mbar_arrive_pair(BAR(B_QEMPTY + 2 + (((u) + 2) & 3))); \
          asm volatile("cp.async.bulk.wait_group.read 2;" ::: "memory"); \
        } \
        __syncwarp(); \
        _Pragma("unroll") for (int t = 0; t < 8; t += 2) \
          stsm4((osw ^ (t * 16)) + so, pack2(a[4 * t], a[4 * t + 1]), pack2(a[4 * t + 2], a[4 * t + 3]), pack2(a[4 * t + 4], a[4 * t + 5]), pack2(a[4 * t + 6], a[4 * t + 7])); \
        fence_async_smem(); \
        __syncwarp(); \
        if (lane == 0) \
          asm volatile("cp.reduce.async.bulk.tensor.3d.global.shared::cta.add.bulk_group [%0, {%2, %3, %4}], [%1];\ncp.async.bulk.commit_group;" \
                       ::"l"(&P.mOut[w]), "r"(ost + so), "r"(min((uint32_t)(c + (u)) * 64u, (uint32_t)(c + (u)) * 64u - 640u)), "r"(b * 64 + w * 8), "r"(0) : "memory"); \
        so = so == 16384u ? 0u : so + 8192u; } while (0)
#define ST12(i)
      if (!ILV) W2_ISSUE(accA, 0);
      mbar_wait(BAR(B_OUTOK), XT);
      mbar_wait(BAR(B_OUTOK + r), XT);
      if (ROLL != 3) fence_async_glob();
      ST12(19);
#define W2_H(acc, k) wg_rs64(acc, ha[4 * (k)], ha[4 * (k) + 1], ha[4 * (k) + 2], ha[4 * (k) + 3], db + (k) * 128, k)
#define W2_ST(a, t) stsm4((osv ^ ((t) * 16)) + OSLOT(r, si), pack2(a[4 * (t)], a[4 * (t) + 1]), pack2(a[4 * (t) + 2], a[4 * (t) + 3]), pack2(a[4 * (t) + 4], a[4 * (t) + 5]), pack2(a[4 * (t) + 6], a[4 * (t) + 7]))
#define W2_FIN() do { \
        __syncwarp(); \
        asm volatile("{\n.reg .pred p;\nsetp.eq.u32 p, %1, 0;\n@p mbarrier.arrive.shared::cta.b64 _, [%0];\n}" ::"r"(BAR(B_OFULL + r * 3 + si)), "r"(lane) : "memory"); \
        ph ^= 1u << si; \
        si = si == 2u ? 0u : si + 1u; } while (0)
#define W2_STEP(acc, u, a, PEND) do { \
        mbar_wait(BAR((u) < 5 ? B_W2FULL + (u) : B_BFULL - 5 + (u)), (u) >= 5); \
        mbar_wait(BAR(B_OFREE + r * 3 + si), (ph >> si) & 1u); \
        const uint64_t db = mkdesc(sb + ((u) < 6 ? (u) : (u) - 6) * 28672, HI); \
        WG_FENCE(); \
        W2_H(acc, 0); \
        if (RK > 1) W2_H(acc, 1); \
        if (PEND) { WG_COMMIT(); WG_WAIT(1); } \
        reg_fence(a); \
        W2_ST(a, 0); W2_H(acc, RK); W2_ST(a, 2); W2_H(acc, RK + 1); W2_ST(a, 4); W2_H(acc, RK + 2); W2_ST(a, 6); \
        W2_FIN(); \
        _Pragma("unroll") for (int k = RK + 3; k < 14; k++) W2_H(acc, k); \
        WG_COMMIT(); } while (0)
      const uint32_t osv = sb + (uint32_t)rowm * 128u + (uint32_t)(((lane >> 4) ^ lane) & 7) * 16u;
      uint32_t si = S6 ? 0 : r, ph = 7u;
      if (S6) mbar_wait(BAR(B_BEMPTY + (r ? 2 : 5)), 0);
      else if (!r) mbar_wait(BAR(B_BEMPTY + 7), 0);
      WG_WAIT(0);
#pragma unroll 1
      for (int u = 1; u < 9; u += 2) {
        if (!S6 && u == 3) mbar_wait(BAR(B_BEMPTY + 7), 0);
        W2_STEP(accB, u, accA, 0);
        ST12(19 + u);
        W2_STEP(accA, u + 1, accB, 1);
        ST12(20 + u);
        WG_WAIT(0);
      }
      W2_STEP(accB, 9, accA, 0);
      ST12(28);
      mbar_wait(BAR(B_OFREE + r * 3 + si), (ph >> si) & 1u);
      WG_WAIT(0);
      reg_fence(accB);
      W2_ST(accB, 0); W2_ST(accB, 2); W2_ST(accB, 4); W2_ST(accB, 6);
      W2_FIN();
      ST12(29);
      STAMP(15);
      if (lane == 0) asm volatile("cp.async.bulk.wait_group.read 0;" ::: "memory");
      STAMP(17);
    }
  }
}

typedef CUresult (*EncodeFn)(CUtensorMap*, CUtensorMapDataType, cuuint32_t, void*, const cuuint64_t*, const cuuint64_t*, const cuuint32_t*,
                             const cuuint32_t*, CUtensorMapInterleave, CUtensorMapSwizzle, CUtensorMapL2promotion, CUtensorMapFloatOOBfill);

static void make_map(EncodeFn enc, CUtensorMap* m, const void* p, int nd, const cuuint64_t* dims, const cuuint64_t* strides, const cuuint32_t* box,
                     CUtensorMapSwizzle sw) {
  const cuuint32_t es[5] = {1, 1, 1, 1, 1};
  enc(m, CU_TENSOR_MAP_DATA_TYPE_BFLOAT16, (cuuint32_t)nd, const_cast<void*>(p), dims, strides, box, es, CU_TENSOR_MAP_INTERLEAVE_NONE, sw,
      CU_TENSOR_MAP_L2_PROMOTION_L2_128B, CU_TENSOR_MAP_FLOAT_OOB_FILL_NONE);
}

extern "C" void kernel_launch(void* const* d_in, const int* in_sizes, int n_in, void* d_out, int out_size) {
  (void)in_sizes; (void)n_in; (void)out_size;
  static EncodeFn enc = nullptr;
  if (!enc) {
    void* f = nullptr;
    cudaDriverEntryPointQueryResult qr;
    cudaGetDriverEntryPoint("cuTensorMapEncodeTiled", &f, cudaEnableDefault, &qr);
    enc = (EncodeFn)f;
    cudaFuncSetAttribute(fused_block_kernel, cudaFuncAttributeMaxDynamicSharedMemorySize, (int)SMEM_BYTES);
  }
  Params P;
  P.x = (const __nv_bfloat16*)d_in[0];
  P.wqkv = (const __nv_bfloat16*)d_in[1];
  P.wo = (const __nv_bfloat16*)d_in[2];
  P.w1 = (const __nv_bfloat16*)d_in[4];
  P.w2 = (const __nv_bfloat16*)d_in[5];
  P.out = (__nv_bfloat16*)d_out;
  for (int k = 0; k < 64; k++) {
    const int c = k < 4 ? k + 4 : k < 36 ? (k - 4) >> 3 : (k * 37 - 308) >> 8;
    const int g = k < 4 ? 0 : k < 36 ? (k - 1) & 7 : k - 33 - 7 * ((k * 37 - 1258) >> 8);
    reinterpret_cast<uint8_t*>(P.map)[k] = (uint8_t)(c + 8 * g);
  }
  { const cuuint64_t d[2] = {640, 2048}, s[1] = {1280}; const cuuint32_t b[2] = {64, 128}; make_map(enc, &P.mX, P.x, 2, d, s, b, CU_TENSOR_MAP_SWIZZLE_128B); }
  { const cuuint64_t d[2] = {640, 2048}, s[1] = {1280}; const cuuint32_t b[2] = {80, 64}; make_map(enc, &P.mXr, P.x, 2, d, s, b, CU_TENSOR_MAP_SWIZZLE_NONE); }
  for (int i = 0; i < 2; i++) {
    const cuuint64_t d[4] = {32, 640, ALN ? 20 : 19, 3}, s[3] = {3840, 64, 1280};
    const cuuint32_t b[4] = {32, 32, 2, 3};
    make_map(enc, &P.mWqM[i], P.wqkv + 16 * i, 4, d, s, b, CU_TENSOR_MAP_SWIZZLE_64B);
  }
  { const cuuint64_t d[4] = {16, 640, 40, 3}, s[3] = {3840, 32, 1280}; const cuuint32_t b[4] = {16, 32, 1, 3}; make_map(enc, &P.mWqL, P.wqkv, 4, d, s, b, CU_TENSOR_MAP_SWIZZLE_32B); }
  { const cuuint64_t d[3] = {16, 640, 40}, s[2] = {1280, 32}; const cuuint32_t b[3] = {16, 80, 5}; make_map(enc, &P.mWo, P.wo, 3, d, s, b, CU_TENSOR_MAP_SWIZZLE_32B); }
  { const cuuint64_t d[3] = {32, 640, 54}, s[2] = {3456, 64}; const cuuint32_t b[3] = {32, 80, 4}; make_map(enc, &P.mW1a, P.w1, 3, d, s, b, CU_TENSOR_MAP_SWIZZLE_64B); }
  { const cuuint64_t d[3] = {32, 640, 54}, s[2] = {3456, 64}; const cuuint32_t b[3] = {32, 80, 3}; make_map(enc, &P.mW1b, P.w1, 3, d, s, b, CU_TENSOR_MAP_SWIZZLE_64B); }
  { const cuuint64_t d[2] = {640, 1728}, s[1] = {1280}; const cuuint32_t b[2] = {64, 112}; make_map(enc, &P.mW2, P.w2, 2, d, s, b, CU_TENSOR_MAP_SWIZZLE_128B); }
  { const cuuint64_t d[2] = {640, 2048}, s[1] = {1280}; const cuuint32_t b[2] = {80, 64}; make_map(enc, &P.mOutH, P.out, 2, d, s, b, CU_TENSOR_MAP_SWIZZLE_NONE); }
  for (int w = 0; w < (SLIM ? 0 : 4); w++) {
    const cuuint64_t d[3] = {640, 2048, 2}, s[2] = {1280, (cuuint64_t)(56 - 16 * w) * 1280};
    const cuuint32_t b[3] = {64, 8, 2};
    make_map(enc, &P.mOut[w], P.out, 3, d, s, b, CU_TENSOR_MAP_SWIZZLE_128B);
  }
  { const cuuint64_t d[2] = {640, 2048}, s[1] = {1280}; const cuuint32_t b[2] = {64, 64 / NOP}; make_map(enc, &P.mOut[0], P.out, 2, d, s, b, CU_TENSOR_MAP_SWIZZLE_128B); }
  fused_block_kernel<<<128, 384, SMEM_BYTES, cudaStreamPerThread>>>(P);
}
```
